```python
import torch

def _softmax(x, axis=-1):
    return torch.softmax(x, dim=axis)
def _gelu(x):
    return torch.nn.functional.gelu(x, approximate="tanh")
def _silu(x):
    return torch.nn.functional.silu(x)
def _sigmoid(x):
    return torch.sigmoid(x)
def _layernorm(x, axis=-1, eps=1e-5):
    m = x.mean(dim=axis, keepdim=True)
    v = x.var(dim=axis, keepdim=True, unbiased=False)
    return (x - m) / torch.sqrt(v + eps)
def _scatter_add(tgt, idx, src, axis=0):
    return tgt.clone().index_add_(axis, idx, src)
def _segment_sum(src, seg, n):
    out = torch.zeros((n,) + src.shape[1:], dtype=src.dtype)
    return out.index_add_(0, seg, src)
def _pad(x, pw):
    flat = tuple(v for pair in reversed(pw) for v in pair)
    return torch.nn.functional.pad(x, flat)

kernel_name = 'interleave_layers__sliding_local_dilated__glu_gated_bilinear__prompt'

def setup_inputs():

    _w = (lambda a: (lambda t: t.to(torch.bfloat16) if t.is_floating_point() else t)(torch.as_tensor(a)))
    def _A_setup():
        B, S, D = 1, 2048, 512
        return {
            "x": _w((lambda *s: torch.randn(*s, dtype=torch.bfloat16) * 0.05)(B, S, D)),
            "wqkv": _w((lambda *s: torch.randn(*s, dtype=torch.bfloat16) * 0.05)(D, 3 * D)),
            "wo": _w((lambda *s: torch.randn(*s, dtype=torch.bfloat16) * 0.05)(D, D)),
        }
    _A_in = _A_setup()

    def _B_setup():
        B, S, D, F = 1, 2048, 512, 1792
        return {
            "x": _w((lambda *s: torch.randn(*s, dtype=torch.bfloat16) * 0.05)(B, S, D)),
            "w_gate": _w((lambda *s: torch.randn(*s, dtype=torch.bfloat16) * 0.8)(D, F) * (D ** -0.5)),
            "w_up": _w((lambda *s: torch.randn(*s, dtype=torch.bfloat16) * 0.8)(D, F) * (D ** -0.5)),
            "w_down": _w((lambda *s: torch.randn(*s, dtype=torch.bfloat16) * 0.8)(F, D) * (F ** -0.5)),
        }
    _B_in = _B_setup()

    return {
        "A_x": _A_in["x"],
        "A_wqkv": _A_in["wqkv"],
        "A_wo": _A_in["wo"],
        "B_x": _B_in["x"],
        "B_w_gate": _B_in["w_gate"],
        "B_w_up": _B_in["w_up"],
        "B_w_down": _B_in["w_down"],
    }

def reference(A_x, A_wqkv, A_wo, B_x, B_w_gate, B_w_up, B_w_down):
    def _A_ref(x, wqkv, wo):
        B, S, D = x.shape
        H = 32; Dh = D // H
        W, dil = 8, 2
        qkv = (lambda x, *d: x.permute(*d))((x @ wqkv).reshape(B, S, 3, H, Dh), 2, 0, 3, 1, 4)
        q, k, v = qkv[0], qkv[1], qkv[2]
        scale = Dh ** -0.5
        pos = torch.arange(S)
        off = torch.arange(W) * dil
        idx = pos[:, None] - off[None, :]
        mask = idx >= 0
        idx_c = torch.where(mask, idx, 0).reshape(-1)
        kg = k[:, :, idx_c, :].reshape(B, H, S, W, Dh)
        vg = v[:, :, idx_c, :].reshape(B, H, S, W, Dh)
        logits = torch.einsum("bhsd,bhswd->bhsw", q, kg) * scale
        logits = torch.where(mask[None, None, :, :], logits, -1e9)
        attn = _softmax(logits, axis=-1)
        o = torch.einsum("bhsw,bhswd->bhsd", attn, vg)
        return (lambda x, *d: x.permute(*d))(o, 0, 2, 1, 3).reshape(B, S, D) @ wo

    def _B_ref(x, w_gate, w_up, w_down):
        g = torch.einsum("bsd,df->bsf", x, w_gate)
        u = torch.einsum("bsd,df->bsf", x, w_up)
        h = g * u
        return torch.einsum("bsf,fd->bsd", h, w_down)

    x = A_x
    x = x + _A_ref(_layernorm(x, axis=-1), A_wqkv, A_wo)
    x = x + _B_ref(_layernorm(x, axis=-1), B_w_gate, B_w_up, B_w_down)
    x = x + _A_ref(_layernorm(x, axis=-1), A_wqkv, A_wo)
    x = x + _B_ref(_layernorm(x, axis=-1), B_w_gate, B_w_up, B_w_down)
    return x
```

```cpp
#include <cuda_runtime.h>
#include <cuda_bf16.h>
#include <cuda.h>
#include <stdint.h>

namespace {

constexpr int NTHREADS = 384;
constexpr int GRAN = 8192;
constexpr int NGRAN = 12;
constexpr int SM_AREG = NGRAN * GRAN;
constexpr int SM_MISC = SM_AREG + 131072;
constexpr int SM_TSTAT = SM_MISC + 256;
constexpr int SMEM_BYTES = SM_TSTAT + 2048;
constexpr int BAR_FULL = 0, BAR_EMPTY = 96, BAR_HRECV = 192, BAR_HREADY = 208, BAR_TSTAT = 224;
constexpr int AR_X = 32768, AR_KV = 49152;

__device__ uint4 g_xn[16 * 8 * 32 * 32];
__device__ uint4 g_xraw[16 * 8 * 32 * 32];
__device__ uint4 g_o[16 * 8 * 32 * 32];
__device__ uint4 g_stats[16 * 8 * 8 * 8];
__device__ uint4 g_halo[2 * 16 * 8 * 8 * 32];
__device__ uint4 g_part[16 * 4 * 2 * 4 * 2 * 16 * 32];

#define OPAQUE(x) asm volatile("" : "+r"(x))
#define PHASE_VARS                                                                                   \
  int tid_ = threadIdx.x, bid_ = blockIdx.x;                                                         \
  OPAQUE(tid_); OPAQUE(bid_);                                                                        \
  const int lane = tid_ & 31, warp = tid_ >> 5, g = warp >> 2, w = warp & 3, t128 = tid_ & 127;      \
  const int qr = lane >> 2, qc = lane & 3, slab = warp;                                              \
  const int c = bid_ >> 3, j = bid_ & 7, ca = j >> 1, cbit = j & 1;                                  \
  const uint32_t areg = sbase + SM_AREG + g * 65536;                                                 \
  (void)w; (void)t128; (void)qr; (void)qc; (void)slab; (void)c; (void)ca; (void)cbit; (void)areg; (void)lane
#define STOP_AT(n)
#define PSTOP_AT(n)

__device__ __forceinline__ uint32_t smem_u32(const void* p) { return (uint32_t)__cvta_generic_to_shared(p); }
__device__ __forceinline__ void mbar_init(uint32_t bar, uint32_t cnt) {
  asm volatile("mbarrier.init.shared::cta.b64 [%0], %1;" ::"r"(bar), "r"(cnt) : "memory");
}
__device__ __forceinline__ void mbar_expect_tx(uint32_t bar, uint32_t bytes) {
  asm volatile("mbarrier.arrive.expect_tx.shared::cta.b64 _, [%0], %1;" ::"r"(bar), "r"(bytes) : "memory");
}
__device__ __forceinline__ void mbar_arrive(uint32_t bar) {
  asm volatile("mbarrier.arrive.shared::cta.b64 _, [%0];" ::"r"(bar) : "memory");
}
__device__ __forceinline__ void mbar_arrive_remote(uint32_t cluster_addr) {
  asm volatile("mbarrier.arrive.relaxed.cluster.shared::cluster.b64 _, [%0];" ::"r"(cluster_addr) : "memory");
}
__device__ __forceinline__ bool mbar_try(uint32_t bar, uint32_t parity) {
  uint32_t ok;
  asm volatile("{\n.reg .pred p;\nmbarrier.try_wait.parity.shared::cta.b64 p, [%1], %2;\nselp.u32 %0, 1, 0, p;\n}"
               : "=r"(ok) : "r"(bar), "r"(parity) : "memory");
  return ok != 0;
}
__device__ __forceinline__ bool mbar_try_cluster(uint32_t bar, uint32_t parity) {
  uint32_t ok;
  asm volatile("{\n.reg .pred p;\nmbarrier.try_wait.parity.acquire.cluster.shared::cta.b64 p, [%1], %2;\nselp.u32 %0, 1, 0, p;\n}"
               : "=r"(ok) : "r"(bar), "r"(parity) : "memory");
  return ok != 0;
}
constexpr uint32_t SPIN_LIMIT = 1u << 21;
__device__ __forceinline__ void mbar_wait(uint32_t bar, uint32_t parity, uint32_t& n) {
  while (!mbar_try(bar, parity)) { if (++n > SPIN_LIMIT) break; }
}
__device__ __forceinline__ void mbar_wait_cluster(uint32_t bar, uint32_t parity, uint32_t& n) {
  while (!mbar_try_cluster(bar, parity)) { if (++n > SPIN_LIMIT) break; }
}
__device__ __forceinline__ uint32_t mapa(uint32_t addr, uint32_t rank) {
  uint32_t r;
  asm volatile("mapa.shared::cluster.u32 %0, %1, %2;" : "=r"(r) : "r"(addr), "r"(rank));
  return r;
}
__device__ __forceinline__ void cluster_sync_all() {
  asm volatile("barrier.cluster.arrive.release.aligned;\nbarrier.cluster.wait.acquire.aligned;" ::: "memory");
}
__device__ __forceinline__ void bar_consumers(int id) { asm volatile("bar.sync %0, 256;" ::"r"(id) : "memory"); }

__device__ __forceinline__ void tma_2d(uint32_t dst, const CUtensorMap* m, uint32_t bar, int c0, int c1) {
  asm volatile("cp.async.bulk.tensor.2d.shared::cluster.global.mbarrier::complete_tx::bytes [%0], [%1, {%3, %4}], [%2];"
               ::"r"(dst), "l"(m), "r"(bar), "r"(c0), "r"(c1) : "memory");
}
__device__ __forceinline__ void tma_3d(uint32_t dst, const CUtensorMap* m, uint32_t bar, int c0, int c1, int c2) {
  asm volatile("cp.async.bulk.tensor.3d.shared::cluster.global.mbarrier::complete_tx::bytes [%0], [%1, {%3, %4, %5}], [%2];"
               ::"r"(dst), "l"(m), "r"(bar), "r"(c0), "r"(c1), "r"(c2) : "memory");
}
__device__ __forceinline__ void tma_4d(uint32_t dst, const CUtensorMap* m, uint32_t bar, int c0, int c1, int c2, int c3) {
  asm volatile("cp.async.bulk.tensor.4d.shared::cluster.global.mbarrier::complete_tx::bytes [%0], [%1, {%3, %4, %5, %6}], [%2];"
               ::"r"(dst), "l"(m), "r"(bar), "r"(c0), "r"(c1), "r"(c2), "r"(c3) : "memory");
}
__device__ __forceinline__ void l2_prefetch(const void* p, uint32_t bytes) {
  asm volatile("cp.async.bulk.prefetch.L2.global [%0], %1;" ::"l"(p), "r"(bytes) : "memory");
}

__device__ __forceinline__ uint4 ld_ll(const uint4* p) {
  uint4 v;
  asm volatile("ld.relaxed.gpu.global.v4.u32 {%0,%1,%2,%3}, [%4];" : "=r"(v.x), "=r"(v.y), "=r"(v.z), "=r"(v.w) : "l"(p) : "memory");
  return v;
}
__device__ __forceinline__ void st_ll(uint4* p, uint4 v) {
  asm volatile("st.relaxed.gpu.global.v4.u32 [%0], {%1,%2,%3,%4};" ::"l"(p), "r"(v.x), "r"(v.y), "r"(v.z), "r"(v.w) : "memory");
}
__device__ __forceinline__ uint4 lds128(uint32_t a) {
  uint4 v;
  asm volatile("ld.shared.v4.u32 {%0,%1,%2,%3}, [%4];" : "=r"(v.x), "=r"(v.y), "=r"(v.z), "=r"(v.w) : "r"(a) : "memory");
  return v;
}
__device__ __forceinline__ void sts128(uint32_t a, uint4 v) {
  asm volatile("st.shared.v4.u32 [%0], {%1,%2,%3,%4};" ::"r"(a), "r"(v.x), "r"(v.y), "r"(v.z), "r"(v.w) : "memory");
}
__device__ __forceinline__ void st_async128(uint32_t cluster_addr, uint4 v, uint32_t cluster_bar) {
  asm volatile("st.async.weak.shared::cluster.mbarrier::complete_tx::bytes.v4.b32 [%0], {%1,%2,%3,%4}, [%5];"
               ::"r"(cluster_addr), "r"(v.x), "r"(v.y), "r"(v.z), "r"(v.w), "r"(cluster_bar) : "memory");
}
__device__ __forceinline__ uint32_t pack2(float lo, float hi) {
  uint32_t r;
  asm("cvt.rn.bf16x2.f32 %0, %1, %2;" : "=r"(r) : "f"(hi), "f"(lo));
  return r;
}
__device__ __forceinline__ float bf_lo(uint32_t w) { return __uint_as_float(w << 16); }
__device__ __forceinline__ float bf_hi(uint32_t w) { return __uint_as_float(w & 0xffff0000u); }
__device__ __forceinline__ uint32_t set_tag(uint32_t w, uint32_t tag) { return (w & ~1u) | tag; }
__device__ __forceinline__ uint32_t movm(uint32_t a) {
  uint32_t d;
  asm volatile("movmatrix.sync.aligned.m8n8.trans.b16 %0, %1;" : "=r"(d) : "r"(a));
  return d;
}
__device__ __forceinline__ void mma16816(float (&d)[4], const uint4& a, uint32_t b0, uint32_t b1) {
  asm volatile("mma.sync.aligned.m16n8k16.row.col.f32.bf16.bf16.f32 {%0,%1,%2,%3}, {%4,%5,%6,%7}, {%8,%9}, {%0,%1,%2,%3};"
               : "+f"(d[0]), "+f"(d[1]), "+f"(d[2]), "+f"(d[3])
               : "r"(a.x), "r"(a.y), "r"(a.z), "r"(a.w), "r"(b0), "r"(b1));
}
__device__ __forceinline__ void wg_fence() { asm volatile("wgmma.fence.sync.aligned;" ::: "memory"); }
__device__ __forceinline__ void wg_commit() { asm volatile("wgmma.commit_group.sync.aligned;" ::: "memory"); }
template <int N> __device__ __forceinline__ void wg_wait() { asm volatile("wgmma.wait_group.sync.aligned %0;" ::"n"(N) : "memory"); }
__device__ __forceinline__ uint64_t make_desc(uint32_t addr, uint32_t lbo, uint32_t sbo, uint32_t swz) {
  return (uint64_t)((addr & 0x3FFFF) >> 4) | ((uint64_t)(lbo >> 4) << 16) | ((uint64_t)(sbo >> 4) << 32) | ((uint64_t)swz << 62);
}
__device__ __forceinline__ void keep(const uint4& a) { asm volatile("" ::"r"(a.x), "r"(a.y), "r"(a.z), "r"(a.w) : "memory"); }
template <int T> __device__ __forceinline__ void zero_acc(float (&d)[T]) {
#pragma unroll
  for (int i = 0; i < T; i++) d[i] = 0.f;
}
template <int T> __device__ __forceinline__ void fence_acc(float (&d)[T]) {
#pragma unroll
  for (int i = 0; i < T; i++) asm volatile("" : "+f"(d[i])::"memory");
}

template <int O, int T> __device__ __forceinline__ void wgmma_rs_n64(float (&d)[T], const uint4& a, uint64_t db, int scale_d) {
  asm volatile("{\n.reg .pred p;\nsetp.ne.b32 p, %37, 0;\n"
    "wgmma.mma_async.sync.aligned.m64n64k16.f32.bf16.bf16 "
    "{%0, %1, %2, %3, %4, %5, %6, %7, %8, %9, %10, %11, %12, %13, %14, %15, "
    "%16, %17, %18, %19, %20, %21, %22, %23, %24, %25, %26, %27, %28, %29, %30, %31}, "
    "{%32, %33, %34, %35}, %36, p, 1, 1, 1;\n}\n"
    : "+f"(d[O + 0]), "+f"(d[O + 1]), "+f"(d[O + 2]), "+f"(d[O + 3]), "+f"(d[O + 4]), "+f"(d[O + 5]), "+f"(d[O + 6]), "+f"(d[O + 7]),
      "+f"(d[O + 8]), "+f"(d[O + 9]), "+f"(d[O + 10]), "+f"(d[O + 11]), "+f"(d[O + 12]), "+f"(d[O + 13]), "+f"(d[O + 14]), "+f"(d[O + 15]),
      "+f"(d[O + 16]), "+f"(d[O + 17]), "+f"(d[O + 18]), "+f"(d[O + 19]), "+f"(d[O + 20]), "+f"(d[O + 21]), "+f"(d[O + 22]), "+f"(d[O + 23]),
      "+f"(d[O + 24]), "+f"(d[O + 25]), "+f"(d[O + 26]), "+f"(d[O + 27]), "+f"(d[O + 28]), "+f"(d[O + 29]), "+f"(d[O + 30]), "+f"(d[O + 31])
    : "r"(a.x), "r"(a.y), "r"(a.z), "r"(a.w), "l"(db), "r"(scale_d));
}
template <int O, int T> __device__ __forceinline__ void wgmma_rs_n128(float (&d)[T], const uint4& a, uint64_t db, int scale_d) {
  asm volatile("{\n.reg .pred p;\nsetp.ne.b32 p, %69, 0;\n"
    "wgmma.mma_async.sync.aligned.m64n128k16.f32.bf16.bf16 "
    "{%0, %1, %2, %3, %4, %5, %6, %7, %8, %9, %10, %11, %12, %13, %14, %15, "
    "%16, %17, %18, %19, %20, %21, %22, %23, %24, %25, %26, %27, %28, %29, %30, %31, "
    "%32, %33, %34, %35, %36, %37, %38, %39, %40, %41, %42, %43, %44, %45, %46, %47, "
    "%48, %49, %50, %51, %52, %53, %54, %55, %56, %57, %58, %59, %60, %61, %62, %63}, "
    "{%64, %65, %66, %67}, %68, p, 1, 1, 1;\n}\n"
    : "+f"(d[O + 0]), "+f"(d[O + 1]), "+f"(d[O + 2]), "+f"(d[O + 3]), "+f"(d[O + 4]), "+f"(d[O + 5]), "+f"(d[O + 6]), "+f"(d[O + 7]),
      "+f"(d[O + 8]), "+f"(d[O + 9]), "+f"(d[O + 10]), "+f"(d[O + 11]), "+f"(d[O + 12]), "+f"(d[O + 13]), "+f"(d[O + 14]), "+f"(d[O + 15]),
      "+f"(d[O + 16]), "+f"(d[O + 17]), "+f"(d[O + 18]), "+f"(d[O + 19]), "+f"(d[O + 20]), "+f"(d[O + 21]), "+f"(d[O + 22]), "+f"(d[O + 23]),
      "+f"(d[O + 24]), "+f"(d[O + 25]), "+f"(d[O + 26]), "+f"(d[O + 27]), "+f"(d[O + 28]), "+f"(d[O + 29]), "+f"(d[O + 30]), "+f"(d[O + 31]),
      "+f"(d[O + 32]), "+f"(d[O + 33]), "+f"(d[O + 34]), "+f"(d[O + 35]), "+f"(d[O + 36]), "+f"(d[O + 37]), "+f"(d[O + 38]), "+f"(d[O + 39]),
      "+f"(d[O + 40]), "+f"(d[O + 41]), "+f"(d[O + 42]), "+f"(d[O + 43]), "+f"(d[O + 44]), "+f"(d[O + 45]), "+f"(d[O + 46]), "+f"(d[O + 47]),
      "+f"(d[O + 48]), "+f"(d[O + 49]), "+f"(d[O + 50]), "+f"(d[O + 51]), "+f"(d[O + 52]), "+f"(d[O + 53]), "+f"(d[O + 54]), "+f"(d[O + 55]),
      "+f"(d[O + 56]), "+f"(d[O + 57]), "+f"(d[O + 58]), "+f"(d[O + 59]), "+f"(d[O + 60]), "+f"(d[O + 61]), "+f"(d[O + 62]), "+f"(d[O + 63])
    : "r"(a.x), "r"(a.y), "r"(a.z), "r"(a.w), "l"(db), "r"(scale_d));
}
template <int O, int T> __device__ __forceinline__ void wgmma_rs_n192(float (&d)[T], const uint4& a, uint64_t db, int scale_d) {
  asm volatile("{\n.reg .pred p;\nsetp.ne.b32 p, %101, 0;\n"
    "wgmma.mma_async.sync.aligned.m64n192k16.f32.bf16.bf16 "
    "{%0, %1, %2, %3, %4, %5, %6, %7, %8, %9, %10, %11, %12, %13, %14, %15, "
    "%16, %17, %18, %19, %20, %21, %22, %23, %24, %25, %26, %27, %28, %29, %30, %31, "
    "%32, %33, %34, %35, %36, %37, %38, %39, %40, %41, %42, %43, %44, %45, %46, %47, "
    "%48, %49, %50, %51, %52, %53, %54, %55, %56, %57, %58, %59, %60, %61, %62, %63, "
    "%64, %65, %66, %67, %68, %69, %70, %71, %72, %73, %74, %75, %76, %77, %78, %79, "
    "%80, %81, %82, %83, %84, %85, %86, %87, %88, %89, %90, %91, %92, %93, %94, %95}, "
    "{%96, %97, %98, %99}, %100, p, 1, 1, 1;\n}\n"
    : "+f"(d[O + 0]), "+f"(d[O + 1]), "+f"(d[O + 2]), "+f"(d[O + 3]), "+f"(d[O + 4]), "+f"(d[O + 5]), "+f"(d[O + 6]), "+f"(d[O + 7]),
      "+f"(d[O + 8]), "+f"(d[O + 9]), "+f"(d[O + 10]), "+f"(d[O + 11]), "+f"(d[O + 12]), "+f"(d[O + 13]), "+f"(d[O + 14]), "+f"(d[O + 15]),
      "+f"(d[O + 16]), "+f"(d[O + 17]), "+f"(d[O + 18]), "+f"(d[O + 19]), "+f"(d[O + 20]), "+f"(d[O + 21]), "+f"(d[O + 22]), "+f"(d[O + 23]),
      "+f"(d[O + 24]), "+f"(d[O + 25]), "+f"(d[O + 26]), "+f"(d[O + 27]), "+f"(d[O + 28]), "+f"(d[O + 29]), "+f"(d[O + 30]), "+f"(d[O + 31]),
      "+f"(d[O + 32]), "+f"(d[O + 33]), "+f"(d[O + 34]), "+f"(d[O + 35]), "+f"(d[O + 36]), "+f"(d[O + 37]), "+f"(d[O + 38]), "+f"(d[O + 39]),
      "+f"(d[O + 40]), "+f"(d[O + 41]), "+f"(d[O + 42]), "+f"(d[O + 43]), "+f"(d[O + 44]), "+f"(d[O + 45]), "+f"(d[O + 46]), "+f"(d[O + 47]),
      "+f"(d[O + 48]), "+f"(d[O + 49]), "+f"(d[O + 50]), "+f"(d[O + 51]), "+f"(d[O + 52]), "+f"(d[O + 53]), "+f"(d[O + 54]), "+f"(d[O + 55]),
      "+f"(d[O + 56]), "+f"(d[O + 57]), "+f"(d[O + 58]), "+f"(d[O + 59]), "+f"(d[O + 60]), "+f"(d[O + 61]), "+f"(d[O + 62]), "+f"(d[O + 63]),
      "+f"(d[O + 64]), "+f"(d[O + 65]), "+f"(d[O + 66]), "+f"(d[O + 67]), "+f"(d[O + 68]), "+f"(d[O + 69]), "+f"(d[O + 70]), "+f"(d[O + 71]),
      "+f"(d[O + 72]), "+f"(d[O + 73]), "+f"(d[O + 74]), "+f"(d[O + 75]), "+f"(d[O + 76]), "+f"(d[O + 77]), "+f"(d[O + 78]), "+f"(d[O + 79]),
      "+f"(d[O + 80]), "+f"(d[O + 81]), "+f"(d[O + 82]), "+f"(d[O + 83]), "+f"(d[O + 84]), "+f"(d[O + 85]), "+f"(d[O + 86]), "+f"(d[O + 87]),
      "+f"(d[O + 88]), "+f"(d[O + 89]), "+f"(d[O + 90]), "+f"(d[O + 91]), "+f"(d[O + 92]), "+f"(d[O + 93]), "+f"(d[O + 94]), "+f"(d[O + 95])
    : "r"(a.x), "r"(a.y), "r"(a.z), "r"(a.w), "l"(db), "r"(scale_d));
}
template <int O, int T> __device__ __forceinline__ void wgmma_rs_n256(float (&d)[T], const uint4& a, uint64_t db, int scale_d) {
  asm volatile("{\n.reg .pred p;\nsetp.ne.b32 p, %133, 0;\n"
    "wgmma.mma_async.sync.aligned.m64n256k16.f32.bf16.bf16 "
    "{%0, %1, %2, %3, %4, %5, %6, %7, %8, %9, %10, %11, %12, %13, %14, %15, "
    "%16, %17, %18, %19, %20, %21, %22, %23, %24, %25, %26, %27, %28, %29, %30, %31, "
    "%32, %33, %34, %35, %36, %37, %38, %39, %40, %41, %42, %43, %44, %45, %46, %47, "
    "%48, %49, %50, %51, %52, %53, %54, %55, %56, %57, %58, %59, %60, %61, %62, %63, "
    "%64, %65, %66, %67, %68, %69, %70, %71, %72, %73, %74, %75, %76, %77, %78, %79, "
    "%80, %81, %82, %83, %84, %85, %86, %87, %88, %89, %90, %91, %92, %93, %94, %95, "
    "%96, %97, %98, %99, %100, %101, %102, %103, %104, %105, %106, %107, %108, %109, %110, %111, "
    "%112, %113, %114, %115, %116, %117, %118, %119, %120, %121, %122, %123, %124, %125, %126, %127}, "
    "{%128, %129, %130, %131}, %132, p, 1, 1, 1;\n}\n"
    : "+f"(d[O + 0]), "+f"(d[O + 1]), "+f"(d[O + 2]), "+f"(d[O + 3]), "+f"(d[O + 4]), "+f"(d[O + 5]), "+f"(d[O + 6]), "+f"(d[O + 7]),
      "+f"(d[O + 8]), "+f"(d[O + 9]), "+f"(d[O + 10]), "+f"(d[O + 11]), "+f"(d[O + 12]), "+f"(d[O + 13]), "+f"(d[O + 14]), "+f"(d[O + 15]),
      "+f"(d[O + 16]), "+f"(d[O + 17]), "+f"(d[O + 18]), "+f"(d[O + 19]), "+f"(d[O + 20]), "+f"(d[O + 21]), "+f"(d[O + 22]), "+f"(d[O + 23]),
      "+f"(d[O + 24]), "+f"(d[O + 25]), "+f"(d[O + 26]), "+f"(d[O + 27]), "+f"(d[O + 28]), "+f"(d[O + 29]), "+f"(d[O + 30]), "+f"(d[O + 31]),
      "+f"(d[O + 32]), "+f"(d[O + 33]), "+f"(d[O + 34]), "+f"(d[O + 35]), "+f"(d[O + 36]), "+f"(d[O + 37]), "+f"(d[O + 38]), "+f"(d[O + 39]),
      "+f"(d[O + 40]), "+f"(d[O + 41]), "+f"(d[O + 42]), "+f"(d[O + 43]), "+f"(d[O + 44]), "+f"(d[O + 45]), "+f"(d[O + 46]), "+f"(d[O + 47]),
      "+f"(d[O + 48]), "+f"(d[O + 49]), "+f"(d[O + 50]), "+f"(d[O + 51]), "+f"(d[O + 52]), "+f"(d[O + 53]), "+f"(d[O + 54]), "+f"(d[O + 55]),
      "+f"(d[O + 56]), "+f"(d[O + 57]), "+f"(d[O + 58]), "+f"(d[O + 59]), "+f"(d[O + 60]), "+f"(d[O + 61]), "+f"(d[O + 62]), "+f"(d[O + 63]),
      "+f"(d[O + 64]), "+f"(d[O + 65]), "+f"(d[O + 66]), "+f"(d[O + 67]), "+f"(d[O + 68]), "+f"(d[O + 69]), "+f"(d[O + 70]), "+f"(d[O + 71]),
      "+f"(d[O + 72]), "+f"(d[O + 73]), "+f"(d[O + 74]), "+f"(d[O + 75]), "+f"(d[O + 76]), "+f"(d[O + 77]), "+f"(d[O + 78]), "+f"(d[O + 79]),
      "+f"(d[O + 80]), "+f"(d[O + 81]), "+f"(d[O + 82]), "+f"(d[O + 83]), "+f"(d[O + 84]), "+f"(d[O + 85]), "+f"(d[O + 86]), "+f"(d[O + 87]),
      "+f"(d[O + 88]), "+f"(d[O + 89]), "+f"(d[O + 90]), "+f"(d[O + 91]), "+f"(d[O + 92]), "+f"(d[O + 93]), "+f"(d[O + 94]), "+f"(d[O + 95]),
      "+f"(d[O + 96]), "+f"(d[O + 97]), "+f"(d[O + 98]), "+f"(d[O + 99]), "+f"(d[O + 100]), "+f"(d[O + 101]), "+f"(d[O + 102]), "+f"(d[O + 103]),
      "+f"(d[O + 104]), "+f"(d[O + 105]), "+f"(d[O + 106]), "+f"(d[O + 107]), "+f"(d[O + 108]), "+f"(d[O + 109]), "+f"(d[O + 110]), "+f"(d[O + 111]),
      "+f"(d[O + 112]), "+f"(d[O + 113]), "+f"(d[O + 114]), "+f"(d[O + 115]), "+f"(d[O + 116]), "+f"(d[O + 117]), "+f"(d[O + 118]), "+f"(d[O + 119]),
      "+f"(d[O + 120]), "+f"(d[O + 121]), "+f"(d[O + 122]), "+f"(d[O + 123]), "+f"(d[O + 124]), "+f"(d[O + 125]), "+f"(d[O + 126]), "+f"(d[O + 127])
    : "r"(a.x), "r"(a.y), "r"(a.z), "r"(a.w), "l"(db), "r"(scale_d));
}

template <int N> __device__ __forceinline__ void load_pk(uint4* a, const uint4* p) {
#pragma unroll
  for (int i = 0; i < N; i++) a[i] = ld_ll(p + i * 32);
}
template <int N> __device__ __forceinline__ bool ok_pk(const uint4* a, uint32_t tag) {
  uint32_t x = 0;
#pragma unroll
  for (int i = 0; i < N; i++) x |= a[i].x ^ tag;
  return __all_sync(0xffffffffu, (x & 1u) == 0u);
}
template <int N> __device__ __forceinline__ void ensure_pk(uint4* a, const uint4* p, uint32_t tag, uint32_t& n) {
  while (!ok_pk<N>(a, tag)) { load_pk<N>(a, p); if (++n > SPIN_LIMIT) break; }
}

struct Ring {
  uint32_t bars;
  uint32_t pos;
  uint32_t par;
  uint32_t spin;
};
template <int N> __device__ __forceinline__ uint32_t ring_next(Ring& r) {
  if (r.pos + N > NGRAN) r.pos = 0;
  uint32_t g0 = r.pos;
  r.pos += N;
  return g0;
}
template <int N> __device__ __forceinline__ uint32_t cons_acquire(Ring& r) {
  uint32_t g0 = ring_next<N>(r);
  mbar_wait(r.bars + BAR_FULL + 8 * g0, (r.par >> g0) & 1u, r.spin);
  r.par ^= 1u << g0;
  return g0;
}
template <int N> __device__ __forceinline__ void cons_release(const Ring& r, uint32_t g0, int lane) {
  if (lane < N) mbar_arrive(r.bars + BAR_EMPTY + 8 * (g0 + lane));
}
template <int N> __device__ __forceinline__ uint32_t prod_acquire(Ring& r, uint32_t bytes) {
  uint32_t g0 = ring_next<N>(r);
#pragma unroll
  for (int i = 0; i < N; i++) {
    mbar_wait(r.bars + BAR_EMPTY + 8 * (g0 + i), ((r.par >> (g0 + i)) & 1u) ^ 1u, r.spin);
  }
  r.par ^= ((1u << N) - 1u) << g0;
  mbar_expect_tx(r.bars + BAR_FULL + 8 * g0, bytes);
  return g0;
}

__device__ __forceinline__ void combine_stats(const uint4& p0, const uint4& p1, float& mean_lo, float& rstd_lo, float& mean_hi, float& rstd_hi) {
  float m0 = __uint_as_float(p0.x), q0 = __uint_as_float(p0.y), m0h = __uint_as_float(p0.z), q0h = __uint_as_float(p0.w);
  float m1 = __uint_as_float(p1.x), q1 = __uint_as_float(p1.y), m1h = __uint_as_float(p1.z), q1h = __uint_as_float(p1.w);
  float s = m0 + m1, sh = m0h + m1h;
  s += __shfl_xor_sync(0xffffffffu, s, 1); sh += __shfl_xor_sync(0xffffffffu, sh, 1);
  s += __shfl_xor_sync(0xffffffffu, s, 2); sh += __shfl_xor_sync(0xffffffffu, sh, 2);
  mean_lo = s * 0.125f; mean_hi = sh * 0.125f;
  float d0 = m0 - mean_lo, d1 = m1 - mean_lo, d0h = m0h - mean_hi, d1h = m1h - mean_hi;
  float t = q0 + q1 + 64.f * (d0 * d0 + d1 * d1), th = q0h + q1h + 64.f * (d0h * d0h + d1h * d1h);
  t += __shfl_xor_sync(0xffffffffu, t, 1); th += __shfl_xor_sync(0xffffffffu, th, 1);
  t += __shfl_xor_sync(0xffffffffu, t, 2); th += __shfl_xor_sync(0xffffffffu, th, 2);
  rstd_lo = rsqrtf(t * (1.f / 512.f) + 1e-5f);
  rstd_hi = rsqrtf(th * (1.f / 512.f) + 1e-5f);
}
__device__ __forceinline__ uint4 local_stats(const float (&v)[32]) {
  float s = 0.f, sh = 0.f;
#pragma unroll
  for (int i = 0; i < 4; i++) {
    s += (v[8 * i + 0] + v[8 * i + 1]) + (v[8 * i + 4] + v[8 * i + 5]);
    sh += (v[8 * i + 2] + v[8 * i + 3]) + (v[8 * i + 6] + v[8 * i + 7]);
  }
  s += __shfl_xor_sync(0xffffffffu, s, 1); sh += __shfl_xor_sync(0xffffffffu, sh, 1);
  s += __shfl_xor_sync(0xffffffffu, s, 2); sh += __shfl_xor_sync(0xffffffffu, sh, 2);
  float m = s * (1.f / 64.f), mh = sh * (1.f / 64.f);
  float q = 0.f, qh = 0.f;
#pragma unroll
  for (int i = 0; i < 4; i++) {
    float a = v[8 * i + 0] - m, b = v[8 * i + 1] - m, c = v[8 * i + 4] - m, d = v[8 * i + 5] - m;
    q += (a * a + b * b) + (c * c + d * d);
    float e = v[8 * i + 2] - mh, f = v[8 * i + 3] - mh, g = v[8 * i + 6] - mh, h = v[8 * i + 7] - mh;
    qh += (e * e + f * f) + (g * g + h * h);
  }
  q += __shfl_xor_sync(0xffffffffu, q, 1); qh += __shfl_xor_sync(0xffffffffu, qh, 1);
  q += __shfl_xor_sync(0xffffffffu, q, 2); qh += __shfl_xor_sync(0xffffffffu, qh, 2);
  return make_uint4(__float_as_uint(m), __float_as_uint(q), __float_as_uint(mh), __float_as_uint(qh));
}

__device__ __forceinline__ void owner_ln_publish(uint32_t sbase, const float (&v)[32], uint32_t tphase, uint32_t tag_xn, uint32_t& spin) {
  PHASE_VARS;
  const uint32_t bars = sbase + SM_MISC;
  const int sg = warp >> 2, qt = warp & 3;
  const int oslab = 2 * ca + sg;
  const int step0 = 16 * cbit + 4 * qt;
  uint4 st = local_stats(v);
  const uint32_t tb = bars + BAR_TSTAT + 8 * sg;
  const uint32_t slot = sbase + SM_TSTAT + sg * 1024 + (4 * cbit + qt) * 128 + qr * 16;
  if (qt == 0 && lane == 0) mbar_expect_tx(tb, 1024);
  if (qc == 0) {
    st_async128(mapa(slot, 0), st, mapa(tb, 0));
    st_async128(mapa(slot, 1), st, mapa(tb, 1));
  }
  mbar_wait_cluster(tb, tphase, spin);
  const uint32_t rd = sbase + SM_TSTAT + sg * 1024 + qc * 256 + qr * 16;
  uint4 p0 = lds128(rd), p1 = lds128(rd + 128);
  float ml, rl, mh, rh;
  combine_stats(p0, p1, ml, rl, mh, rh);
  const float bl = -ml * rl, bh = -mh * rh;
  uint4* xn = g_xn + ((c * 8 + oslab) * 32 + step0) * 32 + lane;
  uint4* xr = g_xraw + ((c * 8 + oslab) * 32 + step0) * 32 + lane;
#pragma unroll
  for (int i = 0; i < 4; i++) {
    uint4 o;
    o.x = set_tag(pack2(fmaf(v[8 * i + 0], rl, bl), fmaf(v[8 * i + 1], rl, bl)), tag_xn);
    o.y = pack2(fmaf(v[8 * i + 2], rh, bh), fmaf(v[8 * i + 3], rh, bh));
    o.z = pack2(fmaf(v[8 * i + 4], rl, bl), fmaf(v[8 * i + 5], rl, bl));
    o.w = pack2(fmaf(v[8 * i + 6], rh, bh), fmaf(v[8 * i + 7], rh, bh));
    st_ll(xn + i * 32, o);
  }
#pragma unroll
  for (int i = 0; i < 4; i++) {
    uint4 o;
    o.x = set_tag(pack2(v[8 * i + 0], v[8 * i + 1]), 1u);
    o.y = pack2(v[8 * i + 2], v[8 * i + 3]);
    o.z = pack2(v[8 * i + 4], v[8 * i + 5]);
    o.w = pack2(v[8 * i + 6], v[8 * i + 7]);
    st_ll(xr + i * 32, o);
  }
}

__global__ void __launch_bounds__(NTHREADS, 1)
fused_kernel(const __grid_constant__ CUtensorMap m_qkv, const __grid_constant__ CUtensorMap m_wo,
             const __grid_constant__ CUtensorMap m_gu4, const __grid_constant__ CUtensorMap m_gu3,
             const __grid_constant__ CUtensorMap m_wd, const __nv_bfloat16* __restrict__ x_in,
             __nv_bfloat16* __restrict__ out, const char* __restrict__ w_o, const char* __restrict__ w_g,
             const char* __restrict__ w_u, const char* __restrict__ w_d
) {
  extern __shared__ __align__(1024) unsigned char smem_raw[];
  const uint32_t sbase = smem_u32(smem_raw);
  const uint32_t bars = sbase + SM_MISC;
  const int tid = threadIdx.x;
  const int warp = tid >> 5, lane = tid & 31;
  const int j = blockIdx.x & 7;

  if (tid == 0) {
    for (int i = 0; i < NGRAN; i++) { mbar_init(bars + BAR_FULL + 8 * i, 1); mbar_init(bars + BAR_EMPTY + 8 * i, 8); }
    for (int i = 0; i < 2; i++) { mbar_init(bars + BAR_HRECV + 8 * i, 1); mbar_init(bars + BAR_HREADY + 8 * i, 4); mbar_init(bars + BAR_TSTAT + 8 * i, 1); }
    asm volatile("fence.mbarrier_init.release.cluster;" ::: "memory");
  }
  __syncthreads();
  cluster_sync_all();

  if (warp >= 8) {
    asm volatile("setmaxnreg.dec.sync.aligned.u32 40;");
    const int a = j >> 1, b = j & 1;
    if (warp == 8 && lane == 0) {
      Ring r{bars, 0u, 0u, 0u};
      for (int L = 0; L < 2; L++) {
        r.pos = 0;
        PSTOP_AT(L == 0 ? 0 : 3);
        for (int kb = 0; kb < 8; kb++) {
          uint32_t g0 = prod_acquire<3>(r, 24576);
          tma_3d(sbase + g0 * GRAN, &m_qkv, bars + BAR_FULL + 8 * g0, 64 * j, 64 * kb, 0);
        }
        PSTOP_AT(10 * L + 1);
        for (int i = 0; i < 8; i++) {
          uint32_t g0 = prod_acquire<2>(r, 16384);
          tma_3d(sbase + g0 * GRAN, &m_wo, bars + BAR_FULL + 8 * g0, 0, 256 * (i & 1) + 64 * (i >> 1), 2 * a);
        }
        PSTOP_AT(10 * L + 2);
        for (int kb = 0; kb < 8; kb++) {
          uint32_t g0 = prod_acquire<4>(r, 32768);
          tma_4d(sbase + g0 * GRAN, &m_gu4, bars + BAR_FULL + 8 * g0, 0, 64 * kb, 0, 7 * j);
        }
        for (int kb = 0; kb < 8; kb++) {
          uint32_t g0 = prod_acquire<3>(r, 24576);
          tma_4d(sbase + g0 * GRAN, &m_gu3, bars + BAR_FULL + 8 * g0, 0, 64 * kb, 0, 7 * j + 4);
        }
        for (int i = 0; i < 16; i++) {
          uint32_t g0 = prod_acquire<2>(r, 14336);
          int src = (i < 8) ? j : (j ^ 1);
          tma_2d(sbase + g0 * GRAN, &m_wd, bars + BAR_FULL + 8 * g0, 256 * b + 64 * ((i >> 1) & 3), 224 * src + 112 * (i & 1));
        }
      }
    } else if (warp == 9) {
      const int cta = blockIdx.x;
      if (lane == 0) l2_prefetch(w_o + cta * 4096, 4096);
      if (lane == 1) l2_prefetch(w_g + cta * 14336, 14336);
      if (lane == 2) l2_prefetch(w_u + cta * 14336, 14336);
      if (lane == 3) l2_prefetch(w_d + cta * 14336, 14336);
    }
    __syncwarp();
    asm volatile("barrier.cluster.arrive.release.aligned;\nbarrier.cluster.wait.acquire.aligned; // producer" ::: "memory");
  } else {
    asm volatile("setmaxnreg.inc.sync.aligned.u32 232;");
    Ring r{bars, 0u, 0u, 0u};

    {
      PHASE_VARS;
      const int sg = warp >> 2, qt = warp & 3;
      const int oslab = 2 * ca + sg;
      const int step0 = 16 * cbit + 4 * qt;
      float v[32];
      const uint32_t* xp = reinterpret_cast<const uint32_t*>(x_in + (size_t)(c * 128 + oslab * 16 + qr) * 512 + step0 * 16 + qc * 2);
#pragma unroll
      for (int i = 0; i < 4; i++) {
        uint32_t w0 = __ldg(xp + i * 8), w1 = __ldg(xp + 8 * 256 + i * 8), w2 = __ldg(xp + i * 8 + 4), w3 = __ldg(xp + 8 * 256 + i * 8 + 4);
        v[8 * i + 0] = bf_lo(w0); v[8 * i + 1] = bf_hi(w0); v[8 * i + 2] = bf_lo(w1); v[8 * i + 3] = bf_hi(w1);
        v[8 * i + 4] = bf_lo(w2); v[8 * i + 5] = bf_hi(w2); v[8 * i + 6] = bf_lo(w3); v[8 * i + 7] = bf_hi(w3);
      }
      owner_ln_publish(sbase, v, 0u, 1u, r.spin);
    }
    STOP_AT(0);

#pragma unroll 1
    for (int L = 0; L < 2; L++) {
      const uint32_t tag = L ^ 1;
      r.pos = 0;
      bar_consumers(1);
      {
      PHASE_VARS;
      uint4 qf[4], kf[4], vf[4], pk[4], pv[4];
#pragma unroll
      for (int h = 0; h < 4; h++) { pk[h] = make_uint4(0, 0, 0, 0); pv[h] = make_uint4(0, 0, 0, 0); }
      const uint4* halo_src = g_halo + (((L * 16 + (c > 0 ? c - 1 : 0)) * 8 + j) * 8) * 32 + lane;
      {
        float acc[96];
        zero_acc(acc);
        uint4 A[3][4];
        const uint4* xs = g_xn + ((c * 8 + slab) * 32) * 32 + lane;
        do { load_pk<4>(A[0], xs); load_pk<4>(A[1], xs + 128); } while (!ok_pk<4>(A[0], tag) && ++r.spin <= SPIN_LIMIT);
        uint32_t prev = 0;
#pragma unroll
        for (int kb = 0; kb < 8; kb++) {
          ensure_pk<4>(A[kb % 3], xs + kb * 128, tag, r.spin);
          uint32_t g0 = cons_acquire<3>(r);
          uint64_t db = make_desc(sbase + g0 * GRAN, 8192, 1024, 1);
          wg_fence();
#pragma unroll
          for (int k = 0; k < 4; k++) wgmma_rs_n192<0>(acc, A[kb % 3][k], db + k * 128, (kb | k) != 0);
          wg_commit();
          if (kb > 0) {
            wg_wait<1>();
#pragma unroll
            for (int k = 0; k < 4; k++) keep(A[(kb + 2) % 3][k]);
            cons_release<3>(r, prev, lane);
          }
          if (kb + 2 < 8) load_pk<4>(A[(kb + 2) % 3], xs + (kb + 2) * 128);
          prev = g0;
        }
        if (slab == 0 && c > 0) { load_pk<4>(pk, halo_src); load_pk<4>(pv, halo_src + 128); }
        wg_wait<0>();
        fence_acc(acc);
#pragma unroll
        for (int k = 0; k < 4; k++) keep(A[1][k]);
        cons_release<3>(r, prev, lane);
#pragma unroll
        for (int h = 0; h < 4; h++) {
          qf[h] = make_uint4(pack2(acc[8 * h], acc[8 * h + 1]), pack2(acc[8 * h + 2], acc[8 * h + 3]), pack2(acc[8 * h + 4], acc[8 * h + 5]), pack2(acc[8 * h + 6], acc[8 * h + 7]));
          kf[h] = make_uint4(pack2(acc[32 + 8 * h], acc[32 + 8 * h + 1]), pack2(acc[32 + 8 * h + 2], acc[32 + 8 * h + 3]), pack2(acc[32 + 8 * h + 4], acc[32 + 8 * h + 5]), pack2(acc[32 + 8 * h + 6], acc[32 + 8 * h + 7]));
          vf[h] = make_uint4(movm(pack2(acc[64 + 8 * h], acc[64 + 8 * h + 1])), movm(pack2(acc[64 + 8 * h + 2], acc[64 + 8 * h + 3])),
                             movm(pack2(acc[64 + 8 * h + 4], acc[64 + 8 * h + 5])), movm(pack2(acc[64 + 8 * h + 6], acc[64 + 8 * h + 7])));
        }
      }
      {
        const uint32_t kvw = areg + AR_KV + w * 4096 + lane * 16;
#pragma unroll
        for (int h = 0; h < 4; h++) { sts128(kvw + h * 512, kf[h]); sts128(kvw + 2048 + h * 512, vf[h]); }
        if (slab == 7 && c < 15) {
          uint4* hd = g_halo + (((L * 16 + c) * 8 + j) * 8) * 32 + lane;
#pragma unroll
          for (int h = 0; h < 4; h++) {
            uint4 t = kf[h]; t.x |= 1u; st_ll(hd + h * 32, t);
            t = vf[h]; t.x |= 1u; st_ll(hd + 128 + h * 32, t);
          }
        }
        bar_consumers(2);
        const bool first = (slab == 0) && (c == 0);
        if (slab > 0) {
          const int ps = slab - 1;
          const uint32_t kvr = sbase + SM_AREG + (ps >> 2) * 65536 + AR_KV + (ps & 3) * 4096 + lane * 16;
#pragma unroll
          for (int h = 0; h < 4; h++) { pk[h] = lds128(kvr + h * 512); pv[h] = lds128(kvr + 2048 + h * 512); }
        } else if (c > 0) {
          ensure_pk<4>(pk, halo_src, 1u, r.spin);
          ensure_pk<4>(pv, halo_src + 128, 1u, r.spin);
          uint4* hz = const_cast<uint4*>(halo_src);
#pragma unroll
          for (int h = 0; h < 8; h++) st_ll(hz + h * 32, make_uint4(0, 0, 0, 0));
        }
        const bool e = qr & 1;
        const bool newer = (2 * qc + (qr & 1)) <= qr;
        const float sc = 0.25f * 1.4426950408889634f;
        const float NEG = -1e30f;
                uint4* od = g_o + ((c * 8 + slab) * 32 + 4 * j) * 32 + lane;
#pragma unroll
        for (int h = 0; h < 4; h++) {
          float s0[4] = {0, 0, 0, 0}, s1[4] = {0, 0, 0, 0}, s2[4] = {0, 0, 0, 0}, s3[4] = {0, 0, 0, 0};
          mma16816(s0, qf[h], pk[h].x, pk[h].z);
          mma16816(s1, qf[h], pk[h].y, pk[h].w);
          mma16816(s2, qf[h], kf[h].x, kf[h].z);
          mma16816(s3, qf[h], kf[h].y, kf[h].w);
          float mid_l = e ? s1[1] : s1[0];
          float oth_l = newer ? (e ? s2[1] : s2[0]) : (e ? s0[1] : s0[0]);
          float mid_h = e ? s2[3] : s2[2];
          float oth_h = newer ? (e ? s3[3] : s3[2]) : (e ? s1[3] : s1[2]);
          if (first) { mid_l = NEG; if (!newer) { oth_l = NEG; oth_h = NEG; } }
          float ml = fmaxf(mid_l, oth_l), mh = fmaxf(mid_h, oth_h);
          ml = fmaxf(ml, __shfl_xor_sync(0xffffffffu, ml, 1)); mh = fmaxf(mh, __shfl_xor_sync(0xffffffffu, mh, 1));
          ml = fmaxf(ml, __shfl_xor_sync(0xffffffffu, ml, 2)); mh = fmaxf(mh, __shfl_xor_sync(0xffffffffu, mh, 2));
          float pml = exp2f((mid_l - ml) * sc), pol = exp2f((oth_l - ml) * sc);
          float pmh = exp2f((mid_h - mh) * sc), poh = exp2f((oth_h - mh) * sc);
          float sl = pml + pol, sh = pmh + poh;
          sl += __shfl_xor_sync(0xffffffffu, sl, 1); sh += __shfl_xor_sync(0xffffffffu, sh, 1);
          sl += __shfl_xor_sync(0xffffffffu, sl, 2); sh += __shfl_xor_sync(0xffffffffu, sh, 2);
          const float il = __fdividef(1.f, sl), ih = __fdividef(1.f, sh);
          const uint32_t sft = e ? 16u : 0u;
          const uint32_t bml = (pack2(pml * il, 0.f) & 0xffffu) << sft, bol = (pack2(pol * il, 0.f) & 0xffffu) << sft;
          const uint32_t bmh = (pack2(pmh * ih, 0.f) & 0xffffu) << sft, boh = (pack2(poh * ih, 0.f) & 0xffffu) << sft;
          uint4 P0 = make_uint4(newer ? 0u : bol, 0u, bml, newer ? 0u : boh);
          uint4 P1 = make_uint4(newer ? bol : 0u, bmh, 0u, newer ? boh : 0u);
          float o0[4] = {0, 0, 0, 0}, o1[4] = {0, 0, 0, 0};
          mma16816(o0, P0, pv[h].x, pv[h].y);
          mma16816(o1, P0, pv[h].z, pv[h].w);
          mma16816(o0, P1, vf[h].x, vf[h].y);
          mma16816(o1, P1, vf[h].z, vf[h].w);
          uint4 o = make_uint4(set_tag(pack2(o0[0], o0[1]), tag), pack2(o0[2], o0[3]), pack2(o1[0], o1[1]), pack2(o1[2], o1[3]));
          st_ll(od + h * 32, o);
        }
      }
      }
      if (L == 0) { STOP_AT(1); } else { STOP_AT(11); }
      {
        PHASE_VARS;
        const int slabA = 4 * cbit + w;
        float acc[64];
        zero_acc(acc);
        uint4 A[16];
        uint4 xr[4];
        const uint4* os = g_o + ((c * 8 + slabA) * 32 + 16 * g) * 32 + lane;
        uint4* xp = g_xraw + ((c * 8 + slabA) * 32 + 8 * ca + 4 * g) * 32 + lane;
        load_pk<4>(xr, xp);
        do { load_pk<16>(A, os); } while (!ok_pk<4>(A, tag) && ++r.spin <= SPIN_LIMIT);
        uint32_t prev = 0;
#pragma unroll
        for (int i = 0; i < 8; i++) {
          uint32_t g0 = cons_acquire<2>(r);
          if ((i & 1) == g) {
            const int kb = i >> 1;
            ensure_pk<4>(A + 4 * kb, os + kb * 128, tag, r.spin);
            uint64_t db = make_desc(sbase + g0 * GRAN, 8192, 1024, 1);
            wg_fence();
#pragma unroll
            for (int k = 0; k < 4; k++) wgmma_rs_n128<0>(acc, A[4 * kb + k], db + k * 128, (kb | k) != 0);
            wg_commit();
            if (kb > 0) { wg_wait<1>(); cons_release<2>(r, prev, lane); }
            prev = g0;
          } else {
            cons_release<2>(r, g0, lane);
          }
        }
        wg_wait<0>();
        fence_acc(acc);
#pragma unroll
        for (int k = 0; k < 16; k++) keep(A[k]);
        cons_release<2>(r, prev, lane);
        const uint32_t xo = sbase + SM_AREG + (g ^ 1) * 65536 + AR_X + t128 * 16;
        const uint32_t xi = areg + AR_X + t128 * 16;
        float v[32];
        if (g == 0) {
#pragma unroll
          for (int i = 0; i < 8; i++) sts128(xo + i * 2048, make_uint4(__float_as_uint(acc[32 + 4 * i]), __float_as_uint(acc[33 + 4 * i]), __float_as_uint(acc[34 + 4 * i]), __float_as_uint(acc[35 + 4 * i])));
#pragma unroll
          for (int i = 0; i < 32; i++) v[i] = acc[i];
        } else {
#pragma unroll
          for (int i = 0; i < 8; i++) sts128(xo + i * 2048, make_uint4(__float_as_uint(acc[4 * i]), __float_as_uint(acc[1 + 4 * i]), __float_as_uint(acc[2 + 4 * i]), __float_as_uint(acc[3 + 4 * i])));
#pragma unroll
          for (int i = 0; i < 32; i++) v[i] = acc[32 + i];
        }
        bar_consumers(3);
        ensure_pk<4>(xr, xp, 1u, r.spin);
#pragma unroll
        for (int i = 0; i < 8; i++) {
          uint4 t = lds128(xi + i * 2048);
          v[4 * i] += __uint_as_float(t.x); v[4 * i + 1] += __uint_as_float(t.y); v[4 * i + 2] += __uint_as_float(t.z); v[4 * i + 3] += __uint_as_float(t.w);
        }
#pragma unroll
        for (int i = 0; i < 4; i++) {
          v[8 * i + 0] += bf_lo(xr[i].x); v[8 * i + 1] += bf_hi(xr[i].x); v[8 * i + 2] += bf_lo(xr[i].y); v[8 * i + 3] += bf_hi(xr[i].y);
          v[8 * i + 4] += bf_lo(xr[i].z); v[8 * i + 5] += bf_hi(xr[i].z); v[8 * i + 6] += bf_lo(xr[i].w); v[8 * i + 7] += bf_hi(xr[i].w);
          uint4 o = make_uint4(set_tag(pack2(v[8 * i], v[8 * i + 1]), 0u), pack2(v[8 * i + 2], v[8 * i + 3]), pack2(v[8 * i + 4], v[8 * i + 5]), pack2(v[8 * i + 6], v[8 * i + 7]));
          st_ll(xp + i * 32, o);
        }
        uint4 st = local_stats(v);
        st.x = set_tag(st.x, tag);
        if (qc == 0) st_ll(g_stats + ((c * 8 + slabA) * 8 + 2 * ca + g) * 8 + qr, st);
      }
      if (L == 0) { STOP_AT(2); } else { STOP_AT(12); }
      uint4 hs[14];
      {
        PHASE_VARS;
                float acc[128];
        zero_acc(acc);
        uint4 X[3][4];
        const uint4* xs = g_xraw + ((c * 8 + slab) * 32) * 32 + lane;
        const uint4* sp = g_stats + ((c * 8 + slab) * 8 + 2 * qc) * 8 + qr;
        float rl, rh, bl, bh;
        {
          uint4 p0, p1;
          bool ok;
          do {
            p0 = ld_ll(sp); p1 = ld_ll(sp + 8);
            load_pk<4>(X[0], xs); load_pk<4>(X[1], xs + 128);
            ok = __all_sync(0xffffffffu, (((p0.x ^ tag) | (p1.x ^ tag)) & 1u) == 0u);
          } while (!ok && ++r.spin <= SPIN_LIMIT);
          float ml, mh;
          combine_stats(p0, p1, ml, rl, mh, rh);
          bl = -ml * rl; bh = -mh * rh;
        }
        const uint32_t acp = areg + t128 * 16;
        uint32_t prev = 0;
#pragma unroll
        for (int kb = 0; kb < 8; kb++) {
          ensure_pk<4>(X[kb % 3], xs + kb * 128, 0u, r.spin);
#pragma unroll
          for (int k = 0; k < 4; k++) {
            const uint4 x = X[kb % 3][k];
            uint4 y;
            y.x = pack2(fmaf(bf_lo(x.x), rl, bl), fmaf(bf_hi(x.x), rl, bl));
            y.y = pack2(fmaf(bf_lo(x.y), rh, bh), fmaf(bf_hi(x.y), rh, bh));
            y.z = pack2(fmaf(bf_lo(x.z), rl, bl), fmaf(bf_hi(x.z), rl, bl));
            y.w = pack2(fmaf(bf_lo(x.w), rh, bh), fmaf(bf_hi(x.w), rh, bh));
            X[kb % 3][k] = y;
            sts128(acp + (kb * 4 + k) * 2048, y);
          }
          uint32_t g0 = cons_acquire<4>(r);
          uint64_t db = make_desc(sbase + g0 * GRAN, 4096, 512, 2);
          wg_fence();
#pragma unroll
          for (int k = 0; k < 4; k++) wgmma_rs_n256<0>(acc, X[kb % 3][k], db + k * 64, (kb | k) != 0);
          wg_commit();
          if (kb > 0) {
            wg_wait<1>();
#pragma unroll
            for (int k = 0; k < 4; k++) keep(X[(kb + 2) % 3][k]);
            cons_release<4>(r, prev, lane);
          }
          if (kb + 2 < 8) load_pk<4>(X[(kb + 2) % 3], xs + (kb + 2) * 128);
          prev = g0;
        }
        wg_wait<0>();
        fence_acc(acc);
#pragma unroll
        for (int k = 0; k < 4; k++) keep(X[1][k]);
        cons_release<4>(r, prev, lane);
        uint4 B[2][4];
#pragma unroll
        for (int k = 0; k < 4; k++) B[0][k] = lds128(acp + k * 2048);
#pragma unroll
        for (int s = 0; s < 8; s++) {
          const int o = 32 * (s >> 1) + 8 * (s & 1);
          hs[s] = make_uint4(pack2(acc[o] * acc[o + 16], acc[o + 1] * acc[o + 17]), pack2(acc[o + 2] * acc[o + 18], acc[o + 3] * acc[o + 19]),
                             pack2(acc[o + 4] * acc[o + 20], acc[o + 5] * acc[o + 21]), pack2(acc[o + 6] * acc[o + 22], acc[o + 7] * acc[o + 23]));
        }
        float acc2[96];
        zero_acc(acc2);
#pragma unroll
        for (int kb = 0; kb < 8; kb++) {
          uint32_t g0 = cons_acquire<3>(r);
          uint64_t db = make_desc(sbase + g0 * GRAN, 4096, 512, 2);
          wg_fence();
#pragma unroll
          for (int k = 0; k < 4; k++) wgmma_rs_n192<0>(acc2, B[kb & 1][k], db + k * 64, (kb | k) != 0);
          wg_commit();
          if (kb > 0) {
            wg_wait<1>();
#pragma unroll
            for (int k = 0; k < 4; k++) keep(B[(kb + 1) & 1][k]);
            cons_release<3>(r, prev, lane);
          }
          if (kb + 1 < 8) {
#pragma unroll
            for (int k = 0; k < 4; k++) B[(kb + 1) & 1][k] = lds128(acp + ((kb + 1) * 4 + k) * 2048);
          }
          if (kb == 3) {
            __syncwarp();
            if (lane == 0) mbar_arrive_remote(mapa(bars + BAR_HREADY + 8 * g, cbit ^ 1));
          }
          prev = g0;
        }
        wg_wait<0>();
        fence_acc(acc2);
#pragma unroll
        for (int k = 0; k < 4; k++) keep(B[1][k]);
        cons_release<3>(r, prev, lane);
#pragma unroll
        for (int s = 0; s < 6; s++) {
          const int o = 32 * (s >> 1) + 8 * (s & 1);
          hs[8 + s] = make_uint4(pack2(acc2[o] * acc2[o + 16], acc2[o + 1] * acc2[o + 17]), pack2(acc2[o + 2] * acc2[o + 18], acc2[o + 3] * acc2[o + 19]),
                                 pack2(acc2[o + 4] * acc2[o + 20], acc2[o + 5] * acc2[o + 21]), pack2(acc2[o + 6] * acc2[o + 22], acc2[o + 7] * acc2[o + 23]));
        }
      }
      {
        PHASE_VARS;
        float v[32];
        if (t128 == 0) mbar_expect_tx(bars + BAR_HRECV + 8 * g, 14 * 2048);
        mbar_wait_cluster(bars + BAR_HREADY + 8 * g, L, r.spin);
        {
          const uint32_t rdst = mapa(areg + t128 * 16, cbit ^ 1), rbar = mapa(bars + BAR_HRECV + 8 * g, cbit ^ 1);
#pragma unroll
          for (int s = 0; s < 14; s++) st_async128(rdst + s * 2048, hs[s], rbar);
        }
        float acc[128];
        zero_acc(acc);
        uint32_t prev = 0;
#pragma unroll
        for (int i = 0; i < 8; i++) {
          uint32_t g0 = cons_acquire<2>(r);
          uint64_t db = make_desc(sbase + g0 * GRAN, 8192, 1024, 1);
          wg_fence();
#pragma unroll
          for (int k = 0; k < 7; k++) {
            const int s = 7 * (i & 1) + k;
            if ((i >> 1) == 0) wgmma_rs_n64<0>(acc, hs[s], db + k * 128, s != 0);
            if ((i >> 1) == 1) wgmma_rs_n64<32>(acc, hs[s], db + k * 128, s != 0);
            if ((i >> 1) == 2) wgmma_rs_n64<64>(acc, hs[s], db + k * 128, s != 0);
            if ((i >> 1) == 3) wgmma_rs_n64<96>(acc, hs[s], db + k * 128, s != 0);
          }
          wg_commit();
          if (i > 0) { wg_wait<1>(); cons_release<2>(r, prev, lane); }
          prev = g0;
        }
        uint4 hp[14];
        mbar_wait_cluster(bars + BAR_HRECV + 8 * g, L, r.spin);
#pragma unroll
        for (int k = 0; k < 7; k++) { keep(hs[k]); hp[k] = lds128(areg + t128 * 16 + k * 2048); }
                uint4* pd = g_part + ((((c * 4 + (slab >> 1)) * 2 + cbit) * 4 + ca) * 2 + (slab & 1)) * 16 * 32 + lane;
#pragma unroll
        for (int i = 0; i < 8; i++) {
          uint32_t g0 = cons_acquire<2>(r);
          uint64_t db = make_desc(sbase + g0 * GRAN, 8192, 1024, 1);
          wg_fence();
#pragma unroll
          for (int k = 0; k < 7; k++) {
            const int s = 7 * (i & 1) + k;
            if ((i >> 1) == 0) wgmma_rs_n64<0>(acc, hp[s], db + k * 128, 1);
            if ((i >> 1) == 1) wgmma_rs_n64<32>(acc, hp[s], db + k * 128, 1);
            if ((i >> 1) == 2) wgmma_rs_n64<64>(acc, hp[s], db + k * 128, 1);
            if ((i >> 1) == 3) wgmma_rs_n64<96>(acc, hp[s], db + k * 128, 1);
          }
          wg_commit();
          wg_wait<1>();
          cons_release<2>(r, prev, lane);
          if (i == 0) {
#pragma unroll
            for (int k = 7; k < 14; k++) { keep(hs[k]); hp[k] = lds128(areg + t128 * 16 + k * 2048); }
          }
          if (i >= 2 && (i & 1) == 0) {
            const int q = (i >> 1) - 1;
#pragma unroll
            for (int k = 0; k < 32; k++) asm volatile("" : "+f"(acc[32 * q + k])::"memory");
#pragma unroll
            for (int s = 0; s < 4; s++) {
              const int o = 32 * q + 8 * s;
              st_ll(pd + (4 * q + s) * 32, make_uint4(set_tag(pack2(acc[o], acc[o + 1]), tag), pack2(acc[o + 2], acc[o + 3]), pack2(acc[o + 4], acc[o + 5]), pack2(acc[o + 6], acc[o + 7])));
            }
          }
          prev = g0;
        }
        const int sg = warp >> 2, qt = warp & 3;
        const int oslab = 2 * ca + sg;
                const uint4* xq = g_xraw + ((c * 8 + oslab) * 32 + 16 * cbit + 4 * qt) * 32 + lane;
        const uint4* ps = g_part + ((((c * 4 + ca) * 2 + cbit) * 4) * 2 + sg) * 16 * 32 + (4 * qt) * 32 + lane;
        uint4 xr[4];
        load_pk<4>(xr, xq);
        wg_wait<0>();
        fence_acc(acc);
#pragma unroll
        for (int k = 0; k < 14; k++) keep(hp[k]);
        cons_release<2>(r, prev, lane);
#pragma unroll
        for (int s = 0; s < 4; s++) {
          const int o = 96 + 8 * s;
          st_ll(pd + (12 + s) * 32, make_uint4(set_tag(pack2(acc[o], acc[o + 1]), tag), pack2(acc[o + 2], acc[o + 3]), pack2(acc[o + 4], acc[o + 5]), pack2(acc[o + 6], acc[o + 7])));
        }
        uint4 P[4][4];
        do {
#pragma unroll
          for (int src = 0; src < 4; src++) load_pk<4>(P[src], ps + src * (2 * 16 * 32));
        } while (!ok_pk<16>(&P[0][0], tag) && ++r.spin <= SPIN_LIMIT);
        ensure_pk<4>(xr, xq, 0u, r.spin);
#pragma unroll
        for (int i = 0; i < 4; i++) {
          v[8 * i + 0] = bf_lo(xr[i].x); v[8 * i + 1] = bf_hi(xr[i].x); v[8 * i + 2] = bf_lo(xr[i].y); v[8 * i + 3] = bf_hi(xr[i].y);
          v[8 * i + 4] = bf_lo(xr[i].z); v[8 * i + 5] = bf_hi(xr[i].z); v[8 * i + 6] = bf_lo(xr[i].w); v[8 * i + 7] = bf_hi(xr[i].w);
          float d[8] = {0, 0, 0, 0, 0, 0, 0, 0};
#pragma unroll
          for (int src = 0; src < 4; src++) {
            const uint4 p = P[src][i];
            d[0] += bf_lo(p.x); d[1] += bf_hi(p.x); d[2] += bf_lo(p.y); d[3] += bf_hi(p.y);
            d[4] += bf_lo(p.z); d[5] += bf_hi(p.z); d[6] += bf_lo(p.w); d[7] += bf_hi(p.w);
          }
#pragma unroll
          for (int k = 0; k < 8; k++) v[8 * i + k] += d[k];
        }
        if (L == 0) {
          owner_ln_publish(sbase, v, 1u, 0u, r.spin);
        } else {
                    uint32_t* op = reinterpret_cast<uint32_t*>(out + (size_t)(c * 128 + oslab * 16 + qr) * 512 + (16 * cbit + 4 * qt) * 16 + qc * 2);
#pragma unroll
          for (int i = 0; i < 4; i++) {
            op[i * 8] = pack2(v[8 * i], v[8 * i + 1]);
            op[8 * 256 + i * 8] = pack2(v[8 * i + 2], v[8 * i + 3]);
            op[i * 8 + 4] = pack2(v[8 * i + 4], v[8 * i + 5]);
            op[8 * 256 + i * 8 + 4] = pack2(v[8 * i + 6], v[8 * i + 7]);
          }
        }
      }
      if (L == 0) { STOP_AT(3); }
    }
    asm volatile("barrier.cluster.arrive.release.aligned;\nbarrier.cluster.wait.acquire.aligned; // consumer" ::: "memory");
  }
}

typedef CUresult (*EncodeFn)(CUtensorMap*, CUtensorMapDataType, cuuint32_t, void*, const cuuint64_t*, const cuuint64_t*,
                             const cuuint32_t*, const cuuint32_t*, CUtensorMapInterleave, CUtensorMapSwizzle,
                             CUtensorMapL2promotion, CUtensorMapFloatOOBfill);

void encode(EncodeFn fn, CUtensorMap* m, int rank, const void* base, const cuuint64_t* dims, const cuuint64_t* strides,
            const cuuint32_t* box, CUtensorMapSwizzle sw) {
  cuuint32_t es[5] = {1, 1, 1, 1, 1};
  fn(m, CU_TENSOR_MAP_DATA_TYPE_BFLOAT16, (cuuint32_t)rank, const_cast<void*>(base), dims, strides, box, es,
     CU_TENSOR_MAP_INTERLEAVE_NONE, sw, CU_TENSOR_MAP_L2_PROMOTION_L2_128B, CU_TENSOR_MAP_FLOAT_OOB_FILL_NONE);
}

}

extern "C" void kernel_launch(void* const* d_in, const int* in_sizes, int n_in, void* d_out, int out_size) {
  (void)in_sizes; (void)n_in; (void)out_size;
  const __nv_bfloat16* x = (const __nv_bfloat16*)d_in[0];
  const char* wqkv = (const char*)d_in[1];
  const char* wo = (const char*)d_in[2];
  const char* wg = (const char*)d_in[4];
  const char* wu = (const char*)d_in[5];
  const char* wd = (const char*)d_in[6];

  static EncodeFn fn = nullptr;
  if (!fn) {
    void* p = nullptr;
    cudaDriverEntryPointQueryResult st;
    cudaGetDriverEntryPoint("cuTensorMapEncodeTiled", &p, cudaEnableDefault, &st);
    fn = (EncodeFn)p;
    cudaFuncSetAttribute(fused_kernel, cudaFuncAttributeMaxDynamicSharedMemorySize, SMEM_BYTES);
  }
  CUtensorMap m_qkv, m_wo, m_gu4, m_gu3, m_wd;
  {
    cuuint64_t dims[3] = {512, 512, 3}, str[2] = {3072, 1024};
    cuuint32_t box[3] = {64, 64, 3};
    encode(fn, &m_qkv, 3, wqkv, dims, str, box, CU_TENSOR_MAP_SWIZZLE_128B);
  }
  {
    cuuint64_t dims[3] = {64, 512, 8}, str[2] = {1024, 128};
    cuuint32_t box[3] = {64, 64, 2};
    encode(fn, &m_wo, 3, wo, dims, str, box, CU_TENSOR_MAP_SWIZZLE_128B);
  }
  {
    const char* lo = wg < wu ? wg : wu;
    cuuint64_t diff = (cuuint64_t)(wg < wu ? wu - wg : wg - wu);
    cuuint64_t dims[4] = {32, 512, 2, 56}, str[3] = {3584, diff, 64};
    cuuint32_t box4[4] = {32, 64, 2, 4}, box3[4] = {32, 64, 2, 3};
    encode(fn, &m_gu4, 4, lo, dims, str, box4, CU_TENSOR_MAP_SWIZZLE_64B);
    encode(fn, &m_gu3, 4, lo, dims, str, box3, CU_TENSOR_MAP_SWIZZLE_64B);
  }
  {
    cuuint64_t dims[2] = {512, 1792}, str[1] = {1024};
    cuuint32_t box[2] = {64, 112};
    encode(fn, &m_wd, 2, wd, dims, str, box, CU_TENSOR_MAP_SWIZZLE_128B);
  }
  cudaLaunchConfig_t cfg = {};
  cfg.gridDim = dim3(128);
  cfg.blockDim = dim3(NTHREADS);
  cfg.dynamicSmemBytes = SMEM_BYTES;
  cfg.stream = cudaStreamPerThread;
  cudaLaunchAttribute at[1];
  at[0].id = cudaLaunchAttributeClusterDimension;
  at[0].val.clusterDim.x = 2; at[0].val.clusterDim.y = 1; at[0].val.clusterDim.z = 1;
  cfg.attrs = at; cfg.numAttrs = 1;
  cudaLaunchKernelEx(&cfg, fused_kernel, m_qkv, m_wo, m_gu4, m_gu3, m_wd, x, (__nv_bfloat16*)d_out, wo, wg, wu, wd
  );
}
```

```cpp
#include <cuda_runtime.h>
#include <cuda_bf16.h>
#include <cuda.h>
#include <stdint.h>

namespace {

constexpr int NTHREADS = 384;
constexpr int GRAN = 8192;
constexpr int NGRAN = 12;
constexpr int SM_AREG = NGRAN * GRAN;
constexpr int SM_MISC = SM_AREG + 131072;
constexpr int SM_TSTAT = SM_MISC + 256;
constexpr int SMEM_BYTES = SM_TSTAT + 2048;
constexpr int BAR_FULL = 0, BAR_EMPTY = 96, BAR_HRECV = 192, BAR_HREADY = 208, BAR_TSTAT = 224;
constexpr int AR_X = 32768, AR_KV = 49152;

__device__ uint4 g_xn[16 * 8 * 32 * 32];
__device__ uint4 g_xraw[16 * 8 * 32 * 32];
__device__ uint4 g_o[16 * 8 * 32 * 32];
__device__ uint4 g_stats[16 * 8 * 8 * 8];
__device__ uint4 g_halo[2 * 16 * 8 * 8 * 32];
__device__ uint4 g_part[16 * 4 * 2 * 4 * 2 * 16 * 32];

#define TS(n)
#define OPAQUE(x) asm volatile("" : "+r"(x))
#define PHASE_VARS                                                                                   \
  int tid_ = threadIdx.x, bid_ = blockIdx.x;                                                         \
  OPAQUE(tid_); OPAQUE(bid_);                                                                        \
  const int lane = tid_ & 31, warp = tid_ >> 5, g = warp >> 2, w = warp & 3, t128 = tid_ & 127;      \
  const int qr = lane >> 2, qc = lane & 3, slab = warp;                                              \
  const int c = bid_ >> 3, j = bid_ & 7, ca = j >> 1, cbit = j & 1;                                  \
  const uint32_t areg = sbase + SM_AREG + g * 65536;                                                 \
  (void)w; (void)t128; (void)qr; (void)qc; (void)slab; (void)c; (void)ca; (void)cbit; (void)areg; (void)lane
#define STOP_AT(n)
#define PSTOP_AT(n)

__device__ __forceinline__ uint32_t smem_u32(const void* p) { return (uint32_t)__cvta_generic_to_shared(p); }
__device__ __forceinline__ void mbar_init(uint32_t bar, uint32_t cnt) {
  asm volatile("mbarrier.init.shared::cta.b64 [%0], %1;" ::"r"(bar), "r"(cnt) : "memory");
}
__device__ __forceinline__ void mbar_expect_tx(uint32_t bar, uint32_t bytes) {
  asm volatile("mbarrier.arrive.expect_tx.shared::cta.b64 _, [%0], %1;" ::"r"(bar), "r"(bytes) : "memory");
}
__device__ __forceinline__ void mbar_arrive(uint32_t bar) {
  asm volatile("mbarrier.arrive.shared::cta.b64 _, [%0];" ::"r"(bar) : "memory");
}
__device__ __forceinline__ void mbar_arrive_remote(uint32_t cluster_addr) {
  asm volatile("mbarrier.arrive.relaxed.cluster.shared::cluster.b64 _, [%0];" ::"r"(cluster_addr) : "memory");
}
__device__ __forceinline__ bool mbar_try(uint32_t bar, uint32_t parity) {
  uint32_t ok;
  asm volatile("{\n.reg .pred p;\nmbarrier.try_wait.parity.shared::cta.b64 p, [%1], %2;\nselp.u32 %0, 1, 0, p;\n}"
               : "=r"(ok) : "r"(bar), "r"(parity) : "memory");
  return ok != 0;
}
__device__ __forceinline__ bool mbar_try_cluster(uint32_t bar, uint32_t parity) {
  uint32_t ok;
  asm volatile("{\n.reg .pred p;\nmbarrier.try_wait.parity.acquire.cluster.shared::cta.b64 p, [%1], %2;\nselp.u32 %0, 1, 0, p;\n}"
               : "=r"(ok) : "r"(bar), "r"(parity) : "memory");
  return ok != 0;
}
constexpr uint32_t SPIN_LIMIT = 1u << 21;
constexpr uint32_t SMEM_ORIGIN = 1024;
constexpr int SM_DEAD = SM_MISC + 248;
__device__ __forceinline__ bool give_up(uint32_t sbase, uint32_t& n) {
  if (++n < 256u) return false;
  uint32_t dead;
  asm volatile("ld.volatile.shared.u32 %0, [%1];" : "=r"(dead) : "r"(sbase + SM_DEAD) : "memory");
  if (dead == 0u && n < SPIN_LIMIT) return false;
  asm volatile("st.volatile.shared.u32 [%0], %1;" ::"r"(sbase + SM_DEAD), "r"(1u) : "memory");
  return true;
}
__device__ __forceinline__ void mbar_wait(uint32_t sbase, uint32_t bar, uint32_t parity) {
  uint32_t n = 0;
  while (!mbar_try(bar, parity)) { if (give_up(sbase, n)) break; }
}
__device__ __forceinline__ void mbar_wait_cluster(uint32_t sbase, uint32_t bar, uint32_t parity) {
  uint32_t n = 0;
  while (!mbar_try_cluster(bar, parity)) { if (give_up(sbase, n)) break; }
}
__device__ __forceinline__ uint32_t mapa(uint32_t addr, uint32_t rank) {
  uint32_t r;
  asm volatile("mapa.shared::cluster.u32 %0, %1, %2;" : "=r"(r) : "r"(addr), "r"(rank));
  return r;
}
__device__ __forceinline__ void cluster_sync_all() {
  asm volatile("barrier.cluster.arrive.release.aligned;\nbarrier.cluster.wait.acquire.aligned;" ::: "memory");
}
__device__ __forceinline__ void bar_consumers(int id) { asm volatile("bar.sync %0, 256;" ::"r"(id) : "memory"); }

__device__ __forceinline__ void tma_2d(uint32_t dst, const CUtensorMap* m, uint32_t bar, int c0, int c1) {
  asm volatile("cp.async.bulk.tensor.2d.shared::cluster.global.mbarrier::complete_tx::bytes [%0], [%1, {%3, %4}], [%2];"
               ::"r"(dst), "l"(m), "r"(bar), "r"(c0), "r"(c1) : "memory");
}
__device__ __forceinline__ void tma_3d(uint32_t dst, const CUtensorMap* m, uint32_t bar, int c0, int c1, int c2) {
  asm volatile("cp.async.bulk.tensor.3d.shared::cluster.global.mbarrier::complete_tx::bytes [%0], [%1, {%3, %4, %5}], [%2];"
               ::"r"(dst), "l"(m), "r"(bar), "r"(c0), "r"(c1), "r"(c2) : "memory");
}
__device__ __forceinline__ void tma_4d(uint32_t dst, const CUtensorMap* m, uint32_t bar, int c0, int c1, int c2, int c3) {
  asm volatile("cp.async.bulk.tensor.4d.shared::cluster.global.mbarrier::complete_tx::bytes [%0], [%1, {%3, %4, %5, %6}], [%2];"
               ::"r"(dst), "l"(m), "r"(bar), "r"(c0), "r"(c1), "r"(c2), "r"(c3) : "memory");
}
__device__ __forceinline__ void l2_prefetch(const void* p, uint32_t bytes) {
  asm volatile("cp.async.bulk.prefetch.L2.global [%0], %1;" ::"l"(p), "r"(bytes) : "memory");
}

__device__ __forceinline__ uint4 ld_ll(const uint4* p) {
  uint4 v;
  asm volatile("ld.relaxed.gpu.global.v4.u32 {%0,%1,%2,%3}, [%4];" : "=r"(v.x), "=r"(v.y), "=r"(v.z), "=r"(v.w) : "l"(p) : "memory");
  return v;
}
__device__ __forceinline__ void st_ll(uint4* p, uint4 v) {
  asm volatile("st.relaxed.gpu.global.v4.u32 [%0], {%1,%2,%3,%4};" ::"l"(p), "r"(v.x), "r"(v.y), "r"(v.z), "r"(v.w) : "memory");
}
__device__ __forceinline__ uint4 lds128(uint32_t a) {
  uint4 v;
  asm volatile("ld.shared.v4.u32 {%0,%1,%2,%3}, [%4];" : "=r"(v.x), "=r"(v.y), "=r"(v.z), "=r"(v.w) : "r"(a) : "memory");
  return v;
}
__device__ __forceinline__ void sts128(uint32_t a, uint4 v) {
  asm volatile("st.shared.v4.u32 [%0], {%1,%2,%3,%4};" ::"r"(a), "r"(v.x), "r"(v.y), "r"(v.z), "r"(v.w) : "memory");
}
__device__ __forceinline__ void st_async128(uint32_t cluster_addr, uint4 v, uint32_t cluster_bar) {
  asm volatile("st.async.weak.shared::cluster.mbarrier::complete_tx::bytes.v4.b32 [%0], {%1,%2,%3,%4}, [%5];"
               ::"r"(cluster_addr), "r"(v.x), "r"(v.y), "r"(v.z), "r"(v.w), "r"(cluster_bar) : "memory");
}
__device__ __forceinline__ uint32_t pack2(float lo, float hi) {
  uint32_t r;
  asm("cvt.rn.bf16x2.f32 %0, %1, %2;" : "=r"(r) : "f"(hi), "f"(lo));
  return r;
}
__device__ __forceinline__ float bf_lo(uint32_t w) { return __uint_as_float(w << 16); }
__device__ __forceinline__ float bf_hi(uint32_t w) { return __uint_as_float(w & 0xffff0000u); }
__device__ __forceinline__ uint32_t set_tag(uint32_t w, uint32_t tag) { return (w & ~1u) | tag; }
__device__ __forceinline__ uint32_t movm(uint32_t a) {
  uint32_t d;
  asm volatile("movmatrix.sync.aligned.m8n8.trans.b16 %0, %1;" : "=r"(d) : "r"(a));
  return d;
}
__device__ __forceinline__ void mma16816(float (&d)[4], const uint4& a, uint32_t b0, uint32_t b1) {
  asm volatile("mma.sync.aligned.m16n8k16.row.col.f32.bf16.bf16.f32 {%0,%1,%2,%3}, {%4,%5,%6,%7}, {%8,%9}, {%0,%1,%2,%3};"
               : "+f"(d[0]), "+f"(d[1]), "+f"(d[2]), "+f"(d[3])
               : "r"(a.x), "r"(a.y), "r"(a.z), "r"(a.w), "r"(b0), "r"(b1));
}
__device__ __forceinline__ void wg_fence() { asm volatile("wgmma.fence.sync.aligned;" ::: "memory"); }
__device__ __forceinline__ void wg_commit() { asm volatile("wgmma.commit_group.sync.aligned;" ::: "memory"); }
template <int N> __device__ __forceinline__ void wg_wait() { asm volatile("wgmma.wait_group.sync.aligned %0;" ::"n"(N) : "memory"); }
__device__ __forceinline__ void keep(const uint4& a) { asm volatile("" ::"r"(a.x), "r"(a.y), "r"(a.z), "r"(a.w) : "memory"); }
template <int T> __device__ __forceinline__ void zero_acc(float (&d)[T]) {
#pragma unroll
  for (int i = 0; i < T; i++) d[i] = 0.f;
}
template <int T> __device__ __forceinline__ void fence_acc(float (&d)[T]) {
#pragma unroll
  for (int i = 0; i < T; i++) asm volatile("" : "+f"(d[i])::"memory");
}

template <int O, int T> __device__ __forceinline__ void wgmma_rs_n64(float (&d)[T], const uint4& a, uint64_t db, int scale_d) {
  asm volatile("{\n.reg .pred p;\nsetp.ne.b32 p, %37, 0;\n"
    "wgmma.mma_async.sync.aligned.m64n64k16.f32.bf16.bf16 "
    "{%0, %1, %2, %3, %4, %5, %6, %7, %8, %9, %10, %11, %12, %13, %14, %15, "
    "%16, %17, %18, %19, %20, %21, %22, %23, %24, %25, %26, %27, %28, %29, %30, %31}, "
    "{%32, %33, %34, %35}, %36, p, 1, 1, 1;\n}\n"
    : "+f"(d[O + 0]), "+f"(d[O + 1]), "+f"(d[O + 2]), "+f"(d[O + 3]), "+f"(d[O + 4]), "+f"(d[O + 5]), "+f"(d[O + 6]), "+f"(d[O + 7]),
      "+f"(d[O + 8]), "+f"(d[O + 9]), "+f"(d[O + 10]), "+f"(d[O + 11]), "+f"(d[O + 12]), "+f"(d[O + 13]), "+f"(d[O + 14]), "+f"(d[O + 15]),
      "+f"(d[O + 16]), "+f"(d[O + 17]), "+f"(d[O + 18]), "+f"(d[O + 19]), "+f"(d[O + 20]), "+f"(d[O + 21]), "+f"(d[O + 22]), "+f"(d[O + 23]),
      "+f"(d[O + 24]), "+f"(d[O + 25]), "+f"(d[O + 26]), "+f"(d[O + 27]), "+f"(d[O + 28]), "+f"(d[O + 29]), "+f"(d[O + 30]), "+f"(d[O + 31])
    : "r"(a.x), "r"(a.y), "r"(a.z), "r"(a.w), "l"(db), "r"(scale_d));
}
template <int O, int T> __device__ __forceinline__ void wgmma_rs_n128(float (&d)[T], const uint4& a, uint64_t db, int scale_d) {
  asm volatile("{\n.reg .pred p;\nsetp.ne.b32 p, %69, 0;\n"
    "wgmma.mma_async.sync.aligned.m64n128k16.f32.bf16.bf16 "
    "{%0, %1, %2, %3, %4, %5, %6, %7, %8, %9, %10, %11, %12, %13, %14, %15, "
    "%16, %17, %18, %19, %20, %21, %22, %23, %24, %25, %26, %27, %28, %29, %30, %31, "
    "%32, %33, %34, %35, %36, %37, %38, %39, %40, %41, %42, %43, %44, %45, %46, %47, "
    "%48, %49, %50, %51, %52, %53, %54, %55, %56, %57, %58, %59, %60, %61, %62, %63}, "
    "{%64, %65, %66, %67}, %68, p, 1, 1, 1;\n}\n"
    : "+f"(d[O + 0]), "+f"(d[O + 1]), "+f"(d[O + 2]), "+f"(d[O + 3]), "+f"(d[O + 4]), "+f"(d[O + 5]), "+f"(d[O + 6]), "+f"(d[O + 7]),
      "+f"(d[O + 8]), "+f"(d[O + 9]), "+f"(d[O + 10]), "+f"(d[O + 11]), "+f"(d[O + 12]), "+f"(d[O + 13]), "+f"(d[O + 14]), "+f"(d[O + 15]),
      "+f"(d[O + 16]), "+f"(d[O + 17]), "+f"(d[O + 18]), "+f"(d[O + 19]), "+f"(d[O + 20]), "+f"(d[O + 21]), "+f"(d[O + 22]), "+f"(d[O + 23]),
      "+f"(d[O + 24]), "+f"(d[O + 25]), "+f"(d[O + 26]), "+f"(d[O + 27]), "+f"(d[O + 28]), "+f"(d[O + 29]), "+f"(d[O + 30]), "+f"(d[O + 31]),
      "+f"(d[O + 32]), "+f"(d[O + 33]), "+f"(d[O + 34]), "+f"(d[O + 35]), "+f"(d[O + 36]), "+f"(d[O + 37]), "+f"(d[O + 38]), "+f"(d[O + 39]),
      "+f"(d[O + 40]), "+f"(d[O + 41]), "+f"(d[O + 42]), "+f"(d[O + 43]), "+f"(d[O + 44]), "+f"(d[O + 45]), "+f"(d[O + 46]), "+f"(d[O + 47]),
      "+f"(d[O + 48]), "+f"(d[O + 49]), "+f"(d[O + 50]), "+f"(d[O + 51]), "+f"(d[O + 52]), "+f"(d[O + 53]), "+f"(d[O + 54]), "+f"(d[O + 55]),
      "+f"(d[O + 56]), "+f"(d[O + 57]), "+f"(d[O + 58]), "+f"(d[O + 59]), "+f"(d[O + 60]), "+f"(d[O + 61]), "+f"(d[O + 62]), "+f"(d[O + 63])
    : "r"(a.x), "r"(a.y), "r"(a.z), "r"(a.w), "l"(db), "r"(scale_d));
}
template <int O, int T> __device__ __forceinline__ void wgmma_rs_n192(float (&d)[T], const uint4& a, uint64_t db, int scale_d) {
  asm volatile("{\n.reg .pred p;\nsetp.ne.b32 p, %101, 0;\n"
    "wgmma.mma_async.sync.aligned.m64n192k16.f32.bf16.bf16 "
    "{%0, %1, %2, %3, %4, %5, %6, %7, %8, %9, %10, %11, %12, %13, %14, %15, "
    "%16, %17, %18, %19, %20, %21, %22, %23, %24, %25, %26, %27, %28, %29, %30, %31, "
    "%32, %33, %34, %35, %36, %37, %38, %39, %40, %41, %42, %43, %44, %45, %46, %47, "
    "%48, %49, %50, %51, %52, %53, %54, %55, %56, %57, %58, %59, %60, %61, %62, %63, "
    "%64, %65, %66, %67, %68, %69, %70, %71, %72, %73, %74, %75, %76, %77, %78, %79, "
    "%80, %81, %82, %83, %84, %85, %86, %87, %88, %89, %90, %91, %92, %93, %94, %95}, "
    "{%96, %97, %98, %99}, %100, p, 1, 1, 1;\n}\n"
    : "+f"(d[O + 0]), "+f"(d[O + 1]), "+f"(d[O + 2]), "+f"(d[O + 3]), "+f"(d[O + 4]), "+f"(d[O + 5]), "+f"(d[O + 6]), "+f"(d[O + 7]),
      "+f"(d[O + 8]), "+f"(d[O + 9]), "+f"(d[O + 10]), "+f"(d[O + 11]), "+f"(d[O + 12]), "+f"(d[O + 13]), "+f"(d[O + 14]), "+f"(d[O + 15]),
      "+f"(d[O + 16]), "+f"(d[O + 17]), "+f"(d[O + 18]), "+f"(d[O + 19]), "+f"(d[O + 20]), "+f"(d[O + 21]), "+f"(d[O + 22]), "+f"(d[O + 23]),
      "+f"(d[O + 24]), "+f"(d[O + 25]), "+f"(d[O + 26]), "+f"(d[O + 27]), "+f"(d[O + 28]), "+f"(d[O + 29]), "+f"(d[O + 30]), "+f"(d[O + 31]),
      "+f"(d[O + 32]), "+f"(d[O + 33]), "+f"(d[O + 34]), "+f"(d[O + 35]), "+f"(d[O + 36]), "+f"(d[O + 37]), "+f"(d[O + 38]), "+f"(d[O + 39]),
      "+f"(d[O + 40]), "+f"(d[O + 41]), "+f"(d[O + 42]), "+f"(d[O + 43]), "+f"(d[O + 44]), "+f"(d[O + 45]), "+f"(d[O + 46]), "+f"(d[O + 47]),
      "+f"(d[O + 48]), "+f"(d[O + 49]), "+f"(d[O + 50]), "+f"(d[O + 51]), "+f"(d[O + 52]), "+f"(d[O + 53]), "+f"(d[O + 54]), "+f"(d[O + 55]),
      "+f"(d[O + 56]), "+f"(d[O + 57]), "+f"(d[O + 58]), "+f"(d[O + 59]), "+f"(d[O + 60]), "+f"(d[O + 61]), "+f"(d[O + 62]), "+f"(d[O + 63]),
      "+f"(d[O + 64]), "+f"(d[O + 65]), "+f"(d[O + 66]), "+f"(d[O + 67]), "+f"(d[O + 68]), "+f"(d[O + 69]), "+f"(d[O + 70]), "+f"(d[O + 71]),
      "+f"(d[O + 72]), "+f"(d[O + 73]), "+f"(d[O + 74]), "+f"(d[O + 75]), "+f"(d[O + 76]), "+f"(d[O + 77]), "+f"(d[O + 78]), "+f"(d[O + 79]),
      "+f"(d[O + 80]), "+f"(d[O + 81]), "+f"(d[O + 82]), "+f"(d[O + 83]), "+f"(d[O + 84]), "+f"(d[O + 85]), "+f"(d[O + 86]), "+f"(d[O + 87]),
      "+f"(d[O + 88]), "+f"(d[O + 89]), "+f"(d[O + 90]), "+f"(d[O + 91]), "+f"(d[O + 92]), "+f"(d[O + 93]), "+f"(d[O + 94]), "+f"(d[O + 95])
    : "r"(a.x), "r"(a.y), "r"(a.z), "r"(a.w), "l"(db), "r"(scale_d));
}
template <int O, int T> __device__ __forceinline__ void wgmma_rs_n256(float (&d)[T], const uint4& a, uint64_t db, int scale_d) {
  asm volatile("{\n.reg .pred p;\nsetp.ne.b32 p, %133, 0;\n"
    "wgmma.mma_async.sync.aligned.m64n256k16.f32.bf16.bf16 "
    "{%0, %1, %2, %3, %4, %5, %6, %7, %8, %9, %10, %11, %12, %13, %14, %15, "
    "%16, %17, %18, %19, %20, %21, %22, %23, %24, %25, %26, %27, %28, %29, %30, %31, "
    "%32, %33, %34, %35, %36, %37, %38, %39, %40, %41, %42, %43, %44, %45, %46, %47, "
    "%48, %49, %50, %51, %52, %53, %54, %55, %56, %57, %58, %59, %60, %61, %62, %63, "
    "%64, %65, %66, %67, %68, %69, %70, %71, %72, %73, %74, %75, %76, %77, %78, %79, "
    "%80, %81, %82, %83, %84, %85, %86, %87, %88, %89, %90, %91, %92, %93, %94, %95, "
    "%96, %97, %98, %99, %100, %101, %102, %103, %104, %105, %106, %107, %108, %109, %110, %111, "
    "%112, %113, %114, %115, %116, %117, %118, %119, %120, %121, %122, %123, %124, %125, %126, %127}, "
    "{%128, %129, %130, %131}, %132, p, 1, 1, 1;\n}\n"
    : "+f"(d[O + 0]), "+f"(d[O + 1]), "+f"(d[O + 2]), "+f"(d[O + 3]), "+f"(d[O + 4]), "+f"(d[O + 5]), "+f"(d[O + 6]), "+f"(d[O + 7]),
      "+f"(d[O + 8]), "+f"(d[O + 9]), "+f"(d[O + 10]), "+f"(d[O + 11]), "+f"(d[O + 12]), "+f"(d[O + 13]), "+f"(d[O + 14]), "+f"(d[O + 15]),
      "+f"(d[O + 16]), "+f"(d[O + 17]), "+f"(d[O + 18]), "+f"(d[O + 19]), "+f"(d[O + 20]), "+f"(d[O + 21]), "+f"(d[O + 22]), "+f"(d[O + 23]),
      "+f"(d[O + 24]), "+f"(d[O + 25]), "+f"(d[O + 26]), "+f"(d[O + 27]), "+f"(d[O + 28]), "+f"(d[O + 29]), "+f"(d[O + 30]), "+f"(d[O + 31]),
      "+f"(d[O + 32]), "+f"(d[O + 33]), "+f"(d[O + 34]), "+f"(d[O + 35]), "+f"(d[O + 36]), "+f"(d[O + 37]), "+f"(d[O + 38]), "+f"(d[O + 39]),
      "+f"(d[O + 40]), "+f"(d[O + 41]), "+f"(d[O + 42]), "+f"(d[O + 43]), "+f"(d[O + 44]), "+f"(d[O + 45]), "+f"(d[O + 46]), "+f"(d[O + 47]),
      "+f"(d[O + 48]), "+f"(d[O + 49]), "+f"(d[O + 50]), "+f"(d[O + 51]), "+f"(d[O + 52]), "+f"(d[O + 53]), "+f"(d[O + 54]), "+f"(d[O + 55]),
      "+f"(d[O + 56]), "+f"(d[O + 57]), "+f"(d[O + 58]), "+f"(d[O + 59]), "+f"(d[O + 60]), "+f"(d[O + 61]), "+f"(d[O + 62]), "+f"(d[O + 63]),
      "+f"(d[O + 64]), "+f"(d[O + 65]), "+f"(d[O + 66]), "+f"(d[O + 67]), "+f"(d[O + 68]), "+f"(d[O + 69]), "+f"(d[O + 70]), "+f"(d[O + 71]),
      "+f"(d[O + 72]), "+f"(d[O + 73]), "+f"(d[O + 74]), "+f"(d[O + 75]), "+f"(d[O + 76]), "+f"(d[O + 77]), "+f"(d[O + 78]), "+f"(d[O + 79]),
      "+f"(d[O + 80]), "+f"(d[O + 81]), "+f"(d[O + 82]), "+f"(d[O + 83]), "+f"(d[O + 84]), "+f"(d[O + 85]), "+f"(d[O + 86]), "+f"(d[O + 87]),
      "+f"(d[O + 88]), "+f"(d[O + 89]), "+f"(d[O + 90]), "+f"(d[O + 91]), "+f"(d[O + 92]), "+f"(d[O + 93]), "+f"(d[O + 94]), "+f"(d[O + 95]),
      "+f"(d[O + 96]), "+f"(d[O + 97]), "+f"(d[O + 98]), "+f"(d[O + 99]), "+f"(d[O + 100]), "+f"(d[O + 101]), "+f"(d[O + 102]), "+f"(d[O + 103]),
      "+f"(d[O + 104]), "+f"(d[O + 105]), "+f"(d[O + 106]), "+f"(d[O + 107]), "+f"(d[O + 108]), "+f"(d[O + 109]), "+f"(d[O + 110]), "+f"(d[O + 111]),
      "+f"(d[O + 112]), "+f"(d[O + 113]), "+f"(d[O + 114]), "+f"(d[O + 115]), "+f"(d[O + 116]), "+f"(d[O + 117]), "+f"(d[O + 118]), "+f"(d[O + 119]),
      "+f"(d[O + 120]), "+f"(d[O + 121]), "+f"(d[O + 122]), "+f"(d[O + 123]), "+f"(d[O + 124]), "+f"(d[O + 125]), "+f"(d[O + 126]), "+f"(d[O + 127])
    : "r"(a.x), "r"(a.y), "r"(a.z), "r"(a.w), "l"(db), "r"(scale_d));
}

template <int N> __device__ __forceinline__ void load_pk(uint4* a, const uint4* p) {
#pragma unroll
  for (int i = 0; i < N; i++) a[i] = ld_ll(p + i * 32);
}
template <int N> __device__ __forceinline__ bool ok_pk(const uint4* a, uint32_t tag) {
  uint32_t x = 0;
#pragma unroll
  for (int i = 0; i < N; i++) x |= a[i].x ^ tag;
  return __all_sync(0xffffffffu, (x & 1u) == 0u);
}
template <int N> __device__ __forceinline__ void ensure_pk(uint32_t sbase, uint4* a, const uint4* p, uint32_t tag) {
  uint32_t n = 0;
  while (!ok_pk<N>(a, tag)) { load_pk<N>(a, p); if (give_up(sbase, n)) break; }
}

constexpr int NSTAGE = 48;
__host__ __device__ constexpr int st_len(int s) { return s < 8 ? 3 : s < 16 ? 2 : s < 24 ? 4 : s < 32 ? 3 : 2; }
__host__ __device__ constexpr int st_g0(int s) {
  int pos = 0, g0 = 0;
  for (int i = 0; i <= s; i++) {
    if (pos + st_len(i) > NGRAN) pos = 0;
    g0 = pos;
    pos += st_len(i);
  }
  return g0;
}
__host__ __device__ constexpr int cnt_first(int g, int s) {
  int n = 0;
  for (int i = 0; i < s; i++) n += (st_g0(i) == g);
  return n;
}
__host__ __device__ constexpr int cnt_cover(int g, int s) {
  int n = 0;
  for (int i = 0; i < s; i++) n += (g >= st_g0(i) && g < st_g0(i) + st_len(i));
  return n;
}
template <int I> struct IC { static constexpr int value = I; };
template <int B, int E, typename F> __device__ __forceinline__ void static_for(F&& f) {
  if constexpr (B < E) { f(IC<B>{}); static_for<B + 1, E>(f); }
}
template <int S> __device__ __forceinline__ void cons_acquire(uint32_t sbase, uint32_t L) {
  constexpr int g0 = st_g0(S);
  constexpr uint32_t p0 = cnt_first(g0, S) & 1, odd = cnt_first(g0, NSTAGE) & 1;
  mbar_wait(sbase, sbase + SM_MISC + BAR_FULL + 8 * g0, p0 ^ (L & odd));
}
template <int S> __device__ __forceinline__ void cons_release(uint32_t sbase, int lane) {
  if (lane < st_len(S)) mbar_arrive(sbase + SM_MISC + BAR_EMPTY + 8 * st_g0(S) + 8 * lane);
}
template <int S> __device__ __forceinline__ uint32_t prod_acquire(uint32_t sbase, uint32_t L, uint32_t bytes) {
  constexpr int g0 = st_g0(S);
  static_for<0, st_len(S)>([&](auto I) {
    constexpr int g = g0 + I.value;
    constexpr uint32_t p0 = cnt_cover(g, S) & 1, odd = cnt_cover(g, NSTAGE) & 1;
    mbar_wait(sbase, sbase + SM_MISC + BAR_EMPTY + 8 * g, p0 ^ (L & odd) ^ 1u);
  });
  mbar_expect_tx(sbase + SM_MISC + BAR_FULL + 8 * g0, bytes);
  return g0;
}
template <int S, int KSTEP_BYTES, int LBO, int SBO, int SWZ> __device__ __forceinline__ constexpr uint64_t st_desc(int k) {
  return (uint64_t)((SMEM_ORIGIN + st_g0(S) * GRAN + k * KSTEP_BYTES) >> 4) | ((uint64_t)(LBO >> 4) << 16) |
         ((uint64_t)(SBO >> 4) << 32) | ((uint64_t)SWZ << 62);
}

__device__ __forceinline__ void combine_stats(const uint4& p0, const uint4& p1, float& mean_lo, float& rstd_lo, float& mean_hi, float& rstd_hi) {
  float m0 = __uint_as_float(p0.x), q0 = __uint_as_float(p0.y), m0h = __uint_as_float(p0.z), q0h = __uint_as_float(p0.w);
  float m1 = __uint_as_float(p1.x), q1 = __uint_as_float(p1.y), m1h = __uint_as_float(p1.z), q1h = __uint_as_float(p1.w);
  float s = m0 + m1, sh = m0h + m1h;
  s += __shfl_xor_sync(0xffffffffu, s, 1); sh += __shfl_xor_sync(0xffffffffu, sh, 1);
  s += __shfl_xor_sync(0xffffffffu, s, 2); sh += __shfl_xor_sync(0xffffffffu, sh, 2);
  mean_lo = s * 0.125f; mean_hi = sh * 0.125f;
  float d0 = m0 - mean_lo, d1 = m1 - mean_lo, d0h = m0h - mean_hi, d1h = m1h - mean_hi;
  float t = q0 + q1 + 64.f * (d0 * d0 + d1 * d1), th = q0h + q1h + 64.f * (d0h * d0h + d1h * d1h);
  t += __shfl_xor_sync(0xffffffffu, t, 1); th += __shfl_xor_sync(0xffffffffu, th, 1);
  t += __shfl_xor_sync(0xffffffffu, t, 2); th += __shfl_xor_sync(0xffffffffu, th, 2);
  rstd_lo = rsqrtf(t * (1.f / 512.f) + 1e-5f);
  rstd_hi = rsqrtf(th * (1.f / 512.f) + 1e-5f);
}
__device__ __forceinline__ uint4 local_stats(const float (&v)[32]) {
  float s = 0.f, sh = 0.f;
#pragma unroll
  for (int i = 0; i < 4; i++) {
    s += (v[8 * i + 0] + v[8 * i + 1]) + (v[8 * i + 4] + v[8 * i + 5]);
    sh += (v[8 * i + 2] + v[8 * i + 3]) + (v[8 * i + 6] + v[8 * i + 7]);
  }
  s += __shfl_xor_sync(0xffffffffu, s, 1); sh += __shfl_xor_sync(0xffffffffu, sh, 1);
  s += __shfl_xor_sync(0xffffffffu, s, 2); sh += __shfl_xor_sync(0xffffffffu, sh, 2);
  float m = s * (1.f / 64.f), mh = sh * (1.f / 64.f);
  float q = 0.f, qh = 0.f;
#pragma unroll
  for (int i = 0; i < 4; i++) {
    float a = v[8 * i + 0] - m, b = v[8 * i + 1] - m, c = v[8 * i + 4] - m, d = v[8 * i + 5] - m;
    q += (a * a + b * b) + (c * c + d * d);
    float e = v[8 * i + 2] - mh, f = v[8 * i + 3] - mh, g = v[8 * i + 6] - mh, h = v[8 * i + 7] - mh;
    qh += (e * e + f * f) + (g * g + h * h);
  }
  q += __shfl_xor_sync(0xffffffffu, q, 1); qh += __shfl_xor_sync(0xffffffffu, qh, 1);
  q += __shfl_xor_sync(0xffffffffu, q, 2); qh += __shfl_xor_sync(0xffffffffu, qh, 2);
  return make_uint4(__float_as_uint(m), __float_as_uint(q), __float_as_uint(mh), __float_as_uint(qh));
}

__device__ __forceinline__ void owner_ln_publish(uint32_t sbase, const float (&v)[32], uint32_t tphase, uint32_t tag_xn) {
  PHASE_VARS;
  const uint32_t bars = sbase + SM_MISC;
  const int sg = warp >> 2, qt = warp & 3;
  const int oslab = 2 * ca + sg;
  const int step0 = 16 * cbit + 4 * qt;
  uint4 st = local_stats(v);
  const uint32_t tb = bars + BAR_TSTAT + 8 * sg;
  const uint32_t slot = sbase + SM_TSTAT + sg * 1024 + (4 * cbit + qt) * 128 + qr * 16;
  if (qt == 0 && lane == 0) mbar_expect_tx(tb, 1024);
  if (qc == 0) {
    st_async128(mapa(slot, 0), st, mapa(tb, 0));
    st_async128(mapa(slot, 1), st, mapa(tb, 1));
  }
  mbar_wait_cluster(sbase, tb, tphase);
  const uint32_t rd = sbase + SM_TSTAT + sg * 1024 + qc * 256 + qr * 16;
  uint4 p0 = lds128(rd), p1 = lds128(rd + 128);
  float ml, rl, mh, rh;
  combine_stats(p0, p1, ml, rl, mh, rh);
  const float bl = -ml * rl, bh = -mh * rh;
  uint4* xn = g_xn + ((c * 8 + oslab) * 32 + step0) * 32 + lane;
  uint4* xr = g_xraw + ((c * 8 + oslab) * 32 + step0) * 32 + lane;
#pragma unroll
  for (int i = 0; i < 4; i++) {
    uint4 o;
    o.x = set_tag(pack2(fmaf(v[8 * i + 0], rl, bl), fmaf(v[8 * i + 1], rl, bl)), tag_xn);
    o.y = pack2(fmaf(v[8 * i + 2], rh, bh), fmaf(v[8 * i + 3], rh, bh));
    o.z = pack2(fmaf(v[8 * i + 4], rl, bl), fmaf(v[8 * i + 5], rl, bl));
    o.w = pack2(fmaf(v[8 * i + 6], rh, bh), fmaf(v[8 * i + 7], rh, bh));
    st_ll(xn + i * 32, o);
  }
#pragma unroll
  for (int i = 0; i < 4; i++) {
    uint4 o;
    o.x = set_tag(pack2(v[8 * i + 0], v[8 * i + 1]), 1u);
    o.y = pack2(v[8 * i + 2], v[8 * i + 3]);
    o.z = pack2(v[8 * i + 4], v[8 * i + 5]);
    o.w = pack2(v[8 * i + 6], v[8 * i + 7]);
    st_ll(xr + i * 32, o);
  }
}

__device__ __forceinline__ uint4 pack8(const float* a) {
  return make_uint4(pack2(a[0], a[1]), pack2(a[2], a[3]), pack2(a[4], a[5]), pack2(a[6], a[7]));
}
__device__ __forceinline__ uint4 glu8(const float* g) {
  return make_uint4(pack2(g[0] * g[16], g[1] * g[17]), pack2(g[2] * g[18], g[3] * g[19]), pack2(g[4] * g[20], g[5] * g[21]), pack2(g[6] * g[22], g[7] * g[23]));
}

__global__ void __launch_bounds__(NTHREADS, 1)
fused_kernel(const __grid_constant__ CUtensorMap m_qkv, const __grid_constant__ CUtensorMap m_wo,
             const __grid_constant__ CUtensorMap m_gu4, const __grid_constant__ CUtensorMap m_gu3,
             const __grid_constant__ CUtensorMap m_wd, const __nv_bfloat16* __restrict__ x_in,
             __nv_bfloat16* __restrict__ out, const char* __restrict__ w_o, const char* __restrict__ w_g,
             const char* __restrict__ w_u, const char* __restrict__ w_d
) {
  extern __shared__ __align__(1024) unsigned char smem_raw[];
  const uint32_t sbase = smem_u32(smem_raw);
  const uint32_t bars = sbase + SM_MISC;

  if (threadIdx.x == 0) {
    for (int i = 0; i < NGRAN; i++) { mbar_init(bars + BAR_FULL + 8 * i, 1); mbar_init(bars + BAR_EMPTY + 8 * i, 8); }
    for (int i = 0; i < 2; i++) { mbar_init(bars + BAR_HRECV + 8 * i, 1); mbar_init(bars + BAR_HREADY + 8 * i, 4); mbar_init(bars + BAR_TSTAT + 8 * i, 1); }
    asm volatile("st.volatile.shared.u32 [%0], %1;" ::"r"(sbase + SM_DEAD), "r"((sbase & 0xFFFFFFu) == SMEM_ORIGIN ? 0u : 1u) : "memory");
    asm volatile("fence.mbarrier_init.release.cluster;" ::: "memory");
  }
  __syncthreads();
  cluster_sync_all();

  if (threadIdx.x >= 256) {
    asm volatile("setmaxnreg.dec.sync.aligned.u32 40;");
    const int warp = threadIdx.x >> 5, lane = threadIdx.x & 31;
    const int j = blockIdx.x & 7, a = j >> 1, b = j & 1;
    if (warp == 8 && lane == 0) {
#pragma unroll 1
      for (uint32_t L = 0; L < 2; L++) {
        PSTOP_AT(L == 0 ? 0 : 3);
        static_for<0, 8>([&](auto I) {
          constexpr int kb = I.value;
          uint32_t g0 = prod_acquire<kb>(sbase, L, 24576);
          tma_3d(sbase + g0 * GRAN, &m_qkv, bars + BAR_FULL + 8 * g0, 64 * j, 64 * kb, 0);
        });
        PSTOP_AT(10 * L + 1);
        static_for<0, 8>([&](auto I) {
          constexpr int i = I.value;
          uint32_t g0 = prod_acquire<8 + i>(sbase, L, 16384);
          tma_3d(sbase + g0 * GRAN, &m_wo, bars + BAR_FULL + 8 * g0, 0, 256 * (i & 1) + 64 * (i >> 1), 2 * a);
        });
        PSTOP_AT(10 * L + 2);
        static_for<0, 8>([&](auto I) {
          constexpr int kb = I.value;
          uint32_t g0 = prod_acquire<16 + kb>(sbase, L, 32768);
          tma_4d(sbase + g0 * GRAN, &m_gu4, bars + BAR_FULL + 8 * g0, 0, 64 * kb, 0, 7 * j);
        });
        static_for<0, 8>([&](auto I) {
          constexpr int kb = I.value;
          uint32_t g0 = prod_acquire<24 + kb>(sbase, L, 24576);
          tma_4d(sbase + g0 * GRAN, &m_gu3, bars + BAR_FULL + 8 * g0, 0, 64 * kb, 0, 7 * j + 4);
        });
        static_for<0, 16>([&](auto I) {
          constexpr int i = I.value;
          uint32_t g0 = prod_acquire<32 + i>(sbase, L, 14336);
          const int src = (i < 8) ? j : (j ^ 1);
          tma_2d(sbase + g0 * GRAN, &m_wd, bars + BAR_FULL + 8 * g0, 256 * b + 64 * ((i >> 1) & 3), 224 * src + 112 * (i & 1));
        });
      }
    } else if (warp == 9) {
      const int cta = blockIdx.x;
      if (lane == 0) l2_prefetch(w_o + cta * 4096, 4096);
      if (lane == 1) l2_prefetch(w_g + cta * 14336, 14336);
      if (lane == 2) l2_prefetch(w_u + cta * 14336, 14336);
      if (lane == 3) l2_prefetch(w_d + cta * 14336, 14336);
    }
    __syncwarp();
    asm volatile("barrier.cluster.arrive.release.aligned;\nbarrier.cluster.wait.acquire.aligned; // producer" ::: "memory");
  } else {
    asm volatile("setmaxnreg.inc.sync.aligned.u32 232;");
    TS(0);

    {
      PHASE_VARS;
      const int sg = warp >> 2, qt = warp & 3;
      const int oslab = 2 * ca + sg;
      const int step0 = 16 * cbit + 4 * qt;
      float v[32];
      const uint32_t* xp = reinterpret_cast<const uint32_t*>(x_in + (size_t)(c * 128 + oslab * 16 + qr) * 512 + step0 * 16 + qc * 2);
#pragma unroll
      for (int i = 0; i < 4; i++) {
        uint32_t w0 = __ldg(xp + i * 8), w1 = __ldg(xp + 8 * 256 + i * 8), w2 = __ldg(xp + i * 8 + 4), w3 = __ldg(xp + 8 * 256 + i * 8 + 4);
        v[8 * i + 0] = bf_lo(w0); v[8 * i + 1] = bf_hi(w0); v[8 * i + 2] = bf_lo(w1); v[8 * i + 3] = bf_hi(w1);
        v[8 * i + 4] = bf_lo(w2); v[8 * i + 5] = bf_hi(w2); v[8 * i + 6] = bf_lo(w3); v[8 * i + 7] = bf_hi(w3);
      }
      owner_ln_publish(sbase, v, 0u, 1u);
    }
    STOP_AT(0);
    TS(1);

#pragma unroll 1
    for (uint32_t L = 0; L < 2; L++) {
      const uint32_t tag = L ^ 1;
      bar_consumers(1);
      {
        PHASE_VARS;
        uint4 qf[4], kf[4], vf[4], pk[4], pv[4];
        const uint4* halo_src = g_halo + (((L * 16 + (c > 0 ? c - 1 : 0)) * 8 + j) * 8) * 32 + lane;
        {
          float acc[96];
          zero_acc(acc);
          uint4 A[3][4];
          const uint4* xs = g_xn + ((c * 8 + slab) * 32) * 32 + lane;
          load_pk<4>(A[0], xs);
          ensure_pk<4>(sbase, A[0], xs, tag);
          TS(2 + 20 * L);
          load_pk<4>(A[1], xs + 128);
          static_for<0, 8>([&](auto I) {
            constexpr int kb = I.value;
            cons_acquire<kb>(sbase, L);
            wg_fence();
#pragma unroll
            for (int k = 0; k < 4; k++) wgmma_rs_n192<0>(acc, A[kb % 3][k], st_desc<kb, 2048, 8192, 1024, 1>(k), 1);
            wg_commit();
            if constexpr (kb > 0) {
              wg_wait<1>();
#pragma unroll
              for (int k = 0; k < 4; k++) keep(A[(kb + 2) % 3][k]);
              cons_release<kb - 1>(sbase, lane);
            }
            if constexpr (kb + 1 < 8) ensure_pk<4>(sbase, A[(kb + 1) % 3], xs + (kb + 1) * 128, tag);
            if constexpr (kb + 2 < 8) load_pk<4>(A[(kb + 2) % 3], xs + (kb + 2) * 128);
          });
#pragma unroll
          for (int h = 0; h < 4; h++) { pk[h] = make_uint4(0, 0, 0, 0); pv[h] = make_uint4(0, 0, 0, 0); }
          wg_wait<0>();
          TS(3 + 20 * L);
          fence_acc(acc);
#pragma unroll
          for (int k = 0; k < 4; k++) keep(A[1][k]);
          cons_release<7>(sbase, lane);
#pragma unroll
          for (int h = 0; h < 4; h++) kf[h] = pack8(&acc[32 + 8 * h]);
#pragma unroll
          for (int h = 0; h < 4; h++) {
            uint4 t = pack8(&acc[64 + 8 * h]);
            vf[h] = make_uint4(movm(t.x), movm(t.y), movm(t.z), movm(t.w));
          }
          if (slab == 7 && c < 15) {
            uint4* hd = g_halo + (((L * 16 + c) * 8 + j) * 8) * 32 + lane;
#pragma unroll
            for (int h = 0; h < 4; h++) {
              uint4 t = kf[h]; t.x |= 1u; st_ll(hd + h * 32, t);
              t = vf[h]; t.x |= 1u; st_ll(hd + 128 + h * 32, t);
            }
          }
          const uint32_t kvw = areg + AR_KV + w * 4096 + lane * 16;
#pragma unroll
          for (int h = 0; h < 4; h++) { sts128(kvw + h * 512, kf[h]); sts128(kvw + 2048 + h * 512, vf[h]); }
          if (slab == 0 && c > 0) { load_pk<4>(pk, halo_src); load_pk<4>(pv, halo_src + 128); }
#pragma unroll
          for (int h = 0; h < 4; h++) qf[h] = pack8(&acc[8 * h]);
        }
        bar_consumers(2);
        const bool first = (slab == 0) && (c == 0);
        if (slab > 0) {
          const int ps = slab - 1;
          const uint32_t kvr = sbase + SM_AREG + (ps >> 2) * 65536 + AR_KV + (ps & 3) * 4096 + lane * 16;
#pragma unroll
          for (int h = 0; h < 4; h++) { pk[h] = lds128(kvr + h * 512); pv[h] = lds128(kvr + 2048 + h * 512); }
        } else if (c > 0) {
          ensure_pk<4>(sbase, pk, halo_src, 1u);
          ensure_pk<4>(sbase, pv, halo_src + 128, 1u);
          uint4* hz = const_cast<uint4*>(halo_src);
#pragma unroll
          for (int h = 0; h < 8; h++) st_ll(hz + h * 32, make_uint4(0, 0, 0, 0));
        }
        TS(4 + 20 * L);
        const bool e = qr & 1;
        const bool newer = (2 * qc + (qr & 1)) <= qr;
        const float sc = 0.25f * 1.4426950408889634f;
        const float NEG = -1e30f;
        uint4* od = g_o + ((c * 8 + slab) * 32 + 4 * j) * 32 + lane;
#pragma unroll
        for (int h = 0; h < 4; h++) {
          float s0[4] = {0, 0, 0, 0}, s1[4] = {0, 0, 0, 0}, s2[4] = {0, 0, 0, 0}, s3[4] = {0, 0, 0, 0};
          mma16816(s0, qf[h], pk[h].x, pk[h].z);
          mma16816(s1, qf[h], pk[h].y, pk[h].w);
          mma16816(s2, qf[h], kf[h].x, kf[h].z);
          mma16816(s3, qf[h], kf[h].y, kf[h].w);
          float mid_l = e ? s1[1] : s1[0];
          float oth_l = newer ? (e ? s2[1] : s2[0]) : (e ? s0[1] : s0[0]);
          float mid_h = e ? s2[3] : s2[2];
          float oth_h = newer ? (e ? s3[3] : s3[2]) : (e ? s1[3] : s1[2]);
          if (first) { mid_l = NEG; if (!newer) { oth_l = NEG; oth_h = NEG; } }
          float ml = fmaxf(mid_l, oth_l), mh = fmaxf(mid_h, oth_h);
          ml = fmaxf(ml, __shfl_xor_sync(0xffffffffu, ml, 1)); mh = fmaxf(mh, __shfl_xor_sync(0xffffffffu, mh, 1));
          ml = fmaxf(ml, __shfl_xor_sync(0xffffffffu, ml, 2)); mh = fmaxf(mh, __shfl_xor_sync(0xffffffffu, mh, 2));
          float pml = exp2f((mid_l - ml) * sc), pol = exp2f((oth_l - ml) * sc);
          float pmh = exp2f((mid_h - mh) * sc), poh = exp2f((oth_h - mh) * sc);
          float sl = pml + pol, sh = pmh + poh;
          sl += __shfl_xor_sync(0xffffffffu, sl, 1); sh += __shfl_xor_sync(0xffffffffu, sh, 1);
          sl += __shfl_xor_sync(0xffffffffu, sl, 2); sh += __shfl_xor_sync(0xffffffffu, sh, 2);
          const float il = __fdividef(1.f, sl), ih = __fdividef(1.f, sh);
          const uint32_t sft = e ? 16u : 0u;
          const uint32_t bml = (pack2(pml * il, 0.f) & 0xffffu) << sft, bol = (pack2(pol * il, 0.f) & 0xffffu) << sft;
          const uint32_t bmh = (pack2(pmh * ih, 0.f) & 0xffffu) << sft, boh = (pack2(poh * ih, 0.f) & 0xffffu) << sft;
          uint4 P0 = make_uint4(newer ? 0u : bol, 0u, bml, newer ? 0u : boh);
          uint4 P1 = make_uint4(newer ? bol : 0u, bmh, 0u, newer ? boh : 0u);
          float o0[4] = {0, 0, 0, 0}, o1[4] = {0, 0, 0, 0};
          mma16816(o0, P0, pv[h].x, pv[h].y);
          mma16816(o1, P0, pv[h].z, pv[h].w);
          mma16816(o0, P1, vf[h].x, vf[h].y);
          mma16816(o1, P1, vf[h].z, vf[h].w);
          uint4 o = make_uint4(set_tag(pack2(o0[0], o0[1]), tag), pack2(o0[2], o0[3]), pack2(o1[0], o1[1]), pack2(o1[2], o1[3]));
          st_ll(od + h * 32, o);
        }
      }
      TS(5 + 20 * L);
      if (L == 0) { STOP_AT(1); } else { STOP_AT(11); }
      {
        PHASE_VARS;
        const int slabA = 4 * cbit + w;
        float acc[64];
        zero_acc(acc);
        uint4 A[16];
        uint4 xr[4];
        const uint4* os = g_o + ((c * 8 + slabA) * 32 + 16 * g) * 32 + lane;
        uint4* xp = g_xraw + ((c * 8 + slabA) * 32 + 8 * ca + 4 * g) * 32 + lane;
        load_pk<4>(A, os);
        ensure_pk<4>(sbase, A, os, tag);
        TS(6 + 20 * L);
        load_pk<12>(A + 4, os + 128);
        load_pk<4>(xr, xp);
        static_for<0, 8>([&](auto I) {
          constexpr int i = I.value, kb = i >> 1;
          cons_acquire<8 + i>(sbase, L);
          if ((i & 1) == g) {
            if constexpr (kb > 0) ensure_pk<4>(sbase, A + 4 * kb, os + kb * 128, tag);
            wg_fence();
#pragma unroll
            for (int k = 0; k < 4; k++) wgmma_rs_n128<0>(acc, A[4 * kb + k], st_desc<8 + i, 2048, 8192, 1024, 1>(k), 1);
            wg_commit();
            if constexpr (kb > 0) { wg_wait<1>(); cons_release<8 + i - 2>(sbase, lane); }
          } else {
            cons_release<8 + i>(sbase, lane);
          }
        });
        wg_wait<0>();
        TS(7 + 20 * L);
        fence_acc(acc);
#pragma unroll
        for (int k = 0; k < 16; k++) keep(A[k]);
        if (g == 0) cons_release<14>(sbase, lane); else cons_release<15>(sbase, lane);
        const uint32_t xo = sbase + SM_AREG + (g ^ 1) * 65536 + AR_X + t128 * 16;
        const uint32_t xi = areg + AR_X + t128 * 16;
        float v[32];
        if (g == 0) {
#pragma unroll
          for (int i = 0; i < 8; i++) sts128(xo + i * 2048, make_uint4(__float_as_uint(acc[32 + 4 * i]), __float_as_uint(acc[33 + 4 * i]), __float_as_uint(acc[34 + 4 * i]), __float_as_uint(acc[35 + 4 * i])));
#pragma unroll
          for (int i = 0; i < 32; i++) v[i] = acc[i];
        } else {
#pragma unroll
          for (int i = 0; i < 8; i++) sts128(xo + i * 2048, make_uint4(__float_as_uint(acc[4 * i]), __float_as_uint(acc[1 + 4 * i]), __float_as_uint(acc[2 + 4 * i]), __float_as_uint(acc[3 + 4 * i])));
#pragma unroll
          for (int i = 0; i < 32; i++) v[i] = acc[32 + i];
        }
        bar_consumers(3);
        ensure_pk<4>(sbase, xr, xp, 1u);
#pragma unroll
        for (int i = 0; i < 8; i++) {
          uint4 t = lds128(xi + i * 2048);
          v[4 * i] += __uint_as_float(t.x); v[4 * i + 1] += __uint_as_float(t.y); v[4 * i + 2] += __uint_as_float(t.z); v[4 * i + 3] += __uint_as_float(t.w);
        }
#pragma unroll
        for (int i = 0; i < 4; i++) {
          v[8 * i + 0] += bf_lo(xr[i].x); v[8 * i + 1] += bf_hi(xr[i].x); v[8 * i + 2] += bf_lo(xr[i].y); v[8 * i + 3] += bf_hi(xr[i].y);
          v[8 * i + 4] += bf_lo(xr[i].z); v[8 * i + 5] += bf_hi(xr[i].z); v[8 * i + 6] += bf_lo(xr[i].w); v[8 * i + 7] += bf_hi(xr[i].w);
          uint4 o = pack8(&v[8 * i]);
          o.x = set_tag(o.x, 0u);
          st_ll(xp + i * 32, o);
        }
        uint4 st = local_stats(v);
        st.x = set_tag(st.x, tag);
        if (qc == 0) st_ll(g_stats + ((c * 8 + slabA) * 8 + 2 * ca + g) * 8 + qr, st);
      }
      TS(8 + 20 * L);
      if (L == 0) { STOP_AT(2); } else { STOP_AT(12); }
      uint4 hs[14];
      {
        PHASE_VARS;
        float acc[128];
        zero_acc(acc);
        uint4 X[3][4];
        const uint4* xs = g_xraw + ((c * 8 + slab) * 32) * 32 + lane;
        const uint4* sp = g_stats + ((c * 8 + slab) * 8 + 2 * qc) * 8 + qr;
        float rl, rh, bl, bh;
        {
          uint4 p[2];
          uint32_t n = 0;
          load_pk<4>(X[0], xs);
          while (true) {
            p[0] = ld_ll(sp); p[1] = ld_ll(sp + 8);
            if (ok_pk<2>(p, tag) || give_up(sbase, n)) break;
          }
          TS(9 + 20 * L);
          float ml, mh;
          combine_stats(p[0], p[1], ml, rl, mh, rh);
          bl = -ml * rl; bh = -mh * rh;
        }
        ensure_pk<4>(sbase, X[0], xs, 0u);
        load_pk<4>(X[1], xs + 128);
        const uint32_t acp = areg + t128 * 16;
        auto normalise = [&](uint4 (&xb)[4], int kb) {
#pragma unroll
          for (int k = 0; k < 4; k++) {
            const uint4 x = xb[k];
            uint4 y;
            y.x = pack2(fmaf(bf_lo(x.x), rl, bl), fmaf(bf_hi(x.x), rl, bl));
            y.y = pack2(fmaf(bf_lo(x.y), rh, bh), fmaf(bf_hi(x.y), rh, bh));
            y.z = pack2(fmaf(bf_lo(x.z), rl, bl), fmaf(bf_hi(x.z), rl, bl));
            y.w = pack2(fmaf(bf_lo(x.w), rh, bh), fmaf(bf_hi(x.w), rh, bh));
            xb[k] = y;
            sts128(acp + (kb * 4 + k) * 2048, y);
          }
        };
        normalise(X[0], 0);
        static_for<0, 8>([&](auto I) {
          constexpr int kb = I.value;
          cons_acquire<16 + kb>(sbase, L);
          wg_fence();
#pragma unroll
          for (int k = 0; k < 4; k++) wgmma_rs_n256<0>(acc, X[kb % 3][k], st_desc<16 + kb, 1024, 4096, 512, 2>(k), 1);
          wg_commit();
          if constexpr (kb > 0) {
            wg_wait<1>();
#pragma unroll
            for (int k = 0; k < 4; k++) keep(X[(kb + 2) % 3][k]);
            cons_release<16 + kb - 1>(sbase, lane);
          }
          if constexpr (kb + 1 < 8) ensure_pk<4>(sbase, X[(kb + 1) % 3], xs + (kb + 1) * 128, 0u);
          if constexpr (kb + 2 < 8) load_pk<4>(X[(kb + 2) % 3], xs + (kb + 2) * 128);
          if constexpr (kb + 1 < 8) normalise(X[(kb + 1) % 3], kb + 1);
        });
        wg_wait<0>();
        TS(10 + 20 * L);
        fence_acc(acc);
#pragma unroll
        for (int k = 0; k < 4; k++) keep(X[1][k]);
        cons_release<23>(sbase, lane);
        uint4 B[2][4];
#pragma unroll
        for (int k = 0; k < 4; k++) B[0][k] = lds128(acp + k * 2048);
#pragma unroll
        for (int s = 0; s < 8; s++) hs[s] = glu8(&acc[32 * (s >> 1) + 8 * (s & 1)]);
        float acc2[96];
        zero_acc(acc2);
        static_for<0, 8>([&](auto I) {
          constexpr int kb = I.value;
          cons_acquire<24 + kb>(sbase, L);
          wg_fence();
#pragma unroll
          for (int k = 0; k < 4; k++) wgmma_rs_n192<0>(acc2, B[kb & 1][k], st_desc<24 + kb, 1024, 4096, 512, 2>(k), 1);
          wg_commit();
          if constexpr (kb > 0) {
            wg_wait<1>();
#pragma unroll
            for (int k = 0; k < 4; k++) keep(B[(kb + 1) & 1][k]);
            cons_release<24 + kb - 1>(sbase, lane);
          }
          if constexpr (kb + 1 < 8) {
#pragma unroll
            for (int k = 0; k < 4; k++) B[(kb + 1) & 1][k] = lds128(acp + ((kb + 1) * 4 + k) * 2048);
          }
          if constexpr (kb == 3) {
            __syncwarp();
            if (lane == 0) mbar_arrive_remote(mapa(bars + BAR_HREADY + 8 * g, cbit ^ 1));
          }
        });
        wg_wait<0>();
        TS(11 + 20 * L);
        fence_acc(acc2);
#pragma unroll
        for (int k = 0; k < 4; k++) keep(B[1][k]);
        cons_release<31>(sbase, lane);
#pragma unroll
        for (int s = 0; s < 6; s++) hs[8 + s] = glu8(&acc2[32 * (s >> 1) + 8 * (s & 1)]);
      }
      {
        PHASE_VARS;
#pragma unroll
        for (int s = 0; s < 14; s++) sts128(areg + (14 + s) * 2048 + t128 * 16, hs[s]);
        asm volatile("fence.proxy.async.shared::cta;" ::: "memory");
        asm volatile("bar.sync %0, 128;" ::"r"(4 + g) : "memory");
        if (t128 == 0) {
          mbar_expect_tx(bars + BAR_HRECV + 8 * g, 14 * 2048);
          mbar_wait_cluster(sbase, bars + BAR_HREADY + 8 * g, L);
          asm volatile("cp.async.bulk.shared::cluster.shared::cta.mbarrier::complete_tx::bytes [%0], [%1], %2, [%3];"
                       ::"r"(mapa(areg, cbit ^ 1)), "r"(areg + 14 * 2048), "r"(14 * 2048), "r"(mapa(bars + BAR_HRECV + 8 * g, cbit ^ 1)) : "memory");
        }
        __syncwarp();
        TS(12 + 20 * L);
        float acc[128];
        zero_acc(acc);
        static_for<0, 8>([&](auto I) {
          constexpr int i = I.value;
          cons_acquire<32 + i>(sbase, L);
          wg_fence();
#pragma unroll
          for (int k = 0; k < 7; k++) wgmma_rs_n64<32 * (i >> 1)>(acc, hs[7 * (i & 1) + k], st_desc<32 + i, 2048, 8192, 1024, 1>(k), 1);
          wg_commit();
          if constexpr (i > 0) { wg_wait<1>(); cons_release<32 + i - 1>(sbase, lane); }
        });
        uint4 hp[14];
        TS(13 + 20 * L);
        mbar_wait_cluster(sbase, bars + BAR_HRECV + 8 * g, L);
        TS(14 + 20 * L);
#pragma unroll
        for (int k = 0; k < 7; k++) { keep(hs[k]); hp[k] = lds128(areg + t128 * 16 + k * 2048); }
        uint4* pd = g_part + ((((c * 4 + (slab >> 1)) * 2 + cbit) * 4 + ca) * 2 + (slab & 1)) * 16 * 32;
        const uint32_t pstage = areg + 28 * 2048 + w * 2048;
        static_for<0, 8>([&](auto I) {
          constexpr int i = I.value;
          cons_acquire<40 + i>(sbase, L);
          wg_fence();
#pragma unroll
          for (int k = 0; k < 7; k++) wgmma_rs_n64<32 * (i >> 1)>(acc, hp[7 * (i & 1) + k], st_desc<40 + i, 2048, 8192, 1024, 1>(k), 1);
          wg_commit();
          wg_wait<1>();
          cons_release<40 + i - 1>(sbase, lane);
          if constexpr (i == 0) {
#pragma unroll
            for (int k = 7; k < 14; k++) { keep(hs[k]); hp[k] = lds128(areg + t128 * 16 + k * 2048); }
          }
          if constexpr (i >= 2 && (i & 1) == 0) {
            constexpr int q = (i >> 1) - 1;
#pragma unroll
            for (int k = 0; k < 32; k++) asm volatile("" : "+f"(acc[32 * q + k])::"memory");
            if constexpr (q > 0) {
              if (lane == 0) asm volatile("cp.async.bulk.wait_group.read 0;" ::: "memory");
              __syncwarp();
            }
#pragma unroll
            for (int s = 0; s < 4; s++) {
              uint4 o = pack8(&acc[32 * q + 8 * s]);
              o.x = set_tag(o.x, tag);
              sts128(pstage + s * 512 + lane * 16, o);
            }
            asm volatile("fence.proxy.async.shared::cta;" ::: "memory");
            __syncwarp();
            if (lane == 0) {
              asm volatile("cp.async.bulk.global.shared::cta.bulk_group [%0], [%1], %2;" ::"l"(pd + q * 128), "r"(pstage), "r"(2048) : "memory");
              asm volatile("cp.async.bulk.commit_group;" ::: "memory");
            }
          }
        });
        wg_wait<0>();
        TS(15 + 20 * L);
        fence_acc(acc);
#pragma unroll
        for (int k = 0; k < 14; k++) keep(hp[k]);
        cons_release<47>(sbase, lane);
#pragma unroll
        for (int s = 0; s < 4; s++) {
          uint4 o = pack8(&acc[96 + 8 * s]);
          o.x = set_tag(o.x, tag);
          st_ll(pd + (12 + s) * 32 + lane, o);
        }
        if (lane == 0) asm volatile("cp.async.bulk.wait_group.read 0;" ::: "memory");
      }
      {
        PHASE_VARS;
        const int sg = warp >> 2, qt = warp & 3;
        const int oslab = 2 * ca + sg;
        const uint4* xq = g_xraw + ((c * 8 + oslab) * 32 + 16 * cbit + 4 * qt) * 32 + lane;
        const uint4* ps = g_part + ((((c * 4 + ca) * 2 + cbit) * 4) * 2 + sg) * 16 * 32 + (4 * qt) * 32 + lane;
        uint4 xr[4], P[4][4];
        float v[32];
        load_pk<4>(xr, xq);
#pragma unroll
        for (int src = 0; src < 4; src++) load_pk<4>(P[src], ps + src * (2 * 16 * 32));
#pragma unroll
        for (int src = 0; src < 4; src++) ensure_pk<4>(sbase, P[src], ps + src * (2 * 16 * 32), tag);
        TS(16 + 20 * L);
        ensure_pk<4>(sbase, xr, xq, 0u);
#pragma unroll
        for (int i = 0; i < 4; i++) {
          v[8 * i + 0] = bf_lo(xr[i].x); v[8 * i + 1] = bf_hi(xr[i].x); v[8 * i + 2] = bf_lo(xr[i].y); v[8 * i + 3] = bf_hi(xr[i].y);
          v[8 * i + 4] = bf_lo(xr[i].z); v[8 * i + 5] = bf_hi(xr[i].z); v[8 * i + 6] = bf_lo(xr[i].w); v[8 * i + 7] = bf_hi(xr[i].w);
          float d[8] = {0, 0, 0, 0, 0, 0, 0, 0};
#pragma unroll
          for (int src = 0; src < 4; src++) {
            const uint4 p = P[src][i];
            d[0] += bf_lo(p.x); d[1] += bf_hi(p.x); d[2] += bf_lo(p.y); d[3] += bf_hi(p.y);
            d[4] += bf_lo(p.z); d[5] += bf_hi(p.z); d[6] += bf_lo(p.w); d[7] += bf_hi(p.w);
          }
#pragma unroll
          for (int k = 0; k < 8; k++) v[8 * i + k] += d[k];
        }
        if (L == 0) {
          owner_ln_publish(sbase, v, 1u, 0u);
        } else {
          uint32_t* op = reinterpret_cast<uint32_t*>(out + (size_t)(c * 128 + oslab * 16 + qr) * 512 + (16 * cbit + 4 * qt) * 16 + qc * 2);
#pragma unroll
          for (int i = 0; i < 4; i++) {
            op[i * 8] = pack2(v[8 * i], v[8 * i + 1]);
            op[8 * 256 + i * 8] = pack2(v[8 * i + 2], v[8 * i + 3]);
            op[i * 8 + 4] = pack2(v[8 * i + 4], v[8 * i + 5]);
            op[8 * 256 + i * 8 + 4] = pack2(v[8 * i + 6], v[8 * i + 7]);
          }
        }
      }
      TS(17 + 20 * L);
      if (L == 0) { STOP_AT(3); }
    }
    asm volatile("barrier.cluster.arrive.release.aligned;\nbarrier.cluster.wait.acquire.aligned; // consumer" ::: "memory");
  }
}

typedef CUresult (*EncodeFn)(CUtensorMap*, CUtensorMapDataType, cuuint32_t, void*, const cuuint64_t*, const cuuint64_t*,
                             const cuuint32_t*, const cuuint32_t*, CUtensorMapInterleave, CUtensorMapSwizzle,
                             CUtensorMapL2promotion, CUtensorMapFloatOOBfill);

void encode(EncodeFn fn, CUtensorMap* m, int rank, const void* base, const cuuint64_t* dims, const cuuint64_t* strides,
            const cuuint32_t* box, CUtensorMapSwizzle sw) {
  cuuint32_t es[5] = {1, 1, 1, 1, 1};
  fn(m, CU_TENSOR_MAP_DATA_TYPE_BFLOAT16, (cuuint32_t)rank, const_cast<void*>(base), dims, strides, box, es,
     CU_TENSOR_MAP_INTERLEAVE_NONE, sw, CU_TENSOR_MAP_L2_PROMOTION_L2_128B, CU_TENSOR_MAP_FLOAT_OOB_FILL_NONE);
}

}

extern "C" void kernel_launch(void* const* d_in, const int* in_sizes, int n_in, void* d_out, int out_size) {
  (void)in_sizes; (void)n_in; (void)out_size;
  const __nv_bfloat16* x = (const __nv_bfloat16*)d_in[0];
  const char* wqkv = (const char*)d_in[1];
  const char* wo = (const char*)d_in[2];
  const char* wg = (const char*)d_in[4];
  const char* wu = (const char*)d_in[5];
  const char* wd = (const char*)d_in[6];

  static EncodeFn fn = nullptr;
  if (!fn) {
    void* p = nullptr;
    cudaDriverEntryPointQueryResult st;
    cudaGetDriverEntryPoint("cuTensorMapEncodeTiled", &p, cudaEnableDefault, &st);
    fn = (EncodeFn)p;
    cudaFuncSetAttribute(fused_kernel, cudaFuncAttributeMaxDynamicSharedMemorySize, SMEM_BYTES);
  }
  CUtensorMap m_qkv, m_wo, m_gu4, m_gu3, m_wd;
  {
    cuuint64_t dims[3] = {512, 512, 3}, str[2] = {3072, 1024};
    cuuint32_t box[3] = {64, 64, 3};
    encode(fn, &m_qkv, 3, wqkv, dims, str, box, CU_TENSOR_MAP_SWIZZLE_128B);
  }
  {
    cuuint64_t dims[3] = {64, 512, 8}, str[2] = {1024, 128};
    cuuint32_t box[3] = {64, 64, 2};
    encode(fn, &m_wo, 3, wo, dims, str, box, CU_TENSOR_MAP_SWIZZLE_128B);
  }
  {
    const char* lo = wg < wu ? wg : wu;
    cuuint64_t diff = (cuuint64_t)(wg < wu ? wu - wg : wg - wu);
    cuuint64_t dims[4] = {32, 512, 2, 56}, str[3] = {3584, diff, 64};
    cuuint32_t box4[4] = {32, 64, 2, 4}, box3[4] = {32, 64, 2, 3};
    encode(fn, &m_gu4, 4, lo, dims, str, box4, CU_TENSOR_MAP_SWIZZLE_64B);
    encode(fn, &m_gu3, 4, lo, dims, str, box3, CU_TENSOR_MAP_SWIZZLE_64B);
  }
  {
    cuuint64_t dims[2] = {512, 1792}, str[1] = {1024};
    cuuint32_t box[2] = {64, 112};
    encode(fn, &m_wd, 2, wd, dims, str, box, CU_TENSOR_MAP_SWIZZLE_128B);
  }
  cudaLaunchConfig_t cfg = {};
  cfg.gridDim = dim3(128);
  cfg.blockDim = dim3(NTHREADS);
  cfg.dynamicSmemBytes = SMEM_BYTES;
  cfg.stream = cudaStreamPerThread;
  cudaLaunchAttribute at[1];
  at[0].id = cudaLaunchAttributeClusterDimension;
  at[0].val.clusterDim.x = 2; at[0].val.clusterDim.y = 1; at[0].val.clusterDim.z = 1;
  cfg.attrs = at; cfg.numAttrs = 1;
  cudaLaunchKernelEx(&cfg, fused_kernel, m_qkv, m_wo, m_gu4, m_gu3, m_wd, x, (__nv_bfloat16*)d_out, wo, wg, wu, wd
  );
}
```

```cpp
#include <cuda_runtime.h>
#include <cuda_bf16.h>
#include <cuda.h>
#include <stdint.h>

namespace {

constexpr int NTHREADS = 384;
constexpr int GRAN = 8192;
constexpr int NGRAN = 12;
constexpr int SM_AREG = NGRAN * GRAN;
constexpr int SM_MISC = SM_AREG + 131072;
constexpr int SM_TSTAT = SM_MISC + 256;
constexpr int SMEM_BYTES = SM_TSTAT + 2048;
constexpr int BAR_FULL = 0, BAR_EMPTY = 96, BAR_HRECV = 192, BAR_HREADY = 224, BAR_TSTAT = 240;
constexpr int AR_X = 32768, AR_KV = 49152;

__device__ uint4 g_xn[16 * 8 * 32 * 32];
__device__ uint4 g_xraw[16 * 8 * 32 * 32];
__device__ uint4 g_o[16 * 8 * 32 * 32];
__device__ uint4 g_stats[16 * 8 * 8 * 8];
__device__ uint4 g_halo[2 * 16 * 8 * 8 * 32];
__device__ uint4 g_part[16 * 4 * 2 * 4 * 2 * 16 * 32];

#define TS(n)
#define TG(n)
#define OPAQUE(x) asm volatile("" : "+r"(x))
#define PHASE_VARS                                                                                   \
  int tid_ = threadIdx.x, bid_ = blockIdx.x;                                                         \
  OPAQUE(tid_); OPAQUE(bid_);                                                                        \
  const int lane = tid_ & 31, warp = tid_ >> 5, g = warp >> 2, w = warp & 3, t128 = tid_ & 127;      \
  const int qr = lane >> 2, qc = lane & 3, slab = warp;                                              \
  const int c = bid_ >> 3, j = bid_ & 7, ca = j >> 1, cbit = j & 1;                                  \
  const uint32_t areg = sbase + SM_AREG + g * 65536;                                                 \
  (void)w; (void)t128; (void)qr; (void)qc; (void)slab; (void)c; (void)ca; (void)cbit; (void)areg; (void)lane
#define STOP_AT(n)
#define PSTOP_AT(n)

__device__ __forceinline__ uint32_t smem_u32(const void* p) { return (uint32_t)__cvta_generic_to_shared(p); }
__device__ __forceinline__ void mbar_init(uint32_t bar, uint32_t cnt) {
  asm volatile("mbarrier.init.shared::cta.b64 [%0], %1;" ::"r"(bar), "r"(cnt) : "memory");
}
__device__ __forceinline__ void mbar_expect_tx(uint32_t bar, uint32_t bytes) {
  asm volatile("mbarrier.arrive.expect_tx.shared::cta.b64 _, [%0], %1;" ::"r"(bar), "r"(bytes) : "memory");
}
__device__ __forceinline__ void mbar_arrive(uint32_t bar) {
  asm volatile("mbarrier.arrive.shared::cta.b64 _, [%0];" ::"r"(bar) : "memory");
}
__device__ __forceinline__ void mbar_arrive_remote(uint32_t cluster_addr) {
  asm volatile("mbarrier.arrive.relaxed.cluster.shared::cluster.b64 _, [%0];" ::"r"(cluster_addr) : "memory");
}
__device__ __forceinline__ bool mbar_try(uint32_t bar, uint32_t parity) {
  uint32_t ok;
  asm volatile("{\n.reg .pred p;\nmbarrier.try_wait.parity.shared::cta.b64 p, [%1], %2;\nselp.u32 %0, 1, 0, p;\n}"
               : "=r"(ok) : "r"(bar), "r"(parity) : "memory");
  return ok != 0;
}
constexpr uint32_t SPIN_LIMIT = 1u << 16;
constexpr uint32_t SMEM_ORIGIN = 1024;
__device__ __forceinline__ void mbar_wait(uint32_t bar, uint32_t parity) {
  for (uint32_t n = 0; !mbar_try(bar, parity) && n < SPIN_LIMIT; n++) {}
}
__device__ __forceinline__ uint32_t mapa(uint32_t addr, uint32_t rank) {
  uint32_t r;
  asm volatile("mapa.shared::cluster.u32 %0, %1, %2;" : "=r"(r) : "r"(addr), "r"(rank));
  return r;
}
__device__ __forceinline__ void cluster_sync_all() {
  asm volatile("barrier.cluster.arrive.release.aligned;\nbarrier.cluster.wait.acquire.aligned;" ::: "memory");
}
__device__ __forceinline__ void bar_consumers(int id) { asm volatile("bar.sync %0, 256;" ::"r"(id) : "memory"); }

__device__ __forceinline__ void tma_2d(uint32_t dst, const CUtensorMap* m, uint32_t bar, int c0, int c1) {
  asm volatile("cp.async.bulk.tensor.2d.shared::cluster.global.mbarrier::complete_tx::bytes [%0], [%1, {%3, %4}], [%2];"
               ::"r"(dst), "l"(m), "r"(bar), "r"(c0), "r"(c1) : "memory");
}
__device__ __forceinline__ void tma_3d(uint32_t dst, const CUtensorMap* m, uint32_t bar, int c0, int c1, int c2) {
  asm volatile("cp.async.bulk.tensor.3d.shared::cluster.global.mbarrier::complete_tx::bytes [%0], [%1, {%3, %4, %5}], [%2];"
               ::"r"(dst), "l"(m), "r"(bar), "r"(c0), "r"(c1), "r"(c2) : "memory");
}
__device__ __forceinline__ void tma_4d(uint32_t dst, const CUtensorMap* m, uint32_t bar, int c0, int c1, int c2, int c3) {
  asm volatile("cp.async.bulk.tensor.4d.shared::cluster.global.mbarrier::complete_tx::bytes [%0], [%1, {%3, %4, %5, %6}], [%2];"
               ::"r"(dst), "l"(m), "r"(bar), "r"(c0), "r"(c1), "r"(c2), "r"(c3) : "memory");
}
__device__ __forceinline__ void l2_prefetch(const void* p, uint32_t bytes) {
  asm volatile("cp.async.bulk.prefetch.L2.global [%0], %1;" ::"l"(p), "r"(bytes) : "memory");
}

__device__ __forceinline__ uint4 ld_ll(const uint4* p) {
  uint4 v;
  asm volatile("ld.relaxed.gpu.global.v4.u32 {%0,%1,%2,%3}, [%4];" : "=r"(v.x), "=r"(v.y), "=r"(v.z), "=r"(v.w) : "l"(p) : "memory");
  return v;
}
__device__ __forceinline__ void st_ll(uint4* p, uint4 v) {
  asm volatile("st.relaxed.gpu.global.v4.u32 [%0], {%1,%2,%3,%4};" ::"l"(p), "r"(v.x), "r"(v.y), "r"(v.z), "r"(v.w) : "memory");
}
__device__ __forceinline__ uint4 lds128(uint32_t a) {
  uint4 v;
  asm volatile("ld.shared.v4.u32 {%0,%1,%2,%3}, [%4];" : "=r"(v.x), "=r"(v.y), "=r"(v.z), "=r"(v.w) : "r"(a) : "memory");
  return v;
}
__device__ __forceinline__ void sts128(uint32_t a, uint4 v) {
  asm volatile("st.shared.v4.u32 [%0], {%1,%2,%3,%4};" ::"r"(a), "r"(v.x), "r"(v.y), "r"(v.z), "r"(v.w) : "memory");
}
__device__ __forceinline__ void st_async128(uint32_t cluster_addr, uint4 v, uint32_t cluster_bar) {
  asm volatile("st.async.weak.shared::cluster.mbarrier::complete_tx::bytes.v4.b32 [%0], {%1,%2,%3,%4}, [%5];"
               ::"r"(cluster_addr), "r"(v.x), "r"(v.y), "r"(v.z), "r"(v.w), "r"(cluster_bar) : "memory");
}
__device__ __forceinline__ uint32_t pack2(float lo, float hi) {
  uint32_t r;
  asm("cvt.rn.bf16x2.f32 %0, %1, %2;" : "=r"(r) : "f"(hi), "f"(lo));
  return r;
}
__device__ __forceinline__ float bf_lo(uint32_t w) { return __uint_as_float(w << 16); }
__device__ __forceinline__ float bf_hi(uint32_t w) { return __uint_as_float(w & 0xffff0000u); }
__device__ __forceinline__ uint32_t set_tag(uint32_t w, uint32_t tag) { return (w & ~1u) | tag; }
__device__ __forceinline__ uint32_t movm(uint32_t a) {
  uint32_t d;
  asm("movmatrix.sync.aligned.m8n8.trans.b16 %0, %1;" : "=r"(d) : "r"(a));
  return d;
}
__device__ __forceinline__ void mma16816(float (&d)[4], const uint4& a, uint32_t b0, uint32_t b1) {
  asm("mma.sync.aligned.m16n8k16.row.col.f32.bf16.bf16.f32 {%0,%1,%2,%3}, {%4,%5,%6,%7}, {%8,%9}, {%0,%1,%2,%3};"
               : "+f"(d[0]), "+f"(d[1]), "+f"(d[2]), "+f"(d[3])
               : "r"(a.x), "r"(a.y), "r"(a.z), "r"(a.w), "r"(b0), "r"(b1));
}
__device__ __forceinline__ void wg_fence() { asm volatile("wgmma.fence.sync.aligned;" ::: "memory"); }
__device__ __forceinline__ void wg_commit() { asm volatile("wgmma.commit_group.sync.aligned;" ::: "memory"); }
template <int N> __device__ __forceinline__ void wg_wait() { asm volatile("wgmma.wait_group.sync.aligned %0;" ::"n"(N) : "memory"); }
__device__ __forceinline__ void keep(const uint4& a) { asm volatile("" ::"r"(a.x), "r"(a.y), "r"(a.z), "r"(a.w) : "memory"); }
template <int T> __device__ __forceinline__ void zero_acc(float (&d)[T]) {
#pragma unroll
  for (int i = 0; i < T; i++) d[i] = 0.f;
}
template <int T> __device__ __forceinline__ void fence_acc(float (&d)[T]) {
#pragma unroll
  for (int i = 0; i < T; i++) asm volatile("" : "+f"(d[i])::"memory");
}

template <int O, int T> __device__ __forceinline__ void wgmma_rs_n64(float (&d)[T], const uint4& a, uint64_t db) {
  asm volatile("{\n.reg .pred p;\nsetp.ne.b32 p, 1, 0;\n"
    "wgmma.mma_async.sync.aligned.m64n64k16.f32.bf16.bf16 "
    "{%0, %1, %2, %3, %4, %5, %6, %7, %8, %9, %10, %11, %12, %13, %14, %15, "
    "%16, %17, %18, %19, %20, %21, %22, %23, %24, %25, %26, %27, %28, %29, %30, %31}, "
    "{%32, %33, %34, %35}, %36, p, 1, 1, 1;\n}\n"
    : "+f"(d[O + 0]), "+f"(d[O + 1]), "+f"(d[O + 2]), "+f"(d[O + 3]), "+f"(d[O + 4]), "+f"(d[O + 5]), "+f"(d[O + 6]), "+f"(d[O + 7]),
      "+f"(d[O + 8]), "+f"(d[O + 9]), "+f"(d[O + 10]), "+f"(d[O + 11]), "+f"(d[O + 12]), "+f"(d[O + 13]), "+f"(d[O + 14]), "+f"(d[O + 15]),
      "+f"(d[O + 16]), "+f"(d[O + 17]), "+f"(d[O + 18]), "+f"(d[O + 19]), "+f"(d[O + 20]), "+f"(d[O + 21]), "+f"(d[O + 22]), "+f"(d[O + 23]),
      "+f"(d[O + 24]), "+f"(d[O + 25]), "+f"(d[O + 26]), "+f"(d[O + 27]), "+f"(d[O + 28]), "+f"(d[O + 29]), "+f"(d[O + 30]), "+f"(d[O + 31])
    : "r"(a.x), "r"(a.y), "r"(a.z), "r"(a.w), "l"(db));
}
template <int O, int T> __device__ __forceinline__ void wgmma_rs_n64_init(float (&d)[T], const uint4& a, uint64_t db) {
  asm volatile("{\n.reg .pred p;\nsetp.ne.b32 p, 0, 0;\n"
    "wgmma.mma_async.sync.aligned.m64n64k16.f32.bf16.bf16 "
    "{%0, %1, %2, %3, %4, %5, %6, %7, %8, %9, %10, %11, %12, %13, %14, %15, "
    "%16, %17, %18, %19, %20, %21, %22, %23, %24, %25, %26, %27, %28, %29, %30, %31}, "
    "{%32, %33, %34, %35}, %36, p, 1, 1, 1;\n}\n"
    : "=f"(d[O + 0]), "=f"(d[O + 1]), "=f"(d[O + 2]), "=f"(d[O + 3]), "=f"(d[O + 4]), "=f"(d[O + 5]), "=f"(d[O + 6]), "=f"(d[O + 7]),
      "=f"(d[O + 8]), "=f"(d[O + 9]), "=f"(d[O + 10]), "=f"(d[O + 11]), "=f"(d[O + 12]), "=f"(d[O + 13]), "=f"(d[O + 14]), "=f"(d[O + 15]),
      "=f"(d[O + 16]), "=f"(d[O + 17]), "=f"(d[O + 18]), "=f"(d[O + 19]), "=f"(d[O + 20]), "=f"(d[O + 21]), "=f"(d[O + 22]), "=f"(d[O + 23]),
      "=f"(d[O + 24]), "=f"(d[O + 25]), "=f"(d[O + 26]), "=f"(d[O + 27]), "=f"(d[O + 28]), "=f"(d[O + 29]), "=f"(d[O + 30]), "=f"(d[O + 31])
    : "r"(a.x), "r"(a.y), "r"(a.z), "r"(a.w), "l"(db));
}
template <bool INIT, int O, int T> __device__ __forceinline__ void wgmma_n64(float (&d)[T], const uint4& a, uint64_t db) {
  if constexpr (INIT) wgmma_rs_n64_init<O>(d, a, db); else wgmma_rs_n64<O>(d, a, db);
}
template <int O, int T> __device__ __forceinline__ void wgmma_rs_n128(float (&d)[T], const uint4& a, uint64_t db) {
  asm volatile("{\n.reg .pred p;\nsetp.ne.b32 p, 1, 0;\n"
    "wgmma.mma_async.sync.aligned.m64n128k16.f32.bf16.bf16 "
    "{%0, %1, %2, %3, %4, %5, %6, %7, %8, %9, %10, %11, %12, %13, %14, %15, "
    "%16, %17, %18, %19, %20, %21, %22, %23, %24, %25, %26, %27, %28, %29, %30, %31, "
    "%32, %33, %34, %35, %36, %37, %38, %39, %40, %41, %42, %43, %44, %45, %46, %47, "
    "%48, %49, %50, %51, %52, %53, %54, %55, %56, %57, %58, %59, %60, %61, %62, %63}, "
    "{%64, %65, %66, %67}, %68, p, 1, 1, 1;\n}\n"
    : "+f"(d[O + 0]), "+f"(d[O + 1]), "+f"(d[O + 2]), "+f"(d[O + 3]), "+f"(d[O + 4]), "+f"(d[O + 5]), "+f"(d[O + 6]), "+f"(d[O + 7]),
      "+f"(d[O + 8]), "+f"(d[O + 9]), "+f"(d[O + 10]), "+f"(d[O + 11]), "+f"(d[O + 12]), "+f"(d[O + 13]), "+f"(d[O + 14]), "+f"(d[O + 15]),
      "+f"(d[O + 16]), "+f"(d[O + 17]), "+f"(d[O + 18]), "+f"(d[O + 19]), "+f"(d[O + 20]), "+f"(d[O + 21]), "+f"(d[O + 22]), "+f"(d[O + 23]),
      "+f"(d[O + 24]), "+f"(d[O + 25]), "+f"(d[O + 26]), "+f"(d[O + 27]), "+f"(d[O + 28]), "+f"(d[O + 29]), "+f"(d[O + 30]), "+f"(d[O + 31]),
      "+f"(d[O + 32]), "+f"(d[O + 33]), "+f"(d[O + 34]), "+f"(d[O + 35]), "+f"(d[O + 36]), "+f"(d[O + 37]), "+f"(d[O + 38]), "+f"(d[O + 39]),
      "+f"(d[O + 40]), "+f"(d[O + 41]), "+f"(d[O + 42]), "+f"(d[O + 43]), "+f"(d[O + 44]), "+f"(d[O + 45]), "+f"(d[O + 46]), "+f"(d[O + 47]),
      "+f"(d[O + 48]), "+f"(d[O + 49]), "+f"(d[O + 50]), "+f"(d[O + 51]), "+f"(d[O + 52]), "+f"(d[O + 53]), "+f"(d[O + 54]), "+f"(d[O + 55]),
      "+f"(d[O + 56]), "+f"(d[O + 57]), "+f"(d[O + 58]), "+f"(d[O + 59]), "+f"(d[O + 60]), "+f"(d[O + 61]), "+f"(d[O + 62]), "+f"(d[O + 63])
    : "r"(a.x), "r"(a.y), "r"(a.z), "r"(a.w), "l"(db));
}
template <int O, int T> __device__ __forceinline__ void wgmma_rs_n128_init(float (&d)[T], const uint4& a, uint64_t db) {
  asm volatile("{\n.reg .pred p;\nsetp.ne.b32 p, 0, 0;\n"
    "wgmma.mma_async.sync.aligned.m64n128k16.f32.bf16.bf16 "
    "{%0, %1, %2, %3, %4, %5, %6, %7, %8, %9, %10, %11, %12, %13, %14, %15, "
    "%16, %17, %18, %19, %20, %21, %22, %23, %24, %25, %26, %27, %28, %29, %30, %31, "
    "%32, %33, %34, %35, %36, %37, %38, %39, %40, %41, %42, %43, %44, %45, %46, %47, "
    "%48, %49, %50, %51, %52, %53, %54, %55, %56, %57, %58, %59, %60, %61, %62, %63}, "
    "{%64, %65, %66, %67}, %68, p, 1, 1, 1;\n}\n"
    : "=f"(d[O + 0]), "=f"(d[O + 1]), "=f"(d[O + 2]), "=f"(d[O + 3]), "=f"(d[O + 4]), "=f"(d[O + 5]), "=f"(d[O + 6]), "=f"(d[O + 7]),
      "=f"(d[O + 8]), "=f"(d[O + 9]), "=f"(d[O + 10]), "=f"(d[O + 11]), "=f"(d[O + 12]), "=f"(d[O + 13]), "=f"(d[O + 14]), "=f"(d[O + 15]),
      "=f"(d[O + 16]), "=f"(d[O + 17]), "=f"(d[O + 18]), "=f"(d[O + 19]), "=f"(d[O + 20]), "=f"(d[O + 21]), "=f"(d[O + 22]), "=f"(d[O + 23]),
      "=f"(d[O + 24]), "=f"(d[O + 25]), "=f"(d[O + 26]), "=f"(d[O + 27]), "=f"(d[O + 28]), "=f"(d[O + 29]), "=f"(d[O + 30]), "=f"(d[O + 31]),
      "=f"(d[O + 32]), "=f"(d[O + 33]), "=f"(d[O + 34]), "=f"(d[O + 35]), "=f"(d[O + 36]), "=f"(d[O + 37]), "=f"(d[O + 38]), "=f"(d[O + 39]),
      "=f"(d[O + 40]), "=f"(d[O + 41]), "=f"(d[O + 42]), "=f"(d[O + 43]), "=f"(d[O + 44]), "=f"(d[O + 45]), "=f"(d[O + 46]), "=f"(d[O + 47]),
      "=f"(d[O + 48]), "=f"(d[O + 49]), "=f"(d[O + 50]), "=f"(d[O + 51]), "=f"(d[O + 52]), "=f"(d[O + 53]), "=f"(d[O + 54]), "=f"(d[O + 55]),
      "=f"(d[O + 56]), "=f"(d[O + 57]), "=f"(d[O + 58]), "=f"(d[O + 59]), "=f"(d[O + 60]), "=f"(d[O + 61]), "=f"(d[O + 62]), "=f"(d[O + 63])
    : "r"(a.x), "r"(a.y), "r"(a.z), "r"(a.w), "l"(db));
}
template <bool INIT, int O, int T> __device__ __forceinline__ void wgmma_n128(float (&d)[T], const uint4& a, uint64_t db) {
  if constexpr (INIT) wgmma_rs_n128_init<O>(d, a, db); else wgmma_rs_n128<O>(d, a, db);
}
template <int O, int T> __device__ __forceinline__ void wgmma_rs_n192(float (&d)[T], const uint4& a, uint64_t db) {
  asm volatile("{\n.reg .pred p;\nsetp.ne.b32 p, 1, 0;\n"
    "wgmma.mma_async.sync.aligned.m64n192k16.f32.bf16.bf16 "
    "{%0, %1, %2, %3, %4, %5, %6, %7, %8, %9, %10, %11, %12, %13, %14, %15, "
    "%16, %17, %18, %19, %20, %21, %22, %23, %24, %25, %26, %27, %28, %29, %30, %31, "
    "%32, %33, %34, %35, %36, %37, %38, %39, %40, %41, %42, %43, %44, %45, %46, %47, "
    "%48, %49, %50, %51, %52, %53, %54, %55, %56, %57, %58, %59, %60, %61, %62, %63, "
    "%64, %65, %66, %67, %68, %69, %70, %71, %72, %73, %74, %75, %76, %77, %78, %79, "
    "%80, %81, %82, %83, %84, %85, %86, %87, %88, %89, %90, %91, %92, %93, %94, %95}, "
    "{%96, %97, %98, %99}, %100, p, 1, 1, 1;\n}\n"
    : "+f"(d[O + 0]), "+f"(d[O + 1]), "+f"(d[O + 2]), "+f"(d[O + 3]), "+f"(d[O + 4]), "+f"(d[O + 5]), "+f"(d[O + 6]), "+f"(d[O + 7]),
      "+f"(d[O + 8]), "+f"(d[O + 9]), "+f"(d[O + 10]), "+f"(d[O + 11]), "+f"(d[O + 12]), "+f"(d[O + 13]), "+f"(d[O + 14]), "+f"(d[O + 15]),
      "+f"(d[O + 16]), "+f"(d[O + 17]), "+f"(d[O + 18]), "+f"(d[O + 19]), "+f"(d[O + 20]), "+f"(d[O + 21]), "+f"(d[O + 22]), "+f"(d[O + 23]),
      "+f"(d[O + 24]), "+f"(d[O + 25]), "+f"(d[O + 26]), "+f"(d[O + 27]), "+f"(d[O + 28]), "+f"(d[O + 29]), "+f"(d[O + 30]), "+f"(d[O + 31]),
      "+f"(d[O + 32]), "+f"(d[O + 33]), "+f"(d[O + 34]), "+f"(d[O + 35]), "+f"(d[O + 36]), "+f"(d[O + 37]), "+f"(d[O + 38]), "+f"(d[O + 39]),
      "+f"(d[O + 40]), "+f"(d[O + 41]), "+f"(d[O + 42]), "+f"(d[O + 43]), "+f"(d[O + 44]), "+f"(d[O + 45]), "+f"(d[O + 46]), "+f"(d[O + 47]),
      "+f"(d[O + 48]), "+f"(d[O + 49]), "+f"(d[O + 50]), "+f"(d[O + 51]), "+f"(d[O + 52]), "+f"(d[O + 53]), "+f"(d[O + 54]), "+f"(d[O + 55]),
      "+f"(d[O + 56]), "+f"(d[O + 57]), "+f"(d[O + 58]), "+f"(d[O + 59]), "+f"(d[O + 60]), "+f"(d[O + 61]), "+f"(d[O + 62]), "+f"(d[O + 63]),
      "+f"(d[O + 64]), "+f"(d[O + 65]), "+f"(d[O + 66]), "+f"(d[O + 67]), "+f"(d[O + 68]), "+f"(d[O + 69]), "+f"(d[O + 70]), "+f"(d[O + 71]),
      "+f"(d[O + 72]), "+f"(d[O + 73]), "+f"(d[O + 74]), "+f"(d[O + 75]), "+f"(d[O + 76]), "+f"(d[O + 77]), "+f"(d[O + 78]), "+f"(d[O + 79]),
      "+f"(d[O + 80]), "+f"(d[O + 81]), "+f"(d[O + 82]), "+f"(d[O + 83]), "+f"(d[O + 84]), "+f"(d[O + 85]), "+f"(d[O + 86]), "+f"(d[O + 87]),
      "+f"(d[O + 88]), "+f"(d[O + 89]), "+f"(d[O + 90]), "+f"(d[O + 91]), "+f"(d[O + 92]), "+f"(d[O + 93]), "+f"(d[O + 94]), "+f"(d[O + 95])
    : "r"(a.x), "r"(a.y), "r"(a.z), "r"(a.w), "l"(db));
}
template <int O, int T> __device__ __forceinline__ void wgmma_rs_n192_init(float (&d)[T], const uint4& a, uint64_t db) {
  asm volatile("{\n.reg .pred p;\nsetp.ne.b32 p, 0, 0;\n"
    "wgmma.mma_async.sync.aligned.m64n192k16.f32.bf16.bf16 "
    "{%0, %1, %2, %3, %4, %5, %6, %7, %8, %9, %10, %11, %12, %13, %14, %15, "
    "%16, %17, %18, %19, %20, %21, %22, %23, %24, %25, %26, %27, %28, %29, %30, %31, "
    "%32, %33, %34, %35, %36, %37, %38, %39, %40, %41, %42, %43, %44, %45, %46, %47, "
    "%48, %49, %50, %51, %52, %53, %54, %55, %56, %57, %58, %59, %60, %61, %62, %63, "
    "%64, %65, %66, %67, %68, %69, %70, %71, %72, %73, %74, %75, %76, %77, %78, %79, "
    "%80, %81, %82, %83, %84, %85, %86, %87, %88, %89, %90, %91, %92, %93, %94, %95}, "
    "{%96, %97, %98, %99}, %100, p, 1, 1, 1;\n}\n"
    : "=f"(d[O + 0]), "=f"(d[O + 1]), "=f"(d[O + 2]), "=f"(d[O + 3]), "=f"(d[O + 4]), "=f"(d[O + 5]), "=f"(d[O + 6]), "=f"(d[O + 7]),
      "=f"(d[O + 8]), "=f"(d[O + 9]), "=f"(d[O + 10]), "=f"(d[O + 11]), "=f"(d[O + 12]), "=f"(d[O + 13]), "=f"(d[O + 14]), "=f"(d[O + 15]),
      "=f"(d[O + 16]), "=f"(d[O + 17]), "=f"(d[O + 18]), "=f"(d[O + 19]), "=f"(d[O + 20]), "=f"(d[O + 21]), "=f"(d[O + 22]), "=f"(d[O + 23]),
      "=f"(d[O + 24]), "=f"(d[O + 25]), "=f"(d[O + 26]), "=f"(d[O + 27]), "=f"(d[O + 28]), "=f"(d[O + 29]), "=f"(d[O + 30]), "=f"(d[O + 31]),
      "=f"(d[O + 32]), "=f"(d[O + 33]), "=f"(d[O + 34]), "=f"(d[O + 35]), "=f"(d[O + 36]), "=f"(d[O + 37]), "=f"(d[O + 38]), "=f"(d[O + 39]),
      "=f"(d[O + 40]), "=f"(d[O + 41]), "=f"(d[O + 42]), "=f"(d[O + 43]), "=f"(d[O + 44]), "=f"(d[O + 45]), "=f"(d[O + 46]), "=f"(d[O + 47]),
      "=f"(d[O + 48]), "=f"(d[O + 49]), "=f"(d[O + 50]), "=f"(d[O + 51]), "=f"(d[O + 52]), "=f"(d[O + 53]), "=f"(d[O + 54]), "=f"(d[O + 55]),
      "=f"(d[O + 56]), "=f"(d[O + 57]), "=f"(d[O + 58]), "=f"(d[O + 59]), "=f"(d[O + 60]), "=f"(d[O + 61]), "=f"(d[O + 62]), "=f"(d[O + 63]),
      "=f"(d[O + 64]), "=f"(d[O + 65]), "=f"(d[O + 66]), "=f"(d[O + 67]), "=f"(d[O + 68]), "=f"(d[O + 69]), "=f"(d[O + 70]), "=f"(d[O + 71]),
      "=f"(d[O + 72]), "=f"(d[O + 73]), "=f"(d[O + 74]), "=f"(d[O + 75]), "=f"(d[O + 76]), "=f"(d[O + 77]), "=f"(d[O + 78]), "=f"(d[O + 79]),
      "=f"(d[O + 80]), "=f"(d[O + 81]), "=f"(d[O + 82]), "=f"(d[O + 83]), "=f"(d[O + 84]), "=f"(d[O + 85]), "=f"(d[O + 86]), "=f"(d[O + 87]),
      "=f"(d[O + 88]), "=f"(d[O + 89]), "=f"(d[O + 90]), "=f"(d[O + 91]), "=f"(d[O + 92]), "=f"(d[O + 93]), "=f"(d[O + 94]), "=f"(d[O + 95])
    : "r"(a.x), "r"(a.y), "r"(a.z), "r"(a.w), "l"(db));
}
template <bool INIT, int O, int T> __device__ __forceinline__ void wgmma_n192(float (&d)[T], const uint4& a, uint64_t db) {
  if constexpr (INIT) wgmma_rs_n192_init<O>(d, a, db); else wgmma_rs_n192<O>(d, a, db);
}
template <int O, int T> __device__ __forceinline__ void wgmma_rs_n256(float (&d)[T], const uint4& a, uint64_t db) {
  asm volatile("{\n.reg .pred p;\nsetp.ne.b32 p, 1, 0;\n"
    "wgmma.mma_async.sync.aligned.m64n256k16.f32.bf16.bf16 "
    "{%0, %1, %2, %3, %4, %5, %6, %7, %8, %9, %10, %11, %12, %13, %14, %15, "
    "%16, %17, %18, %19, %20, %21, %22, %23, %24, %25, %26, %27, %28, %29, %30, %31, "
    "%32, %33, %34, %35, %36, %37, %38, %39, %40, %41, %42, %43, %44, %45, %46, %47, "
    "%48, %49, %50, %51, %52, %53, %54, %55, %56, %57, %58, %59, %60, %61, %62, %63, "
    "%64, %65, %66, %67, %68, %69, %70, %71, %72, %73, %74, %75, %76, %77, %78, %79, "
    "%80, %81, %82, %83, %84, %85, %86, %87, %88, %89, %90, %91, %92, %93, %94, %95, "
    "%96, %97, %98, %99, %100, %101, %102, %103, %104, %105, %106, %107, %108, %109, %110, %111, "
    "%112, %113, %114, %115, %116, %117, %118, %119, %120, %121, %122, %123, %124, %125, %126, %127}, "
    "{%128, %129, %130, %131}, %132, p, 1, 1, 1;\n}\n"
    : "+f"(d[O + 0]), "+f"(d[O + 1]), "+f"(d[O + 2]), "+f"(d[O + 3]), "+f"(d[O + 4]), "+f"(d[O + 5]), "+f"(d[O + 6]), "+f"(d[O + 7]),
      "+f"(d[O + 8]), "+f"(d[O + 9]), "+f"(d[O + 10]), "+f"(d[O + 11]), "+f"(d[O + 12]), "+f"(d[O + 13]), "+f"(d[O + 14]), "+f"(d[O + 15]),
      "+f"(d[O + 16]), "+f"(d[O + 17]), "+f"(d[O + 18]), "+f"(d[O + 19]), "+f"(d[O + 20]), "+f"(d[O + 21]), "+f"(d[O + 22]), "+f"(d[O + 23]),
      "+f"(d[O + 24]), "+f"(d[O + 25]), "+f"(d[O + 26]), "+f"(d[O + 27]), "+f"(d[O + 28]), "+f"(d[O + 29]), "+f"(d[O + 30]), "+f"(d[O + 31]),
      "+f"(d[O + 32]), "+f"(d[O + 33]), "+f"(d[O + 34]), "+f"(d[O + 35]), "+f"(d[O + 36]), "+f"(d[O + 37]), "+f"(d[O + 38]), "+f"(d[O + 39]),
      "+f"(d[O + 40]), "+f"(d[O + 41]), "+f"(d[O + 42]), "+f"(d[O + 43]), "+f"(d[O + 44]), "+f"(d[O + 45]), "+f"(d[O + 46]), "+f"(d[O + 47]),
      "+f"(d[O + 48]), "+f"(d[O + 49]), "+f"(d[O + 50]), "+f"(d[O + 51]), "+f"(d[O + 52]), "+f"(d[O + 53]), "+f"(d[O + 54]), "+f"(d[O + 55]),
      "+f"(d[O + 56]), "+f"(d[O + 57]), "+f"(d[O + 58]), "+f"(d[O + 59]), "+f"(d[O + 60]), "+f"(d[O + 61]), "+f"(d[O + 62]), "+f"(d[O + 63]),
      "+f"(d[O + 64]), "+f"(d[O + 65]), "+f"(d[O + 66]), "+f"(d[O + 67]), "+f"(d[O + 68]), "+f"(d[O + 69]), "+f"(d[O + 70]), "+f"(d[O + 71]),
      "+f"(d[O + 72]), "+f"(d[O + 73]), "+f"(d[O + 74]), "+f"(d[O + 75]), "+f"(d[O + 76]), "+f"(d[O + 77]), "+f"(d[O + 78]), "+f"(d[O + 79]),
      "+f"(d[O + 80]), "+f"(d[O + 81]), "+f"(d[O + 82]), "+f"(d[O + 83]), "+f"(d[O + 84]), "+f"(d[O + 85]), "+f"(d[O + 86]), "+f"(d[O + 87]),
      "+f"(d[O + 88]), "+f"(d[O + 89]), "+f"(d[O + 90]), "+f"(d[O + 91]), "+f"(d[O + 92]), "+f"(d[O + 93]), "+f"(d[O + 94]), "+f"(d[O + 95]),
      "+f"(d[O + 96]), "+f"(d[O + 97]), "+f"(d[O + 98]), "+f"(d[O + 99]), "+f"(d[O + 100]), "+f"(d[O + 101]), "+f"(d[O + 102]), "+f"(d[O + 103]),
      "+f"(d[O + 104]), "+f"(d[O + 105]), "+f"(d[O + 106]), "+f"(d[O + 107]), "+f"(d[O + 108]), "+f"(d[O + 109]), "+f"(d[O + 110]), "+f"(d[O + 111]),
      "+f"(d[O + 112]), "+f"(d[O + 113]), "+f"(d[O + 114]), "+f"(d[O + 115]), "+f"(d[O + 116]), "+f"(d[O + 117]), "+f"(d[O + 118]), "+f"(d[O + 119]),
      "+f"(d[O + 120]), "+f"(d[O + 121]), "+f"(d[O + 122]), "+f"(d[O + 123]), "+f"(d[O + 124]), "+f"(d[O + 125]), "+f"(d[O + 126]), "+f"(d[O + 127])
    : "r"(a.x), "r"(a.y), "r"(a.z), "r"(a.w), "l"(db));
}
template <int O, int T> __device__ __forceinline__ void wgmma_rs_n256_init(float (&d)[T], const uint4& a, uint64_t db) {
  asm volatile("{\n.reg .pred p;\nsetp.ne.b32 p, 0, 0;\n"
    "wgmma.mma_async.sync.aligned.m64n256k16.f32.bf16.bf16 "
    "{%0, %1, %2, %3, %4, %5, %6, %7, %8, %9, %10, %11, %12, %13, %14, %15, "
    "%16, %17, %18, %19, %20, %21, %22, %23, %24, %25, %26, %27, %28, %29, %30, %31, "
    "%32, %33, %34, %35, %36, %37, %38, %39, %40, %41, %42, %43, %44, %45, %46, %47, "
    "%48, %49, %50, %51, %52, %53, %54, %55, %56, %57, %58, %59, %60, %61, %62, %63, "
    "%64, %65, %66, %67, %68, %69, %70, %71, %72, %73, %74, %75, %76, %77, %78, %79, "
    "%80, %81, %82, %83, %84, %85, %86, %87, %88, %89, %90, %91, %92, %93, %94, %95, "
    "%96, %97, %98, %99, %100, %101, %102, %103, %104, %105, %106, %107, %108, %109, %110, %111, "
    "%112, %113, %114, %115, %116, %117, %118, %119, %120, %121, %122, %123, %124, %125, %126, %127}, "
    "{%128, %129, %130, %131}, %132, p, 1, 1, 1;\n}\n"
    : "=f"(d[O + 0]), "=f"(d[O + 1]), "=f"(d[O + 2]), "=f"(d[O + 3]), "=f"(d[O + 4]), "=f"(d[O + 5]), "=f"(d[O + 6]), "=f"(d[O + 7]),
      "=f"(d[O + 8]), "=f"(d[O + 9]), "=f"(d[O + 10]), "=f"(d[O + 11]), "=f"(d[O + 12]), "=f"(d[O + 13]), "=f"(d[O + 14]), "=f"(d[O + 15]),
      "=f"(d[O + 16]), "=f"(d[O + 17]), "=f"(d[O + 18]), "=f"(d[O + 19]), "=f"(d[O + 20]), "=f"(d[O + 21]), "=f"(d[O + 22]), "=f"(d[O + 23]),
      "=f"(d[O + 24]), "=f"(d[O + 25]), "=f"(d[O + 26]), "=f"(d[O + 27]), "=f"(d[O + 28]), "=f"(d[O + 29]), "=f"(d[O + 30]), "=f"(d[O + 31]),
      "=f"(d[O + 32]), "=f"(d[O + 33]), "=f"(d[O + 34]), "=f"(d[O + 35]), "=f"(d[O + 36]), "=f"(d[O + 37]), "=f"(d[O + 38]), "=f"(d[O + 39]),
      "=f"(d[O + 40]), "=f"(d[O + 41]), "=f"(d[O + 42]), "=f"(d[O + 43]), "=f"(d[O + 44]), "=f"(d[O + 45]), "=f"(d[O + 46]), "=f"(d[O + 47]),
      "=f"(d[O + 48]), "=f"(d[O + 49]), "=f"(d[O + 50]), "=f"(d[O + 51]), "=f"(d[O + 52]), "=f"(d[O + 53]), "=f"(d[O + 54]), "=f"(d[O + 55]),
      "=f"(d[O + 56]), "=f"(d[O + 57]), "=f"(d[O + 58]), "=f"(d[O + 59]), "=f"(d[O + 60]), "=f"(d[O + 61]), "=f"(d[O + 62]), "=f"(d[O + 63]),
      "=f"(d[O + 64]), "=f"(d[O + 65]), "=f"(d[O + 66]), "=f"(d[O + 67]), "=f"(d[O + 68]), "=f"(d[O + 69]), "=f"(d[O + 70]), "=f"(d[O + 71]),
      "=f"(d[O + 72]), "=f"(d[O + 73]), "=f"(d[O + 74]), "=f"(d[O + 75]), "=f"(d[O + 76]), "=f"(d[O + 77]), "=f"(d[O + 78]), "=f"(d[O + 79]),
      "=f"(d[O + 80]), "=f"(d[O + 81]), "=f"(d[O + 82]), "=f"(d[O + 83]), "=f"(d[O + 84]), "=f"(d[O + 85]), "=f"(d[O + 86]), "=f"(d[O + 87]),
      "=f"(d[O + 88]), "=f"(d[O + 89]), "=f"(d[O + 90]), "=f"(d[O + 91]), "=f"(d[O + 92]), "=f"(d[O + 93]), "=f"(d[O + 94]), "=f"(d[O + 95]),
      "=f"(d[O + 96]), "=f"(d[O + 97]), "=f"(d[O + 98]), "=f"(d[O + 99]), "=f"(d[O + 100]), "=f"(d[O + 101]), "=f"(d[O + 102]), "=f"(d[O + 103]),
      "=f"(d[O + 104]), "=f"(d[O + 105]), "=f"(d[O + 106]), "=f"(d[O + 107]), "=f"(d[O + 108]), "=f"(d[O + 109]), "=f"(d[O + 110]), "=f"(d[O + 111]),
      "=f"(d[O + 112]), "=f"(d[O + 113]), "=f"(d[O + 114]), "=f"(d[O + 115]), "=f"(d[O + 116]), "=f"(d[O + 117]), "=f"(d[O + 118]), "=f"(d[O + 119]),
      "=f"(d[O + 120]), "=f"(d[O + 121]), "=f"(d[O + 122]), "=f"(d[O + 123]), "=f"(d[O + 124]), "=f"(d[O + 125]), "=f"(d[O + 126]), "=f"(d[O + 127])
    : "r"(a.x), "r"(a.y), "r"(a.z), "r"(a.w), "l"(db));
}
template <bool INIT, int O, int T> __device__ __forceinline__ void wgmma_n256(float (&d)[T], const uint4& a, uint64_t db) {
  if constexpr (INIT) wgmma_rs_n256_init<O>(d, a, db); else wgmma_rs_n256<O>(d, a, db);
}

template <int N> __device__ __forceinline__ void load_pk(uint4* a, const uint4* p) {
#pragma unroll
  for (int i = 0; i < N; i++) a[i] = ld_ll(p + i * 32);
}
template <int N> __device__ __forceinline__ bool ok_pk(const uint4* a, uint32_t tag) {
  uint32_t x = 0;
#pragma unroll
  for (int i = 0; i < N; i++) x |= a[i].x ^ tag;
  return __all_sync(0xffffffffu, (x & 1u) == 0u);
}
template <int N> __device__ __forceinline__ void ensure_pk(uint4* a, const uint4* p, uint32_t tag) {
  for (uint32_t n = 0; !ok_pk<N>(a, tag) && n < SPIN_LIMIT; n++) load_pk<N>(a, p);
}

constexpr int NSTAGE = 48;
__host__ __device__ constexpr int st_len(int s) { return s < 8 ? 3 : s < 16 ? 2 : s < 24 ? 4 : s < 32 ? 3 : 2; }
__host__ __device__ constexpr int st_g0(int s) {
  int pos = 0, g0 = 0;
  for (int i = 0; i <= s; i++) {
    if (pos + st_len(i) > NGRAN) pos = 0;
    g0 = pos;
    pos += st_len(i);
  }
  return g0;
}
__host__ __device__ constexpr int cnt_first(int g, int s) {
  int n = 0;
  for (int i = 0; i < s; i++) n += (st_g0(i) == g);
  return n;
}
__host__ __device__ constexpr int cnt_cover(int g, int s) {
  int n = 0;
  for (int i = 0; i < s; i++) n += (g >= st_g0(i) && g < st_g0(i) + st_len(i));
  return n;
}
__host__ __device__ constexpr uint32_t flip_mask(int s0, int s1) {
  uint32_t m = 0;
  for (int i = s0; i < s1; i++) m ^= ((1u << st_len(i)) - 1u) << st_g0(i);
  return m;
}
__host__ __device__ constexpr int dn_q(int i) { return i < 3 ? 0 : i < 6 ? 1 : i == 6 ? 0 : i == 7 ? 1 : i < 12 ? 2 : 3; }
__host__ __device__ constexpr int dn_par(int i) { return i < 6 ? (i % 3 == 2) : i < 8 ? 1 : ((i & 3) >= 2); }
__host__ __device__ constexpr int dn_kh(int i) { return i < 6 ? (i % 3 == 1) : i < 8 ? 1 : (i & 1); }
template <int I> struct IC { static constexpr int value = I; };
template <int B, int E, typename F> __device__ __forceinline__ void static_for(F&& f) {
  if constexpr (B < E) { f(IC<B>{}); static_for<B + 1, E>(f); }
}
template <int S> __device__ __forceinline__ void cons_acquire(uint32_t sbase, uint32_t L) {
  constexpr int g0 = st_g0(S);
  constexpr uint32_t p0 = cnt_first(g0, S) & 1, odd = cnt_first(g0, NSTAGE) & 1;
  mbar_wait(sbase + SM_MISC + BAR_FULL + 8 * g0, p0 ^ (L & odd));
}
template <int S> __device__ __forceinline__ void cons_release(uint32_t sbase, int lane) {
  if (lane < st_len(S)) mbar_arrive(sbase + SM_MISC + BAR_EMPTY + 8 * st_g0(S) + 8 * lane);
}
__device__ __forceinline__ bool elect_one() {
  uint32_t p;
  asm volatile("{\n.reg .pred P;\nelect.sync _|P, 0xffffffff;\nselp.u32 %0, 1, 0, P;\n}" : "=r"(p));
  return p != 0;
}
struct ProdRing { uint32_t pos, par; };
template <int N> __device__ __forceinline__ uint32_t prod_acquire(uint32_t sbase, ProdRing& r) {
  if (r.pos + N > NGRAN) r.pos = 0;
  const uint32_t g0 = r.pos;
#pragma unroll
  for (uint32_t i = 0; i < N; i++) mbar_wait(sbase + SM_MISC + BAR_EMPTY + 8 * (g0 + i), ((r.par >> (g0 + i)) & 1u) ^ 1u);
  r.par ^= ((1u << N) - 1u) << g0;
  r.pos = g0 + N;
  return g0;
}
template <int S> __device__ __forceinline__ void prod_acquire_static(uint32_t sbase, uint32_t L) {
  constexpr int g0 = st_g0(S);
  static_for<0, st_len(S)>([&](auto I) {
    constexpr int g = g0 + I.value;
    constexpr uint32_t p0 = cnt_cover(g, S) & 1, odd = cnt_cover(g, NSTAGE) & 1;
    mbar_wait(sbase + SM_MISC + BAR_EMPTY + 8 * g, p0 ^ (L & odd) ^ 1u);
  });
}
template <int S, int KSTEP_BYTES, int LBO, int SBO, int SWZ> __device__ __forceinline__ constexpr uint64_t st_desc(int k) {
  return (uint64_t)((SMEM_ORIGIN + st_g0(S) * GRAN + k * KSTEP_BYTES) >> 4) | ((uint64_t)(LBO >> 4) << 16) |
         ((uint64_t)(SBO >> 4) << 32) | ((uint64_t)SWZ << 62);
}

#define opaque64(...) (__VA_ARGS__)

__device__ __forceinline__ void combine_stats(const uint4& p0, const uint4& p1, float& mean_lo, float& rstd_lo, float& mean_hi, float& rstd_hi) {
  float m0 = __uint_as_float(p0.x), q0 = __uint_as_float(p0.y), m0h = __uint_as_float(p0.z), q0h = __uint_as_float(p0.w);
  float m1 = __uint_as_float(p1.x), q1 = __uint_as_float(p1.y), m1h = __uint_as_float(p1.z), q1h = __uint_as_float(p1.w);
  float s = m0 + m1, sh = m0h + m1h;
  s += __shfl_xor_sync(0xffffffffu, s, 1); sh += __shfl_xor_sync(0xffffffffu, sh, 1);
  s += __shfl_xor_sync(0xffffffffu, s, 2); sh += __shfl_xor_sync(0xffffffffu, sh, 2);
  mean_lo = s * 0.125f; mean_hi = sh * 0.125f;
  float d0 = m0 - mean_lo, d1 = m1 - mean_lo, d0h = m0h - mean_hi, d1h = m1h - mean_hi;
  float t = q0 + q1 + 64.f * (d0 * d0 + d1 * d1), th = q0h + q1h + 64.f * (d0h * d0h + d1h * d1h);
  t += __shfl_xor_sync(0xffffffffu, t, 1); th += __shfl_xor_sync(0xffffffffu, th, 1);
  t += __shfl_xor_sync(0xffffffffu, t, 2); th += __shfl_xor_sync(0xffffffffu, th, 2);
  rstd_lo = rsqrtf(t * (1.f / 512.f) + 1e-5f);
  rstd_hi = rsqrtf(th * (1.f / 512.f) + 1e-5f);
}
__device__ __forceinline__ uint4 local_stats(const float (&v)[32]) {
  float s = 0.f, sh = 0.f;
#pragma unroll
  for (int i = 0; i < 4; i++) {
    s += (v[8 * i + 0] + v[8 * i + 1]) + (v[8 * i + 4] + v[8 * i + 5]);
    sh += (v[8 * i + 2] + v[8 * i + 3]) + (v[8 * i + 6] + v[8 * i + 7]);
  }
  s += __shfl_xor_sync(0xffffffffu, s, 1); sh += __shfl_xor_sync(0xffffffffu, sh, 1);
  s += __shfl_xor_sync(0xffffffffu, s, 2); sh += __shfl_xor_sync(0xffffffffu, sh, 2);
  float m = s * (1.f / 64.f), mh = sh * (1.f / 64.f);
  float q = 0.f, qh = 0.f;
#pragma unroll
  for (int i = 0; i < 4; i++) {
    float a = v[8 * i + 0] - m, b = v[8 * i + 1] - m, c = v[8 * i + 4] - m, d = v[8 * i + 5] - m;
    q += (a * a + b * b) + (c * c + d * d);
    float e = v[8 * i + 2] - mh, f = v[8 * i + 3] - mh, g = v[8 * i + 6] - mh, h = v[8 * i + 7] - mh;
    qh += (e * e + f * f) + (g * g + h * h);
  }
  q += __shfl_xor_sync(0xffffffffu, q, 1); qh += __shfl_xor_sync(0xffffffffu, qh, 1);
  q += __shfl_xor_sync(0xffffffffu, q, 2); qh += __shfl_xor_sync(0xffffffffu, qh, 2);
  return make_uint4(__float_as_uint(m), __float_as_uint(q), __float_as_uint(mh), __float_as_uint(qh));
}

__device__ __forceinline__ void owner_ln_publish(uint32_t sbase, const float (&v)[32], uint32_t tphase, uint32_t tag_xn) {
  PHASE_VARS;
  const uint32_t bars = sbase + SM_MISC;
  const int sg = warp >> 2, qt = warp & 3;
  const int oslab = 2 * ca + sg;
  const int step0 = 16 * cbit + 4 * qt;
  TS(40 + 4 * tphase);
  uint4 st = local_stats(v);
  const uint32_t tb = bars + BAR_TSTAT + 8 * sg;
  const uint32_t slot = sbase + SM_TSTAT + sg * 1024 + (4 * cbit + qt) * 128 + qr * 16;
  if (qt == 0 && lane == 0) mbar_expect_tx(tb, 1024);
  if (qc == 0) {
    st_async128(mapa(slot, 0), st, mapa(tb, 0));
    st_async128(mapa(slot, 1), st, mapa(tb, 1));
  }
  TS(41 + 4 * tphase);
  mbar_wait(tb, tphase);
  TS(42 + 4 * tphase);
  const uint32_t rd = sbase + SM_TSTAT + sg * 1024 + qc * 256 + qr * 16;
  uint4 p0 = lds128(rd), p1 = lds128(rd + 128);
  float ml, rl, mh, rh;
  combine_stats(p0, p1, ml, rl, mh, rh);
  const float bl = -ml * rl, bh = -mh * rh;
  uint4* xn = g_xn + ((c * 8 + oslab) * 32 + step0) * 32 + lane;
  uint4* xr = g_xraw + ((c * 8 + oslab) * 32 + step0) * 32 + lane;
#pragma unroll
  for (int i = 0; i < 4; i++) {
    uint4 o;
    o.x = set_tag(pack2(fmaf(v[8 * i + 0], rl, bl), fmaf(v[8 * i + 1], rl, bl)), tag_xn);
    o.y = pack2(fmaf(v[8 * i + 2], rh, bh), fmaf(v[8 * i + 3], rh, bh));
    o.z = pack2(fmaf(v[8 * i + 4], rl, bl), fmaf(v[8 * i + 5], rl, bl));
    o.w = pack2(fmaf(v[8 * i + 6], rh, bh), fmaf(v[8 * i + 7], rh, bh));
    st_ll(xn + i * 32, o);
  }
#pragma unroll
  for (int i = 0; i < 4; i++) {
    uint4 o;
    o.x = set_tag(pack2(v[8 * i + 0], v[8 * i + 1]), 1u);
    o.y = pack2(v[8 * i + 2], v[8 * i + 3]);
    o.z = pack2(v[8 * i + 4], v[8 * i + 5]);
    o.w = pack2(v[8 * i + 6], v[8 * i + 7]);
    st_ll(xr + i * 32, o);
  }
}

__device__ __forceinline__ uint4 pack8(const float* a) {
  return make_uint4(pack2(a[0], a[1]), pack2(a[2], a[3]), pack2(a[4], a[5]), pack2(a[6], a[7]));
}
template <int U> __device__ __forceinline__ uint4 glu8(const float* g) {
  return make_uint4(pack2(g[0] * g[U], g[1] * g[U + 1]), pack2(g[2] * g[U + 2], g[3] * g[U + 3]), pack2(g[4] * g[U + 4], g[5] * g[U + 5]), pack2(g[6] * g[U + 6], g[7] * g[U + 7]));
}

__global__ void __launch_bounds__(NTHREADS, 1)
fused_kernel(const __grid_constant__ CUtensorMap m_qkv, const __grid_constant__ CUtensorMap m_wo,
             const __grid_constant__ CUtensorMap m_gu2, const __grid_constant__ CUtensorMap m_gu1,
             const __grid_constant__ CUtensorMap m_guh, const __grid_constant__ CUtensorMap m_wd112,
             const __grid_constant__ CUtensorMap m_wd80, const __grid_constant__ CUtensorMap m_wd32,
             const __nv_bfloat16* __restrict__ x_in,
             __nv_bfloat16* __restrict__ out, const char* __restrict__ w_o, const char* __restrict__ w_g,
             const char* __restrict__ w_u, const char* __restrict__ w_d
) {
  extern __shared__ __align__(1024) unsigned char smem_raw[];
  const uint32_t sbase = smem_u32(smem_raw);
  const uint32_t bars = sbase + SM_MISC;
  if ((sbase & 0xFFFFFFu) != SMEM_ORIGIN) return;
  TG(60);

  if (threadIdx.x == 0) {
    for (int i = 0; i < NGRAN; i++) { mbar_init(bars + BAR_FULL + 8 * i, 1); mbar_init(bars + BAR_EMPTY + 8 * i, 8); }
    for (int i = 0; i < 4; i++) mbar_init(bars + BAR_HRECV + 8 * i, 1);
    for (int i = 0; i < 2; i++) { mbar_init(bars + BAR_HREADY + 8 * i, 4); mbar_init(bars + BAR_TSTAT + 8 * i, 1); }
    asm volatile("fence.mbarrier_init.release.cluster;" ::: "memory");
  }
  __syncthreads();
  cluster_sync_all();

  if (threadIdx.x >= 256) {
    asm volatile("setmaxnreg.dec.sync.aligned.u32 40;");
    const int warp = threadIdx.x >> 5, lane = threadIdx.x & 31;
    const int j = blockIdx.x & 7, a = j >> 1, b = j & 1;
    if (warp == 8) {
      ProdRing r{0u, 0u};
      const int cb0 = 224 * j + 32 * b, hb0 = 224 * j + 192 * (b ^ 1);
      const int jp = j ^ 1, cbp = 224 * jp + 32 * (b ^ 1), hbp = 224 * jp + 192 * b;
#pragma unroll 1
      for (uint32_t L = 0; L < 2; L++) {
        r.pos = 0;
        PSTOP_AT(L == 0 ? 0 : 3);
#pragma unroll 1
        for (int kb = 0; kb < 8; kb++) {
          const uint32_t g0 = prod_acquire<3>(sbase, r);
          if (elect_one()) {
            mbar_expect_tx(bars + BAR_FULL + 8 * g0, 24576);
            tma_3d(sbase + g0 * GRAN, &m_qkv, bars + BAR_FULL + 8 * g0, 64 * j, 64 * kb, 0);
          }
        }
        PSTOP_AT(10 * L + 1);
#pragma unroll 1
        for (int i = 0; i < 8; i++) {
          const uint32_t g0 = prod_acquire<2>(sbase, r);
          if (elect_one()) {
            mbar_expect_tx(bars + BAR_FULL + 8 * g0, 16384);
            tma_3d(sbase + g0 * GRAN, &m_wo, bars + BAR_FULL + 8 * g0, 0, 256 * (i & 1) + 64 * (i >> 1), 2 * a);
          }
        }
        PSTOP_AT(10 * L + 2);
#pragma unroll 1
        for (int kb = 0; kb < 8; kb++) {
          const uint32_t g0 = prod_acquire<4>(sbase, r);
          if (elect_one()) {
            mbar_expect_tx(bars + BAR_FULL + 8 * g0, 32768);
            tma_4d(sbase + g0 * GRAN, &m_gu2, bars + BAR_FULL + 8 * g0, cb0, 64 * kb, 0, 0);
          }
        }
#pragma unroll 1
        for (int kb = 0; kb < 8; kb++) {
          const uint32_t g0 = prod_acquire<3>(sbase, r);
          if (elect_one()) {
            mbar_expect_tx(bars + BAR_FULL + 8 * g0, 24576);
            tma_4d(sbase + g0 * GRAN, &m_gu1, bars + BAR_FULL + 8 * g0, cb0 + 128, 64 * kb, 0, 0);
            tma_3d(sbase + g0 * GRAN + 16384, &m_guh, bars + BAR_FULL + 8 * g0, hb0, 64 * kb, 0);
          }
        }
        static_for<0, 16>([&](auto I) {
          constexpr int i = I.value, g0 = st_g0(32 + i);
          prod_acquire_static<32 + i>(sbase, L);
          if (elect_one()) {
            const uint32_t dst = sbase + g0 * GRAN, fb = bars + BAR_FULL + 8 * g0;
            const int n0 = 256 * b + 64 * dn_q(i);
            mbar_expect_tx(fb, 14336);
            if constexpr (dn_kh(i) == 0) {
              tma_2d(dst, &m_wd112, fb, n0, dn_par(i) ? cbp : cb0);
            } else {
              tma_2d(dst, &m_wd80, fb, n0, (dn_par(i) ? cbp : cb0) + 112);
              tma_2d(dst + 10240, &m_wd32, fb, n0, dn_par(i) ? hbp : hb0);
            }
          }
        });
        r.par ^= flip_mask(32, 48);
      }
    } else if (warp == 9) {
      const int cta = blockIdx.x;
      if (lane == 0) l2_prefetch(w_o + cta * 4096, 4096);
      if (lane == 1) l2_prefetch(w_g + cta * 14336, 14336);
      if (lane == 2) l2_prefetch(w_u + cta * 14336, 14336);
      if (lane == 3) l2_prefetch(w_d + cta * 14336, 14336);
    }
    __syncwarp();
    asm volatile("barrier.cluster.arrive.release.aligned;\nbarrier.cluster.wait.acquire.aligned; // producer" ::: "memory");
  } else {
    asm volatile("setmaxnreg.inc.sync.aligned.u32 232;");
    TS(0);
    TG(61);

    {
      PHASE_VARS;
      const int sg = warp >> 2, qt = warp & 3;
      const int oslab = 2 * ca + sg;
      const int step0 = 16 * cbit + 4 * qt;
      float v[32];
      const uint32_t* xp = reinterpret_cast<const uint32_t*>(x_in + (size_t)(c * 128 + oslab * 16 + qr) * 512 + step0 * 16 + qc * 2);
#pragma unroll
      for (int i = 0; i < 4; i++) {
        uint32_t w0 = __ldg(xp + i * 8), w1 = __ldg(xp + 8 * 256 + i * 8), w2 = __ldg(xp + i * 8 + 4), w3 = __ldg(xp + 8 * 256 + i * 8 + 4);
        v[8 * i + 0] = bf_lo(w0); v[8 * i + 1] = bf_hi(w0); v[8 * i + 2] = bf_lo(w1); v[8 * i + 3] = bf_hi(w1);
        v[8 * i + 4] = bf_lo(w2); v[8 * i + 5] = bf_hi(w2); v[8 * i + 6] = bf_lo(w3); v[8 * i + 7] = bf_hi(w3);
      }
      owner_ln_publish(sbase, v, 0u, 1u);
    }
    STOP_AT(0);
    TS(1);

#pragma unroll 1
    for (uint32_t L = 0; L < 2; L++) {
      const uint32_t tag = L ^ 1;
      bar_consumers(1);
      {
        PHASE_VARS;
        uint4 qf[4], kf[4], vf[4], pk[4], pv[4];
        const uint4* halo_src = g_halo + (((L * 16 + (c > 0 ? c - 1 : 0)) * 8 + j) * 8) * 32 + lane;
        {
          float acc[96];
          uint4 A[3][4];
          const uint4* xs = g_xn + ((c * 8 + slab) * 32) * 32 + lane;
          load_pk<4>(A[0], xs);
          ensure_pk<4>(A[0], xs, tag);
          TS(2 + 20 * L);
          load_pk<4>(A[1], xs + 128);
          static_for<0, 8>([&](auto I) {
            constexpr int kb = I.value;
            cons_acquire<kb>(sbase, L);
            wg_fence();
            const uint64_t db = opaque64(st_desc<kb, 2048, 8192, 1024, 1>(0));
            static_for<0, 4>([&](auto K) { constexpr int k = K.value; wgmma_n192<kb == 0 && k == 0, 0>(acc, A[kb % 3][k], db + k * 128); });
            wg_commit();
            if constexpr (kb > 0) {
              wg_wait<1>();
#pragma unroll
              for (int k = 0; k < 4; k++) keep(A[(kb + 2) % 3][k]);
              cons_release<kb - 1>(sbase, lane);
            }
            if constexpr (kb + 1 < 8) ensure_pk<4>(A[(kb + 1) % 3], xs + (kb + 1) * 128, tag);
            if constexpr (kb + 2 < 8) load_pk<4>(A[(kb + 2) % 3], xs + (kb + 2) * 128);
          });
#pragma unroll
          for (int h = 0; h < 4; h++) { pk[h] = make_uint4(0, 0, 0, 0); pv[h] = make_uint4(0, 0, 0, 0); }
          wg_wait<0>();
          TS(3 + 20 * L);
          fence_acc(acc);
#pragma unroll
          for (int k = 0; k < 4; k++) keep(A[1][k]);
          cons_release<7>(sbase, lane);
#pragma unroll
          for (int h = 0; h < 4; h++) kf[h] = pack8(&acc[32 + 8 * h]);
#pragma unroll
          for (int h = 0; h < 4; h++) {
            uint4 t = pack8(&acc[64 + 8 * h]);
            vf[h] = make_uint4(movm(t.x), movm(t.y), movm(t.z), movm(t.w));
          }
          if (slab == 7 && c < 15) {
            uint4* hd = g_halo + (((L * 16 + c) * 8 + j) * 8) * 32 + lane;
#pragma unroll
            for (int h = 0; h < 4; h++) {
              uint4 t = kf[h]; t.x |= 1u; st_ll(hd + h * 32, t);
              t = vf[h]; t.x |= 1u; st_ll(hd + 128 + h * 32, t);
            }
          }
          const uint32_t kvw = areg + AR_KV + w * 4096 + lane * 16;
#pragma unroll
          for (int h = 0; h < 4; h++) { sts128(kvw + h * 512, kf[h]); sts128(kvw + 2048 + h * 512, vf[h]); }
          if (slab == 0 && c > 0) { load_pk<4>(pk, halo_src); load_pk<4>(pv, halo_src + 128); }
#pragma unroll
          for (int h = 0; h < 4; h++) qf[h] = pack8(&acc[8 * h]);
        }
        bar_consumers(2);
        const bool first = (slab == 0) && (c == 0);
        if (slab > 0) {
          const int ps = slab - 1;
          const uint32_t kvr = sbase + SM_AREG + (ps >> 2) * 65536 + AR_KV + (ps & 3) * 4096 + lane * 16;
#pragma unroll
          for (int h = 0; h < 4; h++) { pk[h] = lds128(kvr + h * 512); pv[h] = lds128(kvr + 2048 + h * 512); }
        } else if (c > 0) {
          ensure_pk<4>(pk, halo_src, 1u);
          ensure_pk<4>(pv, halo_src + 128, 1u);
          uint4* hz = const_cast<uint4*>(halo_src);
#pragma unroll
          for (int h = 0; h < 8; h++) st_ll(hz + h * 32, make_uint4(0, 0, 0, 0));
        }
        TS(4 + 20 * L);
        const bool e = qr & 1;
        const bool newer = (2 * qc + (qr & 1)) <= qr;
        const float sc = 0.25f * 1.4426950408889634f;
        const float NEG = -1e30f;
        uint4* od = g_o + ((c * 8 + slab) * 32 + 4 * j) * 32 + lane;
        float mid_l[4], oth_l[4], mid_h[4], oth_h[4], ml[4], mh[4];
#pragma unroll
        for (int h = 0; h < 4; h++) {
          float s0[4] = {0, 0, 0, 0}, s1[4] = {0, 0, 0, 0}, s2[4] = {0, 0, 0, 0}, s3[4] = {0, 0, 0, 0};
          mma16816(s0, qf[h], pk[h].x, pk[h].z);
          mma16816(s1, qf[h], pk[h].y, pk[h].w);
          mma16816(s2, qf[h], kf[h].x, kf[h].z);
          mma16816(s3, qf[h], kf[h].y, kf[h].w);
          mid_l[h] = e ? s1[1] : s1[0];
          oth_l[h] = newer ? (e ? s2[1] : s2[0]) : (e ? s0[1] : s0[0]);
          mid_h[h] = e ? s2[3] : s2[2];
          oth_h[h] = newer ? (e ? s3[3] : s3[2]) : (e ? s1[3] : s1[2]);
          if (first) { mid_l[h] = NEG; if (!newer) { oth_l[h] = NEG; oth_h[h] = NEG; } }
          ml[h] = fmaxf(mid_l[h], oth_l[h]); mh[h] = fmaxf(mid_h[h], oth_h[h]);
        }
#pragma unroll
        for (int h = 0; h < 4; h++) { ml[h] = fmaxf(ml[h], __shfl_xor_sync(0xffffffffu, ml[h], 1)); mh[h] = fmaxf(mh[h], __shfl_xor_sync(0xffffffffu, mh[h], 1)); }
#pragma unroll
        for (int h = 0; h < 4; h++) { ml[h] = fmaxf(ml[h], __shfl_xor_sync(0xffffffffu, ml[h], 2)); mh[h] = fmaxf(mh[h], __shfl_xor_sync(0xffffffffu, mh[h], 2)); }
        float sl[4], sh[4];
#pragma unroll
        for (int h = 0; h < 4; h++) {
          mid_l[h] = exp2f((mid_l[h] - ml[h]) * sc); oth_l[h] = exp2f((oth_l[h] - ml[h]) * sc);
          mid_h[h] = exp2f((mid_h[h] - mh[h]) * sc); oth_h[h] = exp2f((oth_h[h] - mh[h]) * sc);
          sl[h] = mid_l[h] + oth_l[h]; sh[h] = mid_h[h] + oth_h[h];
        }
#pragma unroll
        for (int h = 0; h < 4; h++) { sl[h] += __shfl_xor_sync(0xffffffffu, sl[h], 1); sh[h] += __shfl_xor_sync(0xffffffffu, sh[h], 1); }
#pragma unroll
        for (int h = 0; h < 4; h++) { sl[h] += __shfl_xor_sync(0xffffffffu, sl[h], 2); sh[h] += __shfl_xor_sync(0xffffffffu, sh[h], 2); }
#pragma unroll
        for (int h = 0; h < 4; h++) {
          const float il = __fdividef(1.f, sl[h]), ih = __fdividef(1.f, sh[h]);
          const float a = mid_l[h] * il, b = oth_l[h] * il, cc = mid_h[h] * ih, d = oth_h[h] * ih;
          const uint32_t bml = e ? pack2(0.f, a) : pack2(a, 0.f), bol = e ? pack2(0.f, b) : pack2(b, 0.f);
          const uint32_t bmh = e ? pack2(0.f, cc) : pack2(cc, 0.f), boh = e ? pack2(0.f, d) : pack2(d, 0.f);
          uint4 P0 = make_uint4(newer ? 0u : bol, 0u, bml, newer ? 0u : boh);
          uint4 P1 = make_uint4(newer ? bol : 0u, bmh, 0u, newer ? boh : 0u);
          float o0[4] = {0, 0, 0, 0}, o1[4] = {0, 0, 0, 0};
          mma16816(o0, P0, pv[h].x, pv[h].y);
          mma16816(o1, P0, pv[h].z, pv[h].w);
          mma16816(o0, P1, vf[h].x, vf[h].y);
          mma16816(o1, P1, vf[h].z, vf[h].w);
          uint4 o = make_uint4(set_tag(pack2(o0[0], o0[1]), tag), pack2(o0[2], o0[3]), pack2(o1[0], o1[1]), pack2(o1[2], o1[3]));
          st_ll(od + h * 32, o);
        }
      }
      TS(5 + 20 * L);
      if (L == 0) { STOP_AT(1); } else { STOP_AT(11); }
      {
        PHASE_VARS;
        const int slabA = 4 * cbit + w;
        float acc[64];
        zero_acc(acc);
        uint4 A[16];
        uint4 xr[4];
        const uint4* os = g_o + ((c * 8 + slabA) * 32 + 16 * g) * 32 + lane;
        uint4* xp = g_xraw + ((c * 8 + slabA) * 32 + 8 * ca + 4 * g) * 32 + lane;
        load_pk<4>(A, os);
        ensure_pk<4>(A, os, tag);
        TS(6 + 20 * L);
        load_pk<12>(A + 4, os + 128);
        load_pk<4>(xr, xp);
        static_for<0, 8>([&](auto I) {
          constexpr int i = I.value, kb = i >> 1;
          cons_acquire<8 + i>(sbase, L);
          if ((i & 1) == g) {
            if constexpr (kb > 0) ensure_pk<4>(A + 4 * kb, os + kb * 128, tag);
            wg_fence();
            const uint64_t db = opaque64(st_desc<8 + i, 2048, 8192, 1024, 1>(0));
            static_for<0, 4>([&](auto K) { constexpr int k = K.value; wgmma_n128<false, 0>(acc, A[4 * kb + k], db + k * 128); });
            wg_commit();
            if constexpr (kb > 0) { wg_wait<1>(); cons_release<8 + i - 2>(sbase, lane); }
          } else {
            cons_release<8 + i>(sbase, lane);
          }
        });
        wg_wait<0>();
        TS(7 + 20 * L);
        fence_acc(acc);
#pragma unroll
        for (int k = 0; k < 16; k++) keep(A[k]);
        if (g == 0) cons_release<14>(sbase, lane); else cons_release<15>(sbase, lane);
        const uint32_t xo = sbase + SM_AREG + (g ^ 1) * 65536 + AR_X + t128 * 16;
        const uint32_t xi = areg + AR_X + t128 * 16;
        float v[32];
        if (g == 0) {
#pragma unroll
          for (int i = 0; i < 8; i++) sts128(xo + i * 2048, make_uint4(__float_as_uint(acc[32 + 4 * i]), __float_as_uint(acc[33 + 4 * i]), __float_as_uint(acc[34 + 4 * i]), __float_as_uint(acc[35 + 4 * i])));
#pragma unroll
          for (int i = 0; i < 32; i++) v[i] = acc[i];
        } else {
#pragma unroll
          for (int i = 0; i < 8; i++) sts128(xo + i * 2048, make_uint4(__float_as_uint(acc[4 * i]), __float_as_uint(acc[1 + 4 * i]), __float_as_uint(acc[2 + 4 * i]), __float_as_uint(acc[3 + 4 * i])));
#pragma unroll
          for (int i = 0; i < 32; i++) v[i] = acc[32 + i];
        }
        bar_consumers(3);
        ensure_pk<4>(xr, xp, 1u);
#pragma unroll
        for (int i = 0; i < 8; i++) {
          uint4 t = lds128(xi + i * 2048);
          v[4 * i] += __uint_as_float(t.x); v[4 * i + 1] += __uint_as_float(t.y); v[4 * i + 2] += __uint_as_float(t.z); v[4 * i + 3] += __uint_as_float(t.w);
        }
#pragma unroll
        for (int i = 0; i < 4; i++) {
          v[8 * i + 0] += bf_lo(xr[i].x); v[8 * i + 1] += bf_hi(xr[i].x); v[8 * i + 2] += bf_lo(xr[i].y); v[8 * i + 3] += bf_hi(xr[i].y);
          v[8 * i + 4] += bf_lo(xr[i].z); v[8 * i + 5] += bf_hi(xr[i].z); v[8 * i + 6] += bf_lo(xr[i].w); v[8 * i + 7] += bf_hi(xr[i].w);
          uint4 o = pack8(&v[8 * i]);
          o.x = set_tag(o.x, 0u);
          st_ll(xp + i * 32, o);
        }
        uint4 st = local_stats(v);
        st.x = set_tag(st.x, tag);
        if (qc == 0) st_ll(g_stats + ((c * 8 + slabA) * 8 + 2 * ca + g) * 8 + qr, st);
      }
      TS(8 + 20 * L);
      if (L == 0) { STOP_AT(2); } else { STOP_AT(12); }
      uint4 hs[14];
      {
        PHASE_VARS;
        float acc[128];
        uint4 X[3][4];
        const uint4* xs = g_xraw + ((c * 8 + slab) * 32) * 32 + lane;
        const uint4* sp = g_stats + ((c * 8 + slab) * 8 + 2 * qc) * 8 + qr;
        float rl, rh, bl, bh;
        {
          uint4 p[2];
          load_pk<4>(X[0], xs);
          p[0] = ld_ll(sp); p[1] = ld_ll(sp + 8);
          for (uint32_t n = 0; !ok_pk<2>(p, tag) && n < SPIN_LIMIT; n++) { p[0] = ld_ll(sp); p[1] = ld_ll(sp + 8); }
          TS(9 + 20 * L);
          float ml, mh;
          combine_stats(p[0], p[1], ml, rl, mh, rh);
          bl = -ml * rl; bh = -mh * rh;
        }
        ensure_pk<4>(X[0], xs, 0u);
        load_pk<4>(X[1], xs + 128);
        const uint32_t acp = areg + t128 * 16;
        auto normalise = [&](uint4 (&xb)[4], int kb) {
#pragma unroll
          for (int k = 0; k < 4; k++) {
            const uint4 x = xb[k];
            uint4 y;
            y.x = pack2(fmaf(bf_lo(x.x), rl, bl), fmaf(bf_hi(x.x), rl, bl));
            y.y = pack2(fmaf(bf_lo(x.y), rh, bh), fmaf(bf_hi(x.y), rh, bh));
            y.z = pack2(fmaf(bf_lo(x.z), rl, bl), fmaf(bf_hi(x.z), rl, bl));
            y.w = pack2(fmaf(bf_lo(x.w), rh, bh), fmaf(bf_hi(x.w), rh, bh));
            xb[k] = y;
            sts128(acp + (kb * 4 + k) * 2048, y);
          }
        };
        normalise(X[0], 0);
        static_for<0, 8>([&](auto I) {
          constexpr int kb = I.value;
          cons_acquire<16 + kb>(sbase, L);
          wg_fence();
          const uint64_t db = opaque64(st_desc<16 + kb, 2048, 8192, 1024, 1>(0));
          static_for<0, 4>([&](auto K) { constexpr int k = K.value; wgmma_n256<kb == 0 && k == 0, 0>(acc, X[kb % 3][k], db + k * 128); });
          wg_commit();
          if constexpr (kb > 0) {
            wg_wait<1>();
#pragma unroll
            for (int k = 0; k < 4; k++) keep(X[(kb + 2) % 3][k]);
            cons_release<16 + kb - 1>(sbase, lane);
          }
          if constexpr (kb + 1 < 8) ensure_pk<4>(X[(kb + 1) % 3], xs + (kb + 1) * 128, 0u);
          if constexpr (kb + 2 < 8) load_pk<4>(X[(kb + 2) % 3], xs + (kb + 2) * 128);
          if constexpr (kb + 1 < 8) normalise(X[(kb + 1) % 3], kb + 1);
        });
        wg_wait<0>();
        TS(10 + 20 * L);
        fence_acc(acc);
#pragma unroll
        for (int k = 0; k < 4; k++) keep(X[1][k]);
        cons_release<23>(sbase, lane);
        uint4 B[2][4];
#pragma unroll
        for (int k = 0; k < 4; k++) B[0][k] = lds128(acp + k * 2048);
#pragma unroll
        for (int s = 0; s < 8; s++) hs[s] = glu8<32>(&acc[64 * (s >> 2) + 8 * (s & 3)]);
        float acc2[96];
        const uint32_t hdst = mapa(areg + t128 * 16, cbit ^ 1);
        const uint32_t hbar1 = mapa(bars + BAR_HRECV + 16 * g, cbit ^ 1);
        if (t128 == 0) { mbar_expect_tx(bars + BAR_HRECV + 16 * g, 8 * 2048); mbar_expect_tx(bars + BAR_HRECV + 16 * g + 8, 6 * 2048); }
        static_for<0, 8>([&](auto I) {
          constexpr int kb = I.value;
          cons_acquire<24 + kb>(sbase, L);
          wg_fence();
          const uint64_t db = opaque64(st_desc<24 + kb, 2048, 8192, 1024, 1>(0));
          const uint64_t dh = opaque64(st_desc<24 + kb, 1024, 4096, 512, 2>(0) + (16384 >> 4));
          static_for<0, 4>([&](auto K) {
            constexpr int k = K.value;
            wgmma_n128<kb == 0 && k == 0, 0>(acc2, B[kb & 1][k], db + k * 128);
            wgmma_n64<kb == 0 && k == 0, 64>(acc2, B[kb & 1][k], dh + k * 64);
          });
          wg_commit();
          if constexpr (kb > 0) {
            wg_wait<1>();
#pragma unroll
            for (int k = 0; k < 4; k++) keep(B[(kb + 1) & 1][k]);
            cons_release<24 + kb - 1>(sbase, lane);
          }
          if constexpr (kb + 1 < 8) {
#pragma unroll
            for (int k = 0; k < 4; k++) B[(kb + 1) & 1][k] = lds128(acp + ((kb + 1) * 4 + k) * 2048);
          }
          if constexpr (kb == 3) {
            __syncwarp();
            if (lane == 0) mbar_arrive_remote(mapa(bars + BAR_HREADY + 8 * g, cbit ^ 1));
          }
          if constexpr (kb >= 4) {
            if constexpr (kb == 4) mbar_wait(bars + BAR_HREADY + 8 * g, L);
            st_async128(hdst + (2 * kb - 8) * 2048, hs[2 * kb - 8], hbar1);
            st_async128(hdst + (2 * kb - 7) * 2048, hs[2 * kb - 7], hbar1);
          }
        });
        wg_wait<0>();
        TS(11 + 20 * L);
        fence_acc(acc2);
#pragma unroll
        for (int k = 0; k < 4; k++) keep(B[1][k]);
        cons_release<31>(sbase, lane);
#pragma unroll
        for (int s = 0; s < 4; s++) hs[8 + s] = glu8<32>(&acc2[8 * s]);
#pragma unroll
        for (int s = 0; s < 2; s++) hs[12 + s] = glu8<16>(&acc2[64 + 8 * s]);
      }
      {
        PHASE_VARS;
        TS(12 + 20 * L);
        const uint32_t hdst = mapa(areg + t128 * 16, cbit ^ 1);
        const uint32_t hbar2 = mapa(bars + BAR_HRECV + 16 * g + 8, cbit ^ 1);
        uint4* pd = g_part + ((((c * 4 + (slab >> 1)) * 2 + cbit) * 4 + ca) * 2 + (slab & 1)) * 16 * 32 + lane;
        uint4 hp[14];
        float a0[32], a1[32], a2[32], a3[32];
        auto publish = [&](float (&a)[32], int q, int s0, int s1) {
#pragma unroll
          for (int s = s0; s < s1; s++) {
            uint4 o = pack8(&a[8 * s]);
            o.x = set_tag(o.x, tag);
            st_ll(pd + (4 * q + s) * 32, o);
          }
        };
        static_for<0, 16>([&](auto I) {
          constexpr int i = I.value, q = dn_q(i), par = dn_par(i), kh = dn_kh(i);
          if constexpr (i == 2) {
            mbar_wait(bars + BAR_HRECV + 16 * g, L);
            TS(13 + 20 * L);
#pragma unroll
            for (int k = 0; k < 7; k++) hp[k] = lds128(areg + t128 * 16 + k * 2048);
          }
          if constexpr (i == 6) {
            mbar_wait(bars + BAR_HRECV + 16 * g + 8, L);
            TS(14 + 20 * L);
#pragma unroll
            for (int k = 7; k < 14; k++) hp[k] = lds128(areg + t128 * 16 + k * 2048);
          }
          cons_acquire<32 + i>(sbase, L);
          wg_fence();
          const uint64_t db0 = opaque64(st_desc<32 + i, 2048, 8192, 1024, 1>(0));
          static_for<0, 7>([&](auto K) {
            constexpr int k = K.value;
            constexpr bool init = (k == 0 && par == 0 && kh == 0);
            const uint64_t db = db0 + k * 128;
            if constexpr (q == 0) { if constexpr (par) wgmma_n64<init, 0>(a0, hp[7 * kh + k], db); else wgmma_n64<init, 0>(a0, hs[7 * kh + k], db); }
            if constexpr (q == 1) { if constexpr (par) wgmma_n64<init, 0>(a1, hp[7 * kh + k], db); else wgmma_n64<init, 0>(a1, hs[7 * kh + k], db); }
            if constexpr (q == 2) { if constexpr (par) wgmma_n64<init, 0>(a2, hp[7 * kh + k], db); else wgmma_n64<init, 0>(a2, hs[7 * kh + k], db); }
            if constexpr (q == 3) { if constexpr (par) wgmma_n64<init, 0>(a3, hp[7 * kh + k], db); else wgmma_n64<init, 0>(a3, hs[7 * kh + k], db); }
          });
          wg_commit();
          if constexpr (i > 0) { wg_wait<1>(); cons_release<32 + i - 1>(sbase, lane); }
          if constexpr (i < 3) {
            st_async128(hdst + (8 + 2 * i) * 2048, hs[8 + 2 * i], hbar2);
            st_async128(hdst + (9 + 2 * i) * 2048, hs[9 + 2 * i], hbar2);
          }
          if constexpr (i == 7) { fence_acc(a0); publish(a0, 0, 0, 2); }
          if constexpr (i == 8) { fence_acc(a1); publish(a0, 0, 2, 4); }
          if constexpr (i == 9) publish(a1, 1, 0, 2);
          if constexpr (i == 10) publish(a1, 1, 2, 4);
          if constexpr (i == 12) { fence_acc(a2); publish(a2, 2, 0, 2); }
          if constexpr (i == 13) publish(a2, 2, 2, 4);
        });
        wg_wait<0>();
        TS(15 + 20 * L);
        fence_acc(a3);
#pragma unroll
        for (int k = 0; k < 14; k++) { keep(hp[k]); keep(hs[k]); }
        cons_release<47>(sbase, lane);
        publish(a3, 3, 0, 4);
      }
      {
        PHASE_VARS;
        const int sg = warp >> 2, qt = warp & 3;
        const int oslab = 2 * ca + sg;
        const uint4* xq = g_xraw + ((c * 8 + oslab) * 32 + 16 * cbit + 4 * qt) * 32 + lane;
        const uint4* ps = g_part + ((((c * 4 + ca) * 2 + cbit) * 4) * 2 + sg) * 16 * 32 + (4 * qt) * 32 + lane;
        uint4 xr[4], P[4][4];
        float v[32];
        load_pk<4>(xr, xq);
#pragma unroll
        for (int src = 0; src < 4; src++) load_pk<4>(P[src], ps + src * (2 * 16 * 32));
#pragma unroll
        for (int src = 0; src < 4; src++) ensure_pk<4>(P[src], ps + src * (2 * 16 * 32), tag);
        TS(16 + 20 * L);
        ensure_pk<4>(xr, xq, 0u);
#pragma unroll
        for (int i = 0; i < 4; i++) {
          v[8 * i + 0] = bf_lo(xr[i].x); v[8 * i + 1] = bf_hi(xr[i].x); v[8 * i + 2] = bf_lo(xr[i].y); v[8 * i + 3] = bf_hi(xr[i].y);
          v[8 * i + 4] = bf_lo(xr[i].z); v[8 * i + 5] = bf_hi(xr[i].z); v[8 * i + 6] = bf_lo(xr[i].w); v[8 * i + 7] = bf_hi(xr[i].w);
          float d[8] = {0, 0, 0, 0, 0, 0, 0, 0};
#pragma unroll
          for (int src = 0; src < 4; src++) {
            const uint4 p = P[src][i];
            d[0] += bf_lo(p.x); d[1] += bf_hi(p.x); d[2] += bf_lo(p.y); d[3] += bf_hi(p.y);
            d[4] += bf_lo(p.z); d[5] += bf_hi(p.z); d[6] += bf_lo(p.w); d[7] += bf_hi(p.w);
          }
#pragma unroll
          for (int k = 0; k < 8; k++) v[8 * i + k] += d[k];
        }
        if (L == 0) {
          owner_ln_publish(sbase, v, 1u, 0u);
        } else {
          uint32_t* op = reinterpret_cast<uint32_t*>(out + (size_t)(c * 128 + oslab * 16 + qr) * 512 + (16 * cbit + 4 * qt) * 16 + qc * 2);
#pragma unroll
          for (int i = 0; i < 4; i++) {
            op[i * 8] = pack2(v[8 * i], v[8 * i + 1]);
            op[8 * 256 + i * 8] = pack2(v[8 * i + 2], v[8 * i + 3]);
            op[i * 8 + 4] = pack2(v[8 * i + 4], v[8 * i + 5]);
            op[8 * 256 + i * 8 + 4] = pack2(v[8 * i + 6], v[8 * i + 7]);
          }
        }
      }
      TS(17 + 20 * L);
      if (L == 0) { STOP_AT(3); }
    }
    TG(62);
    asm volatile("barrier.cluster.arrive.release.aligned;\nbarrier.cluster.wait.acquire.aligned; // consumer" ::: "memory");
    TG(63);
  }
}

typedef CUresult (*EncodeFn)(CUtensorMap*, CUtensorMapDataType, cuuint32_t, void*, const cuuint64_t*, const cuuint64_t*,
                             const cuuint32_t*, const cuuint32_t*, CUtensorMapInterleave, CUtensorMapSwizzle,
                             CUtensorMapL2promotion, CUtensorMapFloatOOBfill);

void encode(EncodeFn fn, CUtensorMap* m, int rank, const void* base, const cuuint64_t* dims, const cuuint64_t* strides,
            const cuuint32_t* box, CUtensorMapSwizzle sw) {
  cuuint32_t es[5] = {1, 1, 1, 1, 1};
  fn(m, CU_TENSOR_MAP_DATA_TYPE_BFLOAT16, (cuuint32_t)rank, const_cast<void*>(base), dims, strides, box, es,
     CU_TENSOR_MAP_INTERLEAVE_NONE, sw, CU_TENSOR_MAP_L2_PROMOTION_L2_128B, CU_TENSOR_MAP_FLOAT_OOB_FILL_NONE);
}

}

extern "C" void kernel_launch(void* const* d_in, const int* in_sizes, int n_in, void* d_out, int out_size) {
  (void)in_sizes; (void)n_in; (void)out_size;
  const __nv_bfloat16* x = (const __nv_bfloat16*)d_in[0];
  const char* wqkv = (const char*)d_in[1];
  const char* wo = (const char*)d_in[2];
  const char* wg = (const char*)d_in[4];
  const char* wu = (const char*)d_in[5];
  const char* wd = (const char*)d_in[6];

  static EncodeFn fn = nullptr;
  if (!fn) {
    void* p = nullptr;
    cudaDriverEntryPointQueryResult st;
    cudaGetDriverEntryPoint("cuTensorMapEncodeTiled", &p, cudaEnableDefault, &st);
    fn = (EncodeFn)p;
    cudaFuncSetAttribute(fused_kernel, cudaFuncAttributeMaxDynamicSharedMemorySize, SMEM_BYTES);
  }
  CUtensorMap m_qkv, m_wo, m_gu2, m_gu1, m_guh, m_wd112, m_wd80, m_wd32;
  {
    cuuint64_t dims[3] = {512, 512, 3}, str[2] = {3072, 1024};
    cuuint32_t box[3] = {64, 64, 3};
    encode(fn, &m_qkv, 3, wqkv, dims, str, box, CU_TENSOR_MAP_SWIZZLE_128B);
  }
  {
    cuuint64_t dims[3] = {64, 512, 8}, str[2] = {1024, 128};
    cuuint32_t box[3] = {64, 64, 2};
    encode(fn, &m_wo, 3, wo, dims, str, box, CU_TENSOR_MAP_SWIZZLE_128B);
  }
  {
    const char* lo = wg < wu ? wg : wu;
    cuuint64_t diff = (cuuint64_t)(wg < wu ? wu - wg : wg - wu);
    cuuint64_t dims[4] = {1792, 512, 2, 2}, str[3] = {3584, diff, 128};
    cuuint32_t box2[4] = {64, 64, 2, 2}, box1[4] = {64, 64, 2, 1}, boxh[3] = {32, 64, 2};
    encode(fn, &m_gu2, 4, lo, dims, str, box2, CU_TENSOR_MAP_SWIZZLE_128B);
    encode(fn, &m_gu1, 4, lo, dims, str, box1, CU_TENSOR_MAP_SWIZZLE_128B);
    encode(fn, &m_guh, 3, lo, dims, str, boxh, CU_TENSOR_MAP_SWIZZLE_64B);
  }
  {
    cuuint64_t dims[2] = {512, 1792}, str[1] = {1024};
    cuuint32_t b112[2] = {64, 112}, b80[2] = {64, 80}, b32[2] = {64, 32};
    encode(fn, &m_wd112, 2, wd, dims, str, b112, CU_TENSOR_MAP_SWIZZLE_128B);
    encode(fn, &m_wd80, 2, wd, dims, str, b80, CU_TENSOR_MAP_SWIZZLE_128B);
    encode(fn, &m_wd32, 2, wd, dims, str, b32, CU_TENSOR_MAP_SWIZZLE_128B);
  }
  cudaLaunchConfig_t cfg = {};
  cfg.gridDim = dim3(128);
  cfg.blockDim = dim3(NTHREADS);
  cfg.dynamicSmemBytes = SMEM_BYTES;
  cfg.stream = cudaStreamPerThread;
  cudaLaunchAttribute at[1];
  at[0].id = cudaLaunchAttributeClusterDimension;
  at[0].val.clusterDim.x = 2; at[0].val.clusterDim.y = 1; at[0].val.clusterDim.z = 1;
  cfg.attrs = at; cfg.numAttrs = 1;
  cudaLaunchKernelEx(&cfg, fused_kernel, m_qkv, m_wo, m_gu2, m_gu1, m_guh, m_wd112, m_wd80, m_wd32, x, (__nv_bfloat16*)d_out, wo, wg, wu, wd
  );
}
```

```cpp
#include <cuda_runtime.h>
#include <cuda_bf16.h>
#include <cuda.h>
#include <stdint.h>

namespace {

constexpr int NTHREADS = 384;
constexpr int GRAN = 8192;
constexpr int NGRAN = 12;
constexpr int SM_AREG = NGRAN * GRAN;
constexpr int SM_MISC = SM_AREG + 131072;
constexpr int SM_TSTAT = SM_MISC + 256;
constexpr int SMEM_BYTES = SM_TSTAT + 2048;
constexpr int BAR_FULL = 0, BAR_EMPTY = 96, BAR_HRECV = 192, BAR_HREADY = 224, BAR_TSTAT = 240;

__device__ uint4 g_xn[16 * 8 * 32 * 32];
__device__ uint4 g_xraw[16 * 8 * 32 * 32];
__device__ uint4 g_o[16 * 8 * 32 * 32];
__device__ uint4 g_stats[16 * 8 * 8 * 8];
__device__ uint4 g_halo[2 * 32 * 8 * 8 * 32];
__device__ uint4 g_part[16 * 4 * 2 * 4 * 2 * 16 * 32];

#define TS(n)
#define TG(n)
#define OPAQUE(x) asm volatile("" : "+r"(x))
#define PHASE_VARS                                                                                   \
  int tid_ = threadIdx.x, bid_ = blockIdx.x;                                                         \
  OPAQUE(tid_); OPAQUE(bid_);                                                                        \
  const int lane = tid_ & 31, warp = tid_ >> 5, g = warp >> 2, w = warp & 3, t128 = tid_ & 127;      \
  const int qr = lane >> 2, qc = lane & 3, slab = warp;                                              \
  const int c = bid_ >> 3, j = bid_ & 7, ca = j >> 1, cbit = j & 1;                                  \
  const uint32_t areg = sbase + SM_AREG + g * 65536;                                                 \
  (void)g; (void)j; (void)w; (void)t128; (void)qr; (void)qc; (void)slab; (void)c; (void)ca; (void)cbit; (void)areg; (void)lane
#define STOP_AT(n)
#define PSTOP_AT(n)

__device__ __forceinline__ uint32_t smem_u32(const void* p) { return (uint32_t)__cvta_generic_to_shared(p); }
__device__ __forceinline__ void mbar_init(uint32_t bar, uint32_t cnt) {
  asm volatile("mbarrier.init.shared::cta.b64 [%0], %1;" ::"r"(bar), "r"(cnt) : "memory");
}
__device__ __forceinline__ void mbar_expect_tx(uint32_t bar, uint32_t bytes) {
  asm volatile("mbarrier.arrive.expect_tx.shared::cta.b64 _, [%0], %1;" ::"r"(bar), "r"(bytes) : "memory");
}
__device__ __forceinline__ void mbar_arrive(uint32_t bar) {
  asm volatile("mbarrier.arrive.shared::cta.b64 _, [%0];" ::"r"(bar) : "memory");
}
__device__ __forceinline__ void mbar_arrive_remote(uint32_t cluster_addr) {
  asm volatile("mbarrier.arrive.relaxed.cluster.shared::cluster.b64 _, [%0];" ::"r"(cluster_addr) : "memory");
}
__device__ __forceinline__ bool mbar_try(uint32_t bar, uint32_t parity) {
  uint32_t ok;
  asm volatile("{\n.reg .pred p;\nmbarrier.try_wait.parity.shared::cta.b64 p, [%1], %2;\nselp.u32 %0, 1, 0, p;\n}"
               : "=r"(ok) : "r"(bar), "r"(parity) : "memory");
  return ok != 0;
}
constexpr uint32_t SPIN_LIMIT = 1u << 16;
constexpr uint32_t SMEM_ORIGIN = 1024;
__device__ __forceinline__ void mbar_wait(uint32_t bar, uint32_t parity) {
  for (uint32_t n = 0; !mbar_try(bar, parity) && n < SPIN_LIMIT; n++) {}
}
__device__ __forceinline__ uint32_t mapa(uint32_t addr, uint32_t rank) {
  uint32_t r;
  asm volatile("mapa.shared::cluster.u32 %0, %1, %2;" : "=r"(r) : "r"(addr), "r"(rank));
  return r;
}
__device__ __forceinline__ void cluster_sync_all() {
  asm volatile("barrier.cluster.arrive.release.aligned;\nbarrier.cluster.wait.acquire.aligned;" ::: "memory");
}

__device__ __forceinline__ void tma_2d(uint32_t dst, const CUtensorMap* m, uint32_t bar, int c0, int c1) {
  asm volatile("cp.async.bulk.tensor.2d.shared::cluster.global.mbarrier::complete_tx::bytes [%0], [%1, {%3, %4}], [%2];"
               ::"r"(dst), "l"(m), "r"(bar), "r"(c0), "r"(c1) : "memory");
}
__device__ __forceinline__ void tma_3d(uint32_t dst, const CUtensorMap* m, uint32_t bar, int c0, int c1, int c2) {
  asm volatile("cp.async.bulk.tensor.3d.shared::cluster.global.mbarrier::complete_tx::bytes [%0], [%1, {%3, %4, %5}], [%2];"
               ::"r"(dst), "l"(m), "r"(bar), "r"(c0), "r"(c1), "r"(c2) : "memory");
}
__device__ __forceinline__ void tma_4d(uint32_t dst, const CUtensorMap* m, uint32_t bar, int c0, int c1, int c2, int c3) {
  asm volatile("cp.async.bulk.tensor.4d.shared::cluster.global.mbarrier::complete_tx::bytes [%0], [%1, {%3, %4, %5, %6}], [%2];"
               ::"r"(dst), "l"(m), "r"(bar), "r"(c0), "r"(c1), "r"(c2), "r"(c3) : "memory");
}
__device__ __forceinline__ void l2_prefetch(const void* p, uint32_t bytes) {
  asm volatile("cp.async.bulk.prefetch.L2.global [%0], %1;" ::"l"(p), "r"(bytes) : "memory");
}

__device__ __forceinline__ uint4 ld_ll(const uint4* p) {
  uint4 v;
  asm volatile("ld.relaxed.gpu.global.v4.u32 {%0,%1,%2,%3}, [%4];" : "=r"(v.x), "=r"(v.y), "=r"(v.z), "=r"(v.w) : "l"(p) : "memory");
  return v;
}
__device__ __forceinline__ void st_ll(uint4* p, uint4 v) {
  asm volatile("st.relaxed.gpu.global.v4.u32 [%0], {%1,%2,%3,%4};" ::"l"(p), "r"(v.x), "r"(v.y), "r"(v.z), "r"(v.w) : "memory");
}
__device__ __forceinline__ uint4 lds128(uint32_t a) {
  uint4 v;
  asm volatile("ld.shared.v4.u32 {%0,%1,%2,%3}, [%4];" : "=r"(v.x), "=r"(v.y), "=r"(v.z), "=r"(v.w) : "r"(a) : "memory");
  return v;
}
__device__ __forceinline__ void sts128(uint32_t a, uint4 v) {
  asm volatile("st.shared.v4.u32 [%0], {%1,%2,%3,%4};" ::"r"(a), "r"(v.x), "r"(v.y), "r"(v.z), "r"(v.w) : "memory");
}
__device__ __forceinline__ void st_async128(uint32_t cluster_addr, uint4 v, uint32_t cluster_bar) {
  asm volatile("st.async.weak.shared::cluster.mbarrier::complete_tx::bytes.v4.b32 [%0], {%1,%2,%3,%4}, [%5];"
               ::"r"(cluster_addr), "r"(v.x), "r"(v.y), "r"(v.z), "r"(v.w), "r"(cluster_bar) : "memory");
}
__device__ __forceinline__ uint32_t pack2(float lo, float hi) {
  uint32_t r;
  asm("cvt.rn.bf16x2.f32 %0, %1, %2;" : "=r"(r) : "f"(hi), "f"(lo));
  return r;
}
__device__ __forceinline__ float bf_lo(uint32_t w) { return __uint_as_float(w << 16); }
__device__ __forceinline__ float bf_hi(uint32_t w) { return __uint_as_float(w & 0xffff0000u); }
__device__ __forceinline__ uint32_t set_tag(uint32_t w, uint32_t tag) { return (w & ~1u) | tag; }
__device__ __forceinline__ uint32_t movm(uint32_t a) {
  uint32_t d;
  asm("movmatrix.sync.aligned.m8n8.trans.b16 %0, %1;" : "=r"(d) : "r"(a));
  return d;
}
__device__ __forceinline__ void mma16816(float (&d)[4], const uint4& a, uint32_t b0, uint32_t b1) {
  asm("mma.sync.aligned.m16n8k16.row.col.f32.bf16.bf16.f32 {%0,%1,%2,%3}, {%4,%5,%6,%7}, {%8,%9}, {%0,%1,%2,%3};"
               : "+f"(d[0]), "+f"(d[1]), "+f"(d[2]), "+f"(d[3])
               : "r"(a.x), "r"(a.y), "r"(a.z), "r"(a.w), "r"(b0), "r"(b1));
}
__device__ __forceinline__ void mma1688(float (&d)[4], uint32_t a0, uint32_t a1, uint32_t b0) {
  asm("mma.sync.aligned.m16n8k8.row.col.f32.bf16.bf16.f32 {%0,%1,%2,%3}, {%4,%5}, {%6}, {%0,%1,%2,%3};"
      : "+f"(d[0]), "+f"(d[1]), "+f"(d[2]), "+f"(d[3])
      : "r"(a0), "r"(a1), "r"(b0));
}
__device__ __forceinline__ void mma16816_z(float (&d)[4], const uint4& a, uint32_t b0, uint32_t b1) {
  asm("mma.sync.aligned.m16n8k16.row.col.f32.bf16.bf16.f32 {%0,%1,%2,%3}, {%4,%5,%6,%7}, {%8,%9}, {%10,%10,%10,%10};"
      : "=f"(d[0]), "=f"(d[1]), "=f"(d[2]), "=f"(d[3])
      : "r"(a.x), "r"(a.y), "r"(a.z), "r"(a.w), "r"(b0), "r"(b1), "f"(0.f));
}
__device__ __forceinline__ float ex2(float x) {
  float y;
  asm("ex2.approx.ftz.f32 %0, %1;" : "=f"(y) : "f"(x));
  return y;
}
__device__ __forceinline__ float rcp(float x) {
  float y;
  asm("rcp.approx.ftz.f32 %0, %1;" : "=f"(y) : "f"(x));
  return y;
}
__device__ __forceinline__ void cp_async16(uint32_t dst, const void* src) {
  asm volatile("cp.async.cg.shared.global [%0], [%1], 16;" ::"r"(dst), "l"(src) : "memory");
}
__device__ __forceinline__ void cp_commit() { asm volatile("cp.async.commit_group;" ::: "memory"); }
template <int N> __device__ __forceinline__ void cp_wait() { asm volatile("cp.async.wait_group %0;" ::"n"(N) : "memory"); }
__device__ __forceinline__ void bar_wg(int id) { asm volatile("bar.sync %0, 128;" ::"r"(id) : "memory"); }
__device__ __forceinline__ void wg_fence() { asm volatile("wgmma.fence.sync.aligned;" ::: "memory"); }
__device__ __forceinline__ void wg_commit() { asm volatile("wgmma.commit_group.sync.aligned;" ::: "memory"); }
template <int N> __device__ __forceinline__ void wg_wait() { asm volatile("wgmma.wait_group.sync.aligned %0;" ::"n"(N) : "memory"); }
__device__ __forceinline__ void keep(const uint4& a) { asm volatile("" ::"r"(a.x), "r"(a.y), "r"(a.z), "r"(a.w) : "memory"); }
template <int T> __device__ __forceinline__ void zero_acc(float (&d)[T]) {
#pragma unroll
  for (int i = 0; i < T; i++) d[i] = 0.f;
}
template <int T> __device__ __forceinline__ void fence_acc(float (&d)[T]) {
#pragma unroll
  for (int i = 0; i < T; i++) asm volatile("" : "+f"(d[i])::"memory");
}

template <int O, int T> __device__ __forceinline__ void wgmma_rs_n64(float (&d)[T], const uint4& a, uint64_t db) {
  asm volatile("{\n.reg .pred p;\nsetp.ne.b32 p, 1, 0;\n"
    "wgmma.mma_async.sync.aligned.m64n64k16.f32.bf16.bf16 "
    "{%0, %1, %2, %3, %4, %5, %6, %7, %8, %9, %10, %11, %12, %13, %14, %15, "
    "%16, %17, %18, %19, %20, %21, %22, %23, %24, %25, %26, %27, %28, %29, %30, %31}, "
    "{%32, %33, %34, %35}, %36, p, 1, 1, 1;\n}\n"
    : "+f"(d[O + 0]), "+f"(d[O + 1]), "+f"(d[O + 2]), "+f"(d[O + 3]), "+f"(d[O + 4]), "+f"(d[O + 5]), "+f"(d[O + 6]), "+f"(d[O + 7]),
      "+f"(d[O + 8]), "+f"(d[O + 9]), "+f"(d[O + 10]), "+f"(d[O + 11]), "+f"(d[O + 12]), "+f"(d[O + 13]), "+f"(d[O + 14]), "+f"(d[O + 15]),
      "+f"(d[O + 16]), "+f"(d[O + 17]), "+f"(d[O + 18]), "+f"(d[O + 19]), "+f"(d[O + 20]), "+f"(d[O + 21]), "+f"(d[O + 22]), "+f"(d[O + 23]),
      "+f"(d[O + 24]), "+f"(d[O + 25]), "+f"(d[O + 26]), "+f"(d[O + 27]), "+f"(d[O + 28]), "+f"(d[O + 29]), "+f"(d[O + 30]), "+f"(d[O + 31])
    : "r"(a.x), "r"(a.y), "r"(a.z), "r"(a.w), "l"(db));
}
template <int O, int T> __device__ __forceinline__ void wgmma_rs_n64_init(float (&d)[T], const uint4& a, uint64_t db) {
  asm volatile("{\n.reg .pred p;\nsetp.ne.b32 p, 0, 0;\n"
    "wgmma.mma_async.sync.aligned.m64n64k16.f32.bf16.bf16 "
    "{%0, %1, %2, %3, %4, %5, %6, %7, %8, %9, %10, %11, %12, %13, %14, %15, "
    "%16, %17, %18, %19, %20, %21, %22, %23, %24, %25, %26, %27, %28, %29, %30, %31}, "
    "{%32, %33, %34, %35}, %36, p, 1, 1, 1;\n}\n"
    : "=f"(d[O + 0]), "=f"(d[O + 1]), "=f"(d[O + 2]), "=f"(d[O + 3]), "=f"(d[O + 4]), "=f"(d[O + 5]), "=f"(d[O + 6]), "=f"(d[O + 7]),
      "=f"(d[O + 8]), "=f"(d[O + 9]), "=f"(d[O + 10]), "=f"(d[O + 11]), "=f"(d[O + 12]), "=f"(d[O + 13]), "=f"(d[O + 14]), "=f"(d[O + 15]),
      "=f"(d[O + 16]), "=f"(d[O + 17]), "=f"(d[O + 18]), "=f"(d[O + 19]), "=f"(d[O + 20]), "=f"(d[O + 21]), "=f"(d[O + 22]), "=f"(d[O + 23]),
      "=f"(d[O + 24]), "=f"(d[O + 25]), "=f"(d[O + 26]), "=f"(d[O + 27]), "=f"(d[O + 28]), "=f"(d[O + 29]), "=f"(d[O + 30]), "=f"(d[O + 31])
    : "r"(a.x), "r"(a.y), "r"(a.z), "r"(a.w), "l"(db));
}
template <bool INIT, int O, int T> __device__ __forceinline__ void wgmma_n64(float (&d)[T], const uint4& a, uint64_t db) {
  if constexpr (INIT) wgmma_rs_n64_init<O>(d, a, db); else wgmma_rs_n64<O>(d, a, db);
}
template <int O, int T> __device__ __forceinline__ void wgmma_rs_n128(float (&d)[T], const uint4& a, uint64_t db) {
  asm volatile("{\n.reg .pred p;\nsetp.ne.b32 p, 1, 0;\n"
    "wgmma.mma_async.sync.aligned.m64n128k16.f32.bf16.bf16 "
    "{%0, %1, %2, %3, %4, %5, %6, %7, %8, %9, %10, %11, %12, %13, %14, %15, "
    "%16, %17, %18, %19, %20, %21, %22, %23, %24, %25, %26, %27, %28, %29, %30, %31, "
    "%32, %33, %34, %35, %36, %37, %38, %39, %40, %41, %42, %43, %44, %45, %46, %47, "
    "%48, %49, %50, %51, %52, %53, %54, %55, %56, %57, %58, %59, %60, %61, %62, %63}, "
    "{%64, %65, %66, %67}, %68, p, 1, 1, 1;\n}\n"
    : "+f"(d[O + 0]), "+f"(d[O + 1]), "+f"(d[O + 2]), "+f"(d[O + 3]), "+f"(d[O + 4]), "+f"(d[O + 5]), "+f"(d[O + 6]), "+f"(d[O + 7]),
      "+f"(d[O + 8]), "+f"(d[O + 9]), "+f"(d[O + 10]), "+f"(d[O + 11]), "+f"(d[O + 12]), "+f"(d[O + 13]), "+f"(d[O + 14]), "+f"(d[O + 15]),
      "+f"(d[O + 16]), "+f"(d[O + 17]), "+f"(d[O + 18]), "+f"(d[O + 19]), "+f"(d[O + 20]), "+f"(d[O + 21]), "+f"(d[O + 22]), "+f"(d[O + 23]),
      "+f"(d[O + 24]), "+f"(d[O + 25]), "+f"(d[O + 26]), "+f"(d[O + 27]), "+f"(d[O + 28]), "+f"(d[O + 29]), "+f"(d[O + 30]), "+f"(d[O + 31]),
      "+f"(d[O + 32]), "+f"(d[O + 33]), "+f"(d[O + 34]), "+f"(d[O + 35]), "+f"(d[O + 36]), "+f"(d[O + 37]), "+f"(d[O + 38]), "+f"(d[O + 39]),
      "+f"(d[O + 40]), "+f"(d[O + 41]), "+f"(d[O + 42]), "+f"(d[O + 43]), "+f"(d[O + 44]), "+f"(d[O + 45]), "+f"(d[O + 46]), "+f"(d[O + 47]),
      "+f"(d[O + 48]), "+f"(d[O + 49]), "+f"(d[O + 50]), "+f"(d[O + 51]), "+f"(d[O + 52]), "+f"(d[O + 53]), "+f"(d[O + 54]), "+f"(d[O + 55]),
      "+f"(d[O + 56]), "+f"(d[O + 57]), "+f"(d[O + 58]), "+f"(d[O + 59]), "+f"(d[O + 60]), "+f"(d[O + 61]), "+f"(d[O + 62]), "+f"(d[O + 63])
    : "r"(a.x), "r"(a.y), "r"(a.z), "r"(a.w), "l"(db));
}
template <int O, int T> __device__ __forceinline__ void wgmma_rs_n128_init(float (&d)[T], const uint4& a, uint64_t db) {
  asm volatile("{\n.reg .pred p;\nsetp.ne.b32 p, 0, 0;\n"
    "wgmma.mma_async.sync.aligned.m64n128k16.f32.bf16.bf16 "
    "{%0, %1, %2, %3, %4, %5, %6, %7, %8, %9, %10, %11, %12, %13, %14, %15, "
    "%16, %17, %18, %19, %20, %21, %22, %23, %24, %25, %26, %27, %28, %29, %30, %31, "
    "%32, %33, %34, %35, %36, %37, %38, %39, %40, %41, %42, %43, %44, %45, %46, %47, "
    "%48, %49, %50, %51, %52, %53, %54, %55, %56, %57, %58, %59, %60, %61, %62, %63}, "
    "{%64, %65, %66, %67}, %68, p, 1, 1, 1;\n}\n"
    : "=f"(d[O + 0]), "=f"(d[O + 1]), "=f"(d[O + 2]), "=f"(d[O + 3]), "=f"(d[O + 4]), "=f"(d[O + 5]), "=f"(d[O + 6]), "=f"(d[O + 7]),
      "=f"(d[O + 8]), "=f"(d[O + 9]), "=f"(d[O + 10]), "=f"(d[O + 11]), "=f"(d[O + 12]), "=f"(d[O + 13]), "=f"(d[O + 14]), "=f"(d[O + 15]),
      "=f"(d[O + 16]), "=f"(d[O + 17]), "=f"(d[O + 18]), "=f"(d[O + 19]), "=f"(d[O + 20]), "=f"(d[O + 21]), "=f"(d[O + 22]), "=f"(d[O + 23]),
      "=f"(d[O + 24]), "=f"(d[O + 25]), "=f"(d[O + 26]), "=f"(d[O + 27]), "=f"(d[O + 28]), "=f"(d[O + 29]), "=f"(d[O + 30]), "=f"(d[O + 31]),
      "=f"(d[O + 32]), "=f"(d[O + 33]), "=f"(d[O + 34]), "=f"(d[O + 35]), "=f"(d[O + 36]), "=f"(d[O + 37]), "=f"(d[O + 38]), "=f"(d[O + 39]),
      "=f"(d[O + 40]), "=f"(d[O + 41]), "=f"(d[O + 42]), "=f"(d[O + 43]), "=f"(d[O + 44]), "=f"(d[O + 45]), "=f"(d[O + 46]), "=f"(d[O + 47]),
      "=f"(d[O + 48]), "=f"(d[O + 49]), "=f"(d[O + 50]), "=f"(d[O + 51]), "=f"(d[O + 52]), "=f"(d[O + 53]), "=f"(d[O + 54]), "=f"(d[O + 55]),
      "=f"(d[O + 56]), "=f"(d[O + 57]), "=f"(d[O + 58]), "=f"(d[O + 59]), "=f"(d[O + 60]), "=f"(d[O + 61]), "=f"(d[O + 62]), "=f"(d[O + 63])
    : "r"(a.x), "r"(a.y), "r"(a.z), "r"(a.w), "l"(db));
}
template <bool INIT, int O, int T> __device__ __forceinline__ void wgmma_n128(float (&d)[T], const uint4& a, uint64_t db) {
  if constexpr (INIT) wgmma_rs_n128_init<O>(d, a, db); else wgmma_rs_n128<O>(d, a, db);
}
template <int O, int T> __device__ __forceinline__ void wgmma_rs_n192(float (&d)[T], const uint4& a, uint64_t db) {
  asm volatile("{\n.reg .pred p;\nsetp.ne.b32 p, 1, 0;\n"
    "wgmma.mma_async.sync.aligned.m64n192k16.f32.bf16.bf16 "
    "{%0, %1, %2, %3, %4, %5, %6, %7, %8, %9, %10, %11, %12, %13, %14, %15, "
    "%16, %17, %18, %19, %20, %21, %22, %23, %24, %25, %26, %27, %28, %29, %30, %31, "
    "%32, %33, %34, %35, %36, %37, %38, %39, %40, %41, %42, %43, %44, %45, %46, %47, "
    "%48, %49, %50, %51, %52, %53, %54, %55, %56, %57, %58, %59, %60, %61, %62, %63, "
    "%64, %65, %66, %67, %68, %69, %70, %71, %72, %73, %74, %75, %76, %77, %78, %79, "
    "%80, %81, %82, %83, %84, %85, %86, %87, %88, %89, %90, %91, %92, %93, %94, %95}, "
    "{%96, %97, %98, %99}, %100, p, 1, 1, 1;\n}\n"
    : "+f"(d[O + 0]), "+f"(d[O + 1]), "+f"(d[O + 2]), "+f"(d[O + 3]), "+f"(d[O + 4]), "+f"(d[O + 5]), "+f"(d[O + 6]), "+f"(d[O + 7]),
      "+f"(d[O + 8]), "+f"(d[O + 9]), "+f"(d[O + 10]), "+f"(d[O + 11]), "+f"(d[O + 12]), "+f"(d[O + 13]), "+f"(d[O + 14]), "+f"(d[O + 15]),
      "+f"(d[O + 16]), "+f"(d[O + 17]), "+f"(d[O + 18]), "+f"(d[O + 19]), "+f"(d[O + 20]), "+f"(d[O + 21]), "+f"(d[O + 22]), "+f"(d[O + 23]),
      "+f"(d[O + 24]), "+f"(d[O + 25]), "+f"(d[O + 26]), "+f"(d[O + 27]), "+f"(d[O + 28]), "+f"(d[O + 29]), "+f"(d[O + 30]), "+f"(d[O + 31]),
      "+f"(d[O + 32]), "+f"(d[O + 33]), "+f"(d[O + 34]), "+f"(d[O + 35]), "+f"(d[O + 36]), "+f"(d[O + 37]), "+f"(d[O + 38]), "+f"(d[O + 39]),
      "+f"(d[O + 40]), "+f"(d[O + 41]), "+f"(d[O + 42]), "+f"(d[O + 43]), "+f"(d[O + 44]), "+f"(d[O + 45]), "+f"(d[O + 46]), "+f"(d[O + 47]),
      "+f"(d[O + 48]), "+f"(d[O + 49]), "+f"(d[O + 50]), "+f"(d[O + 51]), "+f"(d[O + 52]), "+f"(d[O + 53]), "+f"(d[O + 54]), "+f"(d[O + 55]),
      "+f"(d[O + 56]), "+f"(d[O + 57]), "+f"(d[O + 58]), "+f"(d[O + 59]), "+f"(d[O + 60]), "+f"(d[O + 61]), "+f"(d[O + 62]), "+f"(d[O + 63]),
      "+f"(d[O + 64]), "+f"(d[O + 65]), "+f"(d[O + 66]), "+f"(d[O + 67]), "+f"(d[O + 68]), "+f"(d[O + 69]), "+f"(d[O + 70]), "+f"(d[O + 71]),
      "+f"(d[O + 72]), "+f"(d[O + 73]), "+f"(d[O + 74]), "+f"(d[O + 75]), "+f"(d[O + 76]), "+f"(d[O + 77]), "+f"(d[O + 78]), "+f"(d[O + 79]),
      "+f"(d[O + 80]), "+f"(d[O + 81]), "+f"(d[O + 82]), "+f"(d[O + 83]), "+f"(d[O + 84]), "+f"(d[O + 85]), "+f"(d[O + 86]), "+f"(d[O + 87]),
      "+f"(d[O + 88]), "+f"(d[O + 89]), "+f"(d[O + 90]), "+f"(d[O + 91]), "+f"(d[O + 92]), "+f"(d[O + 93]), "+f"(d[O + 94]), "+f"(d[O + 95])
    : "r"(a.x), "r"(a.y), "r"(a.z), "r"(a.w), "l"(db));
}
template <int O, int T> __device__ __forceinline__ void wgmma_rs_n192_init(float (&d)[T], const uint4& a, uint64_t db) {
  asm volatile("{\n.reg .pred p;\nsetp.ne.b32 p, 0, 0;\n"
    "wgmma.mma_async.sync.aligned.m64n192k16.f32.bf16.bf16 "
    "{%0, %1, %2, %3, %4, %5, %6, %7, %8, %9, %10, %11, %12, %13, %14, %15, "
    "%16, %17, %18, %19, %20, %21, %22, %23, %24, %25, %26, %27, %28, %29, %30, %31, "
    "%32, %33, %34, %35, %36, %37, %38, %39, %40, %41, %42, %43, %44, %45, %46, %47, "
    "%48, %49, %50, %51, %52, %53, %54, %55, %56, %57, %58, %59, %60, %61, %62, %63, "
    "%64, %65, %66, %67, %68, %69, %70, %71, %72, %73, %74, %75, %76, %77, %78, %79, "
    "%80, %81, %82, %83, %84, %85, %86, %87, %88, %89, %90, %91, %92, %93, %94, %95}, "
    "{%96, %97, %98, %99}, %100, p, 1, 1, 1;\n}\n"
    : "=f"(d[O + 0]), "=f"(d[O + 1]), "=f"(d[O + 2]), "=f"(d[O + 3]), "=f"(d[O + 4]), "=f"(d[O + 5]), "=f"(d[O + 6]), "=f"(d[O + 7]),
      "=f"(d[O + 8]), "=f"(d[O + 9]), "=f"(d[O + 10]), "=f"(d[O + 11]), "=f"(d[O + 12]), "=f"(d[O + 13]), "=f"(d[O + 14]), "=f"(d[O + 15]),
      "=f"(d[O + 16]), "=f"(d[O + 17]), "=f"(d[O + 18]), "=f"(d[O + 19]), "=f"(d[O + 20]), "=f"(d[O + 21]), "=f"(d[O + 22]), "=f"(d[O + 23]),
      "=f"(d[O + 24]), "=f"(d[O + 25]), "=f"(d[O + 26]), "=f"(d[O + 27]), "=f"(d[O + 28]), "=f"(d[O + 29]), "=f"(d[O + 30]), "=f"(d[O + 31]),
      "=f"(d[O + 32]), "=f"(d[O + 33]), "=f"(d[O + 34]), "=f"(d[O + 35]), "=f"(d[O + 36]), "=f"(d[O + 37]), "=f"(d[O + 38]), "=f"(d[O + 39]),
      "=f"(d[O + 40]), "=f"(d[O + 41]), "=f"(d[O + 42]), "=f"(d[O + 43]), "=f"(d[O + 44]), "=f"(d[O + 45]), "=f"(d[O + 46]), "=f"(d[O + 47]),
      "=f"(d[O + 48]), "=f"(d[O + 49]), "=f"(d[O + 50]), "=f"(d[O + 51]), "=f"(d[O + 52]), "=f"(d[O + 53]), "=f"(d[O + 54]), "=f"(d[O + 55]),
      "=f"(d[O + 56]), "=f"(d[O + 57]), "=f"(d[O + 58]), "=f"(d[O + 59]), "=f"(d[O + 60]), "=f"(d[O + 61]), "=f"(d[O + 62]), "=f"(d[O + 63]),
      "=f"(d[O + 64]), "=f"(d[O + 65]), "=f"(d[O + 66]), "=f"(d[O + 67]), "=f"(d[O + 68]), "=f"(d[O + 69]), "=f"(d[O + 70]), "=f"(d[O + 71]),
      "=f"(d[O + 72]), "=f"(d[O + 73]), "=f"(d[O + 74]), "=f"(d[O + 75]), "=f"(d[O + 76]), "=f"(d[O + 77]), "=f"(d[O + 78]), "=f"(d[O + 79]),
      "=f"(d[O + 80]), "=f"(d[O + 81]), "=f"(d[O + 82]), "=f"(d[O + 83]), "=f"(d[O + 84]), "=f"(d[O + 85]), "=f"(d[O + 86]), "=f"(d[O + 87]),
      "=f"(d[O + 88]), "=f"(d[O + 89]), "=f"(d[O + 90]), "=f"(d[O + 91]), "=f"(d[O + 92]), "=f"(d[O + 93]), "=f"(d[O + 94]), "=f"(d[O + 95])
    : "r"(a.x), "r"(a.y), "r"(a.z), "r"(a.w), "l"(db));
}
template <bool INIT, int O, int T> __device__ __forceinline__ void wgmma_n192(float (&d)[T], const uint4& a, uint64_t db) {
  if constexpr (INIT) wgmma_rs_n192_init<O>(d, a, db); else wgmma_rs_n192<O>(d, a, db);
}
template <int O, int T> __device__ __forceinline__ void wgmma_rs_n256(float (&d)[T], const uint4& a, uint64_t db) {
  asm volatile("{\n.reg .pred p;\nsetp.ne.b32 p, 1, 0;\n"
    "wgmma.mma_async.sync.aligned.m64n256k16.f32.bf16.bf16 "
    "{%0, %1, %2, %3, %4, %5, %6, %7, %8, %9, %10, %11, %12, %13, %14, %15, "
    "%16, %17, %18, %19, %20, %21, %22, %23, %24, %25, %26, %27, %28, %29, %30, %31, "
    "%32, %33, %34, %35, %36, %37, %38, %39, %40, %41, %42, %43, %44, %45, %46, %47, "
    "%48, %49, %50, %51, %52, %53, %54, %55, %56, %57, %58, %59, %60, %61, %62, %63, "
    "%64, %65, %66, %67, %68, %69, %70, %71, %72, %73, %74, %75, %76, %77, %78, %79, "
    "%80, %81, %82, %83, %84, %85, %86, %87, %88, %89, %90, %91, %92, %93, %94, %95, "
    "%96, %97, %98, %99, %100, %101, %102, %103, %104, %105, %106, %107, %108, %109, %110, %111, "
    "%112, %113, %114, %115, %116, %117, %118, %119, %120, %121, %122, %123, %124, %125, %126, %127}, "
    "{%128, %129, %130, %131}, %132, p, 1, 1, 1;\n}\n"
    : "+f"(d[O + 0]), "+f"(d[O + 1]), "+f"(d[O + 2]), "+f"(d[O + 3]), "+f"(d[O + 4]), "+f"(d[O + 5]), "+f"(d[O + 6]), "+f"(d[O + 7]),
      "+f"(d[O + 8]), "+f"(d[O + 9]), "+f"(d[O + 10]), "+f"(d[O + 11]), "+f"(d[O + 12]), "+f"(d[O + 13]), "+f"(d[O + 14]), "+f"(d[O + 15]),
      "+f"(d[O + 16]), "+f"(d[O + 17]), "+f"(d[O + 18]), "+f"(d[O + 19]), "+f"(d[O + 20]), "+f"(d[O + 21]), "+f"(d[O + 22]), "+f"(d[O + 23]),
      "+f"(d[O + 24]), "+f"(d[O + 25]), "+f"(d[O + 26]), "+f"(d[O + 27]), "+f"(d[O + 28]), "+f"(d[O + 29]), "+f"(d[O + 30]), "+f"(d[O + 31]),
      "+f"(d[O + 32]), "+f"(d[O + 33]), "+f"(d[O + 34]), "+f"(d[O + 35]), "+f"(d[O + 36]), "+f"(d[O + 37]), "+f"(d[O + 38]), "+f"(d[O + 39]),
      "+f"(d[O + 40]), "+f"(d[O + 41]), "+f"(d[O + 42]), "+f"(d[O + 43]), "+f"(d[O + 44]), "+f"(d[O + 45]), "+f"(d[O + 46]), "+f"(d[O + 47]),
      "+f"(d[O + 48]), "+f"(d[O + 49]), "+f"(d[O + 50]), "+f"(d[O + 51]), "+f"(d[O + 52]), "+f"(d[O + 53]), "+f"(d[O + 54]), "+f"(d[O + 55]),
      "+f"(d[O + 56]), "+f"(d[O + 57]), "+f"(d[O + 58]), "+f"(d[O + 59]), "+f"(d[O + 60]), "+f"(d[O + 61]), "+f"(d[O + 62]), "+f"(d[O + 63]),
      "+f"(d[O + 64]), "+f"(d[O + 65]), "+f"(d[O + 66]), "+f"(d[O + 67]), "+f"(d[O + 68]), "+f"(d[O + 69]), "+f"(d[O + 70]), "+f"(d[O + 71]),
      "+f"(d[O + 72]), "+f"(d[O + 73]), "+f"(d[O + 74]), "+f"(d[O + 75]), "+f"(d[O + 76]), "+f"(d[O + 77]), "+f"(d[O + 78]), "+f"(d[O + 79]),
      "+f"(d[O + 80]), "+f"(d[O + 81]), "+f"(d[O + 82]), "+f"(d[O + 83]), "+f"(d[O + 84]), "+f"(d[O + 85]), "+f"(d[O + 86]), "+f"(d[O + 87]),
      "+f"(d[O + 88]), "+f"(d[O + 89]), "+f"(d[O + 90]), "+f"(d[O + 91]), "+f"(d[O + 92]), "+f"(d[O + 93]), "+f"(d[O + 94]), "+f"(d[O + 95]),
      "+f"(d[O + 96]), "+f"(d[O + 97]), "+f"(d[O + 98]), "+f"(d[O + 99]), "+f"(d[O + 100]), "+f"(d[O + 101]), "+f"(d[O + 102]), "+f"(d[O + 103]),
      "+f"(d[O + 104]), "+f"(d[O + 105]), "+f"(d[O + 106]), "+f"(d[O + 107]), "+f"(d[O + 108]), "+f"(d[O + 109]), "+f"(d[O + 110]), "+f"(d[O + 111]),
      "+f"(d[O + 112]), "+f"(d[O + 113]), "+f"(d[O + 114]), "+f"(d[O + 115]), "+f"(d[O + 116]), "+f"(d[O + 117]), "+f"(d[O + 118]), "+f"(d[O + 119]),
      "+f"(d[O + 120]), "+f"(d[O + 121]), "+f"(d[O + 122]), "+f"(d[O + 123]), "+f"(d[O + 124]), "+f"(d[O + 125]), "+f"(d[O + 126]), "+f"(d[O + 127])
    : "r"(a.x), "r"(a.y), "r"(a.z), "r"(a.w), "l"(db));
}
template <int O, int T> __device__ __forceinline__ void wgmma_rs_n256_init(float (&d)[T], const uint4& a, uint64_t db) {
  asm volatile("{\n.reg .pred p;\nsetp.ne.b32 p, 0, 0;\n"
    "wgmma.mma_async.sync.aligned.m64n256k16.f32.bf16.bf16 "
    "{%0, %1, %2, %3, %4, %5, %6, %7, %8, %9, %10, %11, %12, %13, %14, %15, "
    "%16, %17, %18, %19, %20, %21, %22, %23, %24, %25, %26, %27, %28, %29, %30, %31, "
    "%32, %33, %34, %35, %36, %37, %38, %39, %40, %41, %42, %43, %44, %45, %46, %47, "
    "%48, %49, %50, %51, %52, %53, %54, %55, %56, %57, %58, %59, %60, %61, %62, %63, "
    "%64, %65, %66, %67, %68, %69, %70, %71, %72, %73, %74, %75, %76, %77, %78, %79, "
    "%80, %81, %82, %83, %84, %85, %86, %87, %88, %89, %90, %91, %92, %93, %94, %95, "
    "%96, %97, %98, %99, %100, %101, %102, %103, %104, %105, %106, %107, %108, %109, %110, %111, "
    "%112, %113, %114, %115, %116, %117, %118, %119, %120, %121, %122, %123, %124, %125, %126, %127}, "
    "{%128, %129, %130, %131}, %132, p, 1, 1, 1;\n}\n"
    : "=f"(d[O + 0]), "=f"(d[O + 1]), "=f"(d[O + 2]), "=f"(d[O + 3]), "=f"(d[O + 4]), "=f"(d[O + 5]), "=f"(d[O + 6]), "=f"(d[O + 7]),
      "=f"(d[O + 8]), "=f"(d[O + 9]), "=f"(d[O + 10]), "=f"(d[O + 11]), "=f"(d[O + 12]), "=f"(d[O + 13]), "=f"(d[O + 14]), "=f"(d[O + 15]),
      "=f"(d[O + 16]), "=f"(d[O + 17]), "=f"(d[O + 18]), "=f"(d[O + 19]), "=f"(d[O + 20]), "=f"(d[O + 21]), "=f"(d[O + 22]), "=f"(d[O + 23]),
      "=f"(d[O + 24]), "=f"(d[O + 25]), "=f"(d[O + 26]), "=f"(d[O + 27]), "=f"(d[O + 28]), "=f"(d[O + 29]), "=f"(d[O + 30]), "=f"(d[O + 31]),
      "=f"(d[O + 32]), "=f"(d[O + 33]), "=f"(d[O + 34]), "=f"(d[O + 35]), "=f"(d[O + 36]), "=f"(d[O + 37]), "=f"(d[O + 38]), "=f"(d[O + 39]),
      "=f"(d[O + 40]), "=f"(d[O + 41]), "=f"(d[O + 42]), "=f"(d[O + 43]), "=f"(d[O + 44]), "=f"(d[O + 45]), "=f"(d[O + 46]), "=f"(d[O + 47]),
      "=f"(d[O + 48]), "=f"(d[O + 49]), "=f"(d[O + 50]), "=f"(d[O + 51]), "=f"(d[O + 52]), "=f"(d[O + 53]), "=f"(d[O + 54]), "=f"(d[O + 55]),
      "=f"(d[O + 56]), "=f"(d[O + 57]), "=f"(d[O + 58]), "=f"(d[O + 59]), "=f"(d[O + 60]), "=f"(d[O + 61]), "=f"(d[O + 62]), "=f"(d[O + 63]),
      "=f"(d[O + 64]), "=f"(d[O + 65]), "=f"(d[O + 66]), "=f"(d[O + 67]), "=f"(d[O + 68]), "=f"(d[O + 69]), "=f"(d[O + 70]), "=f"(d[O + 71]),
      "=f"(d[O + 72]), "=f"(d[O + 73]), "=f"(d[O + 74]), "=f"(d[O + 75]), "=f"(d[O + 76]), "=f"(d[O + 77]), "=f"(d[O + 78]), "=f"(d[O + 79]),
      "=f"(d[O + 80]), "=f"(d[O + 81]), "=f"(d[O + 82]), "=f"(d[O + 83]), "=f"(d[O + 84]), "=f"(d[O + 85]), "=f"(d[O + 86]), "=f"(d[O + 87]),
      "=f"(d[O + 88]), "=f"(d[O + 89]), "=f"(d[O + 90]), "=f"(d[O + 91]), "=f"(d[O + 92]), "=f"(d[O + 93]), "=f"(d[O + 94]), "=f"(d[O + 95]),
      "=f"(d[O + 96]), "=f"(d[O + 97]), "=f"(d[O + 98]), "=f"(d[O + 99]), "=f"(d[O + 100]), "=f"(d[O + 101]), "=f"(d[O + 102]), "=f"(d[O + 103]),
      "=f"(d[O + 104]), "=f"(d[O + 105]), "=f"(d[O + 106]), "=f"(d[O + 107]), "=f"(d[O + 108]), "=f"(d[O + 109]), "=f"(d[O + 110]), "=f"(d[O + 111]),
      "=f"(d[O + 112]), "=f"(d[O + 113]), "=f"(d[O + 114]), "=f"(d[O + 115]), "=f"(d[O + 116]), "=f"(d[O + 117]), "=f"(d[O + 118]), "=f"(d[O + 119]),
      "=f"(d[O + 120]), "=f"(d[O + 121]), "=f"(d[O + 122]), "=f"(d[O + 123]), "=f"(d[O + 124]), "=f"(d[O + 125]), "=f"(d[O + 126]), "=f"(d[O + 127])
    : "r"(a.x), "r"(a.y), "r"(a.z), "r"(a.w), "l"(db));
}
template <bool INIT, int O, int T> __device__ __forceinline__ void wgmma_n256(float (&d)[T], const uint4& a, uint64_t db) {
  if constexpr (INIT) wgmma_rs_n256_init<O>(d, a, db); else wgmma_rs_n256<O>(d, a, db);
}

template <int N> __device__ __forceinline__ void load_pk(uint4* a, const uint4* p) {
#pragma unroll
  for (int i = 0; i < N; i++) a[i] = ld_ll(p + i * 32);
}
__device__ __forceinline__ uint32_t xor_or(uint32_t a, uint32_t b, uint32_t t) {
  uint32_t r;
  asm("lop3.b32 %0, %1, %2, %3, 0x7E;" : "=r"(r) : "r"(a), "r"(b), "r"(t));
  return r;
}
template <int N> __device__ __forceinline__ bool ok_pk(const uint4* a, uint32_t tag) {
  static_assert(N % 2 == 0, "");
  uint32_t x = xor_or(a[0].x, a[1].x, tag);
#pragma unroll
  for (int i = 2; i < N; i += 2) x |= xor_or(a[i].x, a[i + 1].x, tag);
  return __all_sync(0xffffffffu, (x & 1u) == 0u);
}
template <int N> __device__ __forceinline__ void ensure_pk(uint4* a, const uint4* p, uint32_t tag) {
  if (ok_pk<N>(a, tag)) return;
  uint32_t n = 0;
  do { load_pk<N>(a, p); } while (!ok_pk<N>(a, tag) && ++n < SPIN_LIMIT);
}

constexpr int NSTAGE = 44;
constexpr int ST_WO = 8, ST_G1 = 12, ST_G2 = 20, ST_DN = 28;
__host__ __device__ constexpr int st_len(int s) { return s < ST_WO ? 3 : s < ST_G1 ? 2 : s < ST_G2 ? 4 : s < ST_DN ? 3 : 2; }
__host__ __device__ constexpr int st_g0(int s) {
  int pos = 0, g0 = 0;
  for (int i = 0; i <= s; i++) {
    if (pos + st_len(i) > NGRAN) pos = 0;
    g0 = pos;
    pos += st_len(i);
  }
  return g0;
}
__host__ __device__ constexpr int cnt_first(int g, int s) {
  int n = 0;
  for (int i = 0; i < s; i++) n += (st_g0(i) == g);
  return n;
}
__host__ __device__ constexpr int cnt_cover(int g, int s) {
  int n = 0;
  for (int i = 0; i < s; i++) n += (g >= st_g0(i) && g < st_g0(i) + st_len(i));
  return n;
}
__host__ __device__ constexpr uint32_t flip_mask(int s0, int s1) {
  uint32_t m = 0;
  for (int i = s0; i < s1; i++) m ^= ((1u << st_len(i)) - 1u) << st_g0(i);
  return m;
}
__host__ __device__ constexpr int dn_q(int i) { return i < 3 ? 0 : i < 6 ? 1 : i == 6 ? 0 : i == 7 ? 1 : i < 12 ? 2 : 3; }
__host__ __device__ constexpr int dn_par(int i) { return i < 8 ? (i == 2 || i == 4 || i >= 6) : (i & 1); }
__host__ __device__ constexpr int dn_kh(int i) { return i < 8 ? (i == 1 || i >= 5) : ((i & 3) >= 2); }
template <int I> struct IC { static constexpr int value = I; };
template <int B, int E, typename F> __device__ __forceinline__ void static_for(F&& f) {
  if constexpr (B < E) { f(IC<B>{}); static_for<B + 1, E>(f); }
}
template <int S> __device__ __forceinline__ void cons_acquire(uint32_t sbase, uint32_t L) {
  constexpr int g0 = st_g0(S);
  constexpr uint32_t p0 = cnt_first(g0, S) & 1, odd = cnt_first(g0, NSTAGE) & 1;
  mbar_wait(sbase + SM_MISC + BAR_FULL + 8 * g0, p0 ^ (L & odd));
}
template <int S> __device__ __forceinline__ void cons_release(uint32_t sbase, int lane) {
  if (lane < st_len(S)) mbar_arrive(sbase + SM_MISC + BAR_EMPTY + 8 * st_g0(S) + 8 * lane);
}
__device__ __forceinline__ bool elect_one() {
  uint32_t p;
  asm volatile("{\n.reg .pred P;\nelect.sync _|P, 0xffffffff;\nselp.u32 %0, 1, 0, P;\n}" : "=r"(p));
  return p != 0;
}
struct ProdRing { uint32_t pos, par; };
template <int N> __device__ __forceinline__ uint32_t prod_acquire(uint32_t sbase, ProdRing& r) {
  if (r.pos + N > NGRAN) r.pos = 0;
  const uint32_t g0 = r.pos;
#pragma unroll
  for (uint32_t i = 0; i < N; i++) mbar_wait(sbase + SM_MISC + BAR_EMPTY + 8 * (g0 + i), ((r.par >> (g0 + i)) & 1u) ^ 1u);
  r.par ^= ((1u << N) - 1u) << g0;
  r.pos = g0 + N;
  return g0;
}
template <int S> __device__ __forceinline__ void prod_acquire_static(uint32_t sbase, uint32_t L) {
  constexpr int g0 = st_g0(S);
  static_for<0, st_len(S)>([&](auto I) {
    constexpr int g = g0 + I.value;
    constexpr uint32_t p0 = cnt_cover(g, S) & 1, odd = cnt_cover(g, NSTAGE) & 1;
    mbar_wait(sbase + SM_MISC + BAR_EMPTY + 8 * g, p0 ^ (L & odd) ^ 1u);
  });
}
template <int S, int KSTEP_BYTES, int LBO, int SBO, int SWZ> __device__ __forceinline__ constexpr uint64_t st_desc(int k) {
  return (uint64_t)((SMEM_ORIGIN + st_g0(S) * GRAN + k * KSTEP_BYTES) >> 4) | ((uint64_t)(LBO >> 4) << 16) |
         ((uint64_t)(SBO >> 4) << 32) | ((uint64_t)SWZ << 62);
}

__device__ __forceinline__ void combine_stats(const uint4& p0, const uint4& p1, float& mean_lo, float& rstd_lo, float& mean_hi, float& rstd_hi) {
  float m0 = __uint_as_float(p0.x), q0 = __uint_as_float(p0.y), m0h = __uint_as_float(p0.z), q0h = __uint_as_float(p0.w);
  float m1 = __uint_as_float(p1.x), q1 = __uint_as_float(p1.y), m1h = __uint_as_float(p1.z), q1h = __uint_as_float(p1.w);
  float s = m0 + m1, sh = m0h + m1h;
  s += __shfl_xor_sync(0xffffffffu, s, 1); sh += __shfl_xor_sync(0xffffffffu, sh, 1);
  s += __shfl_xor_sync(0xffffffffu, s, 2); sh += __shfl_xor_sync(0xffffffffu, sh, 2);
  mean_lo = s * 0.125f; mean_hi = sh * 0.125f;
  float d0 = m0 - mean_lo, d1 = m1 - mean_lo, d0h = m0h - mean_hi, d1h = m1h - mean_hi;
  float t = q0 + q1 + 64.f * (d0 * d0 + d1 * d1), th = q0h + q1h + 64.f * (d0h * d0h + d1h * d1h);
  t += __shfl_xor_sync(0xffffffffu, t, 1); th += __shfl_xor_sync(0xffffffffu, th, 1);
  t += __shfl_xor_sync(0xffffffffu, t, 2); th += __shfl_xor_sync(0xffffffffu, th, 2);
  rstd_lo = rsqrtf(t * (1.f / 512.f) + 1e-5f);
  rstd_hi = rsqrtf(th * (1.f / 512.f) + 1e-5f);
}
__device__ __forceinline__ uint4 local_stats(const float (&v)[32]) {
  float s = 0.f, sh = 0.f;
#pragma unroll
  for (int i = 0; i < 4; i++) {
    s += (v[8 * i + 0] + v[8 * i + 1]) + (v[8 * i + 4] + v[8 * i + 5]);
    sh += (v[8 * i + 2] + v[8 * i + 3]) + (v[8 * i + 6] + v[8 * i + 7]);
  }
  s += __shfl_xor_sync(0xffffffffu, s, 1); sh += __shfl_xor_sync(0xffffffffu, sh, 1);
  s += __shfl_xor_sync(0xffffffffu, s, 2); sh += __shfl_xor_sync(0xffffffffu, sh, 2);
  float m = s * (1.f / 64.f), mh = sh * (1.f / 64.f);
  float q = 0.f, qh = 0.f;
#pragma unroll
  for (int i = 0; i < 4; i++) {
    float a = v[8 * i + 0] - m, b = v[8 * i + 1] - m, c = v[8 * i + 4] - m, d = v[8 * i + 5] - m;
    q += (a * a + b * b) + (c * c + d * d);
    float e = v[8 * i + 2] - mh, f = v[8 * i + 3] - mh, g = v[8 * i + 6] - mh, h = v[8 * i + 7] - mh;
    qh += (e * e + f * f) + (g * g + h * h);
  }
  q += __shfl_xor_sync(0xffffffffu, q, 1); qh += __shfl_xor_sync(0xffffffffu, qh, 1);
  q += __shfl_xor_sync(0xffffffffu, q, 2); qh += __shfl_xor_sync(0xffffffffu, qh, 2);
  return make_uint4(__float_as_uint(m), __float_as_uint(q), __float_as_uint(mh), __float_as_uint(qh));
}

__device__ __forceinline__ int slab_row0(int c, int g, int w) { return 1024 * g + 64 * c + 32 * (w >> 1) + (w & 1); }

__device__ __forceinline__ void owner_ln_publish(uint32_t sbase, const float (&v)[32], uint32_t tphase, uint32_t tag_xn) {
  PHASE_VARS;
  const uint32_t bars = sbase + SM_MISC;
  const int oslab = 4 * g + ca;
  const int step0 = 16 * cbit + 4 * w;
  TS(40 + 4 * tphase);
  uint4 st = local_stats(v);
  const uint32_t tb = bars + BAR_TSTAT + 8 * g;
  const uint32_t slot = sbase + SM_TSTAT + g * 1024 + (4 * cbit + w) * 128 + qr * 16;
  if (t128 == 0) mbar_expect_tx(tb, 1024);
  if (qc == 0) {
    st_async128(mapa(slot, 0), st, mapa(tb, 0));
    st_async128(mapa(slot, 1), st, mapa(tb, 1));
  }
  uint4* xn = g_xn + ((c * 8 + oslab) * 32 + step0) * 32 + lane;
  uint4* xr = g_xraw + ((c * 8 + oslab) * 32 + step0) * 32 + lane;
  TS(41 + 4 * tphase);
  mbar_wait(tb, tphase);
  TS(42 + 4 * tphase);
  const uint32_t rd = sbase + SM_TSTAT + g * 1024 + qc * 256 + qr * 16;
  uint4 p0 = lds128(rd), p1 = lds128(rd + 128);
  float ml, rl, mh, rh;
  combine_stats(p0, p1, ml, rl, mh, rh);
  const float bl = -ml * rl, bh = -mh * rh;
#pragma unroll
  for (int i = 0; i < 4; i++) {
    uint4 o;
    o.x = set_tag(pack2(fmaf(v[8 * i + 0], rl, bl), fmaf(v[8 * i + 1], rl, bl)), tag_xn);
    o.y = pack2(fmaf(v[8 * i + 2], rh, bh), fmaf(v[8 * i + 3], rh, bh));
    o.z = pack2(fmaf(v[8 * i + 4], rl, bl), fmaf(v[8 * i + 5], rl, bl));
    o.w = pack2(fmaf(v[8 * i + 6], rh, bh), fmaf(v[8 * i + 7], rh, bh));
    st_ll(xn + i * 32, o);
  }
#pragma unroll
  for (int i = 0; i < 4; i++) {
    uint4 o;
    o.x = set_tag(pack2(v[8 * i + 0], v[8 * i + 1]), 1u);
    o.y = pack2(v[8 * i + 2], v[8 * i + 3]);
    o.z = pack2(v[8 * i + 4], v[8 * i + 5]);
    o.w = pack2(v[8 * i + 6], v[8 * i + 7]);
    st_ll(xr + i * 32, o);
  }
}

__device__ __forceinline__ uint4 pack8(const float* a) {
  return make_uint4(pack2(a[0], a[1]), pack2(a[2], a[3]), pack2(a[4], a[5]), pack2(a[6], a[7]));
}
template <int U> __device__ __forceinline__ uint4 glu8(const float* g, float cl, float ch) {
  return make_uint4(pack2(g[0] * cl * g[U], g[1] * cl * g[U + 1]), pack2(g[2] * ch * g[U + 2], g[3] * ch * g[U + 3]),
                    pack2(g[4] * cl * g[U + 4], g[5] * cl * g[U + 5]), pack2(g[6] * ch * g[U + 6], g[7] * ch * g[U + 7]));
}
__device__ __forceinline__ uint32_t hfma2(uint32_t a, uint32_t b, uint32_t c) {
  uint32_t d;
  asm("fma.rn.bf16x2 %0, %1, %2, %3;" : "=r"(d) : "r"(a), "r"(b), "r"(c));
  return d;
}
__device__ __forceinline__ void keep4(const uint4 (&a)[4]) { keep(a[0]); keep(a[1]); keep(a[2]); keep(a[3]); }

#define STAGGER 0

__global__ void __launch_bounds__(NTHREADS, 1)
fused_kernel(const __grid_constant__ CUtensorMap m_qkv, const __grid_constant__ CUtensorMap m_wo,
             const __grid_constant__ CUtensorMap m_gu2, const __grid_constant__ CUtensorMap m_gu1,
             const __grid_constant__ CUtensorMap m_guh, const __grid_constant__ CUtensorMap m_wd112,
             const __grid_constant__ CUtensorMap m_wd80, const __grid_constant__ CUtensorMap m_wd32,
             const __nv_bfloat16* __restrict__ x_in,
             __nv_bfloat16* __restrict__ out, const char* __restrict__ w_o, const char* __restrict__ w_g,
             const char* __restrict__ w_u, const char* __restrict__ w_d
) {
  extern __shared__ __align__(1024) unsigned char smem_raw[];
  const uint32_t sbase = smem_u32(smem_raw);
  const uint32_t bars = sbase + SM_MISC;
  if ((sbase & 0xFFFFFFu) != SMEM_ORIGIN) return;
  TG(60);

  if (threadIdx.x == 0) {
    for (int i = 0; i < NGRAN; i++) { mbar_init(bars + BAR_FULL + 8 * i, 1); mbar_init(bars + BAR_EMPTY + 8 * i, 8); }
    for (int i = 0; i < 4; i++) mbar_init(bars + BAR_HRECV + 8 * i, 1);
    for (int i = 0; i < 2; i++) { mbar_init(bars + BAR_HREADY + 8 * i, 4); mbar_init(bars + BAR_TSTAT + 8 * i, 1); }
    asm volatile("fence.mbarrier_init.release.cluster;" ::: "memory");
  }
  __syncthreads();
  asm volatile("barrier.cluster.arrive.release.aligned;" ::: "memory");

  if (threadIdx.x >= 256) {
    asm volatile("setmaxnreg.dec.sync.aligned.u32 40;");
    const int warp = threadIdx.x >> 5, lane = threadIdx.x & 31;
    const int j = blockIdx.x & 7, b = j & 1;
    if (warp == 8) {
      ProdRing r{0u, 0u};
      const int cb0 = 224 * j + 32 * b, hb0 = 224 * j + 192 * (b ^ 1);
      const int jp = j ^ 1, cbp = 224 * jp + 32 * (b ^ 1), hbp = 224 * jp + 192 * b;
#pragma unroll 1
      for (uint32_t L = 0; L < 2; L++) {
        r.pos = 0;
        PSTOP_AT(L == 0 ? 0 : 3);
#pragma unroll 1
        for (int kb = 0; kb < 8; kb++) {
          const uint32_t g0 = prod_acquire<3>(sbase, r);
          if (elect_one()) {
            mbar_expect_tx(bars + BAR_FULL + 8 * g0, 24576);
            tma_3d(sbase + g0 * GRAN, &m_qkv, bars + BAR_FULL + 8 * g0, 64 * j, 64 * kb, 0);
          }
        }
        PSTOP_AT(10 * L + 1);
#pragma unroll 1
        for (int i = 0; i < 4; i++) {
          const uint32_t g0 = prod_acquire<2>(sbase, r);
          if (elect_one()) {
            mbar_expect_tx(bars + BAR_FULL + 8 * g0, 16384);
            tma_2d(sbase + g0 * GRAN, &m_wo, bars + BAR_FULL + 8 * g0, 64 * j, 128 * i);
          }
        }
        PSTOP_AT(10 * L + 2);
#pragma unroll 1
        for (int kb = 0; kb < 8; kb++) {
          const uint32_t g0 = prod_acquire<4>(sbase, r);
          if (elect_one()) {
            mbar_expect_tx(bars + BAR_FULL + 8 * g0, 32768);
            tma_4d(sbase + g0 * GRAN, &m_gu2, bars + BAR_FULL + 8 * g0, cb0, 64 * kb, 0, 0);
          }
        }
#pragma unroll 1
        for (int kb = 0; kb < 8; kb++) {
          const uint32_t g0 = prod_acquire<3>(sbase, r);
          if (elect_one()) {
            mbar_expect_tx(bars + BAR_FULL + 8 * g0, 24576);
            tma_4d(sbase + g0 * GRAN, &m_gu1, bars + BAR_FULL + 8 * g0, cb0 + 128, 64 * kb, 0, 0);
            tma_3d(sbase + g0 * GRAN + 16384, &m_guh, bars + BAR_FULL + 8 * g0, hb0, 64 * kb, 0);
          }
        }
        static_for<0, 16>([&](auto I) {
          constexpr int i = I.value, g0 = st_g0(ST_DN + i);
          prod_acquire_static<ST_DN + i>(sbase, L);
          if (elect_one()) {
            const uint32_t dst = sbase + g0 * GRAN, fb = bars + BAR_FULL + 8 * g0;
            const int n0 = 256 * b + 64 * dn_q(i);
            mbar_expect_tx(fb, 14336);
            if constexpr (dn_kh(i) == 0) {
              tma_2d(dst, &m_wd112, fb, n0, dn_par(i) ? cbp : cb0);
            } else {
              tma_2d(dst, &m_wd80, fb, n0, (dn_par(i) ? cbp : cb0) + 112);
              tma_2d(dst + 10240, &m_wd32, fb, n0, dn_par(i) ? hbp : hb0);
            }
          }
        });
        r.par ^= flip_mask(ST_DN, NSTAGE);
      }
    } else if (warp == 9) {
      const int cta = blockIdx.x;
      if (lane == 0) l2_prefetch(w_o + cta * 4096, 4096);
      if (lane == 1) l2_prefetch(w_g + cta * 14336, 14336);
      if (lane == 2) l2_prefetch(w_u + cta * 14336, 14336);
      if (lane == 3) l2_prefetch(w_d + cta * 14336, 14336);
    }
    __syncwarp();
    asm volatile("barrier.cluster.wait.acquire.aligned; // producer" ::: "memory");
    asm volatile("barrier.cluster.arrive.release.aligned;\nbarrier.cluster.wait.acquire.aligned; // producer" ::: "memory");
  } else {
    asm volatile("setmaxnreg.inc.sync.aligned.u32 232;");
    TS(0);
    TG(61);

    {
      PHASE_VARS;
      const int step0 = 16 * cbit + 4 * w;
      float v[32];
      const uint32_t* xp = reinterpret_cast<const uint32_t*>(x_in + (size_t)(slab_row0(c, g, ca) + 2 * qr) * 512 + step0 * 16 + qc * 2);
      uint32_t xw[16];
#pragma unroll
      for (int i = 0; i < 4; i++) {
        xw[4 * i] = __ldg(xp + i * 8); xw[4 * i + 1] = __ldg(xp + 16 * 256 + i * 8);
        xw[4 * i + 2] = __ldg(xp + i * 8 + 4); xw[4 * i + 3] = __ldg(xp + 16 * 256 + i * 8 + 4);
      }
      asm volatile("barrier.cluster.wait.acquire.aligned; // consumer" ::: "memory");
      if (STAGGER > 0 && g == 1) {
        const long long t0 = clock64();
        while (clock64() - t0 < STAGGER) {}
      }
#pragma unroll
      for (int i = 0; i < 16; i++) { v[2 * i] = bf_lo(xw[i]); v[2 * i + 1] = bf_hi(xw[i]); }
      owner_ln_publish(sbase, v, 0u, 1u);
    }
    STOP_AT(0);
    TS(1);

#pragma unroll 1
    for (uint32_t L = 0; L < 2; L++) {
      const uint32_t tag = L ^ 1;
      {
        PHASE_VARS;
        uint4 qf[4], kf[4], vf[4], pp[4];
        const int blk = 16 * g + c;
        const uint4* halo_src = g_halo + ((((L * 32 + (blk > 0 ? blk - 1 : 0)) * 8 + j) * 2 + (w & 1)) * 4) * 32 + lane;
        {
          float acc[96];
          uint4 A[3][4];
          const uint4* xs = g_xn + ((c * 8 + slab) * 32) * 32 + lane;
          bar_wg(1 + g);
          load_pk<4>(A[0], xs);
          ensure_pk<4>(A[0], xs, tag);
          TS(2 + 20 * L);
          load_pk<4>(A[1], xs + 128);
          static_for<0, 8>([&](auto I) {
            constexpr int kb = I.value;
            cons_acquire<kb>(sbase, L);
            wg_fence();
            static_for<0, 4>([&](auto K) { constexpr int k = K.value; wgmma_n192<kb == 0 && k == 0, 0>(acc, A[kb % 3][k], st_desc<kb, 2048, 8192, 1024, 1>(k)); });
            wg_commit();
            if constexpr (kb > 0) {
              wg_wait<1>();
              keep4(A[(kb + 2) % 3]);
              cons_release<kb - 1>(sbase, lane);
            }
            if constexpr (kb + 1 < 8) ensure_pk<4>(A[(kb + 1) % 3], xs + (kb + 1) * 128, tag);
            if constexpr (kb + 2 < 8) load_pk<4>(A[(kb + 2) % 3], xs + (kb + 2) * 128);
          });
          wg_wait<0>();
          TS(3 + 20 * L);
          fence_acc(acc);
          keep4(A[1]);
          cons_release<7>(sbase, lane);
#pragma unroll
          for (int h = 0; h < 4; h++) {
            kf[h] = pack8(&acc[32 + 8 * h]);
            const uint4 t = pack8(&acc[64 + 8 * h]);
            vf[h] = make_uint4(movm(t.x), movm(t.y), movm(t.z), movm(t.w));
            pp[h] = make_uint4(kf[h].y, kf[h].w, vf[h].y, vf[h].w);
          }
          if (w >= 2 && blk < 31) {
            uint4* hd = g_halo + ((((L * 32 + blk) * 8 + j) * 2 + (w & 1)) * 4) * 32 + lane;
#pragma unroll
            for (int h = 0; h < 4; h++) { uint4 t = pp[h]; t.x |= 1u; st_ll(hd + h * 32, t); }
          }
#pragma unroll
          for (int h = 0; h < 4; h++) sts128(areg + (28 + h) * 2048 + t128 * 16, pp[h]);
          if (w < 2 && blk > 0) load_pk<4>(pp, halo_src);
#pragma unroll
          for (int h = 0; h < 4; h++) qf[h] = pack8(&acc[8 * h]);
        }
        bar_wg(1 + g);
        const bool first = (w < 2) && (blk == 0);
        if (w >= 2) {
#pragma unroll
          for (int h = 0; h < 4; h++) pp[h] = lds128(areg + (28 + h) * 2048 + (t128 - 64) * 16);
        }
        bar_wg(1 + g);
        if (w < 2 && blk > 0) {
          ensure_pk<4>(pp, halo_src, 1u);
          uint4* hz = const_cast<uint4*>(halo_src);
#pragma unroll
          for (int h = 0; h < 4; h++) st_ll(hz + h * 32, make_uint4(0, 0, 0, 0));
        }
        TS(4 + 20 * L);
        const bool n0 = 2 * qc <= qr, n1 = 2 * qc + 1 <= qr;
        const uint32_t msk = (n0 ? 0xffffu : 0u) | (n1 ? 0xffff0000u : 0u);
        const float sc = 0.25f * 1.4426950408889634f;
        const float NEG = -1e30f;
        uint4* od = g_o + ((c * 8 + slab) * 32 + 4 * j) * 32 + lane;
        float l0[4], l1[4], h0[4], h1[4], ml[4], mh[4];
#pragma unroll
        for (int h = 0; h < 4; h++) {
          float sp[4], s0[4], s1[4];
          mma16816_z(sp, qf[h], pp[h].x, pp[h].y);
          mma16816_z(s0, qf[h], kf[h].x, kf[h].z);
          mma16816_z(s1, qf[h], kf[h].y, kf[h].w);
          if (first) { sp[0] = NEG; sp[1] = NEG; }
          l0[h] = n0 ? s0[0] : sp[0]; l1[h] = n1 ? s0[1] : sp[1];
          h0[h] = n0 ? s1[2] : s0[2]; h1[h] = n1 ? s1[3] : s0[3];
          ml[h] = fmaxf(l0[h], l1[h]); mh[h] = fmaxf(h0[h], h1[h]);
        }
#pragma unroll
        for (int h = 0; h < 4; h++) { ml[h] = fmaxf(ml[h], __shfl_xor_sync(0xffffffffu, ml[h], 1)); mh[h] = fmaxf(mh[h], __shfl_xor_sync(0xffffffffu, mh[h], 1)); }
#pragma unroll
        for (int h = 0; h < 4; h++) { ml[h] = fmaxf(ml[h], __shfl_xor_sync(0xffffffffu, ml[h], 2)); mh[h] = fmaxf(mh[h], __shfl_xor_sync(0xffffffffu, mh[h], 2)); }
        float sl[4], sh[4];
#pragma unroll
        for (int h = 0; h < 4; h++) {
          const float bl = -ml[h] * sc, bh = -mh[h] * sc;
          l0[h] = ex2(fmaf(l0[h], sc, bl)); l1[h] = ex2(fmaf(l1[h], sc, bl));
          h0[h] = ex2(fmaf(h0[h], sc, bh)); h1[h] = ex2(fmaf(h1[h], sc, bh));
          sl[h] = l0[h] + l1[h]; sh[h] = h0[h] + h1[h];
        }
#pragma unroll
        for (int h = 0; h < 4; h++) { sl[h] += __shfl_xor_sync(0xffffffffu, sl[h], 1); sh[h] += __shfl_xor_sync(0xffffffffu, sh[h], 1); }
#pragma unroll
        for (int h = 0; h < 4; h++) { sl[h] += __shfl_xor_sync(0xffffffffu, sl[h], 2); sh[h] += __shfl_xor_sync(0xffffffffu, sh[h], 2); }
#pragma unroll
        for (int h = 0; h < 4; h++) {
          const float il = rcp(sl[h]), ih = rcp(sh[h]);
          const uint32_t pl = pack2(l0[h] * il, l1[h] * il), ph = pack2(h0[h] * ih, h1[h] * ih);
          const uint4 P = make_uint4(pl & msk, ph & ~msk, 0u, ph & msk);
          float o0[4], o1[4];
          mma16816_z(o0, P, vf[h].x, vf[h].y);
          mma16816_z(o1, P, vf[h].z, vf[h].w);
          mma1688(o0, pl & ~msk, 0u, pp[h].z);
          mma1688(o1, pl & ~msk, 0u, pp[h].w);
          st_ll(od + h * 32, make_uint4(set_tag(pack2(o0[0], o0[1]), tag), pack2(o0[2], o0[3]), pack2(o1[0], o1[1]), pack2(o1[2], o1[3])));
        }
      }
      TS(5 + 20 * L);
      if (L == 0) { STOP_AT(1); } else { STOP_AT(11); }
      {
        PHASE_VARS;
        float acc[32];
        uint4 A[32], xr[4];
        const uint4* os = g_o + ((c * 8 + slab) * 32) * 32 + lane;
        uint4* xp = g_xraw + ((c * 8 + slab) * 32 + 4 * j) * 32 + lane;
        load_pk<4>(xr, xp);
        load_pk<4>(A, os);
        ensure_pk<4>(A, os, tag);
        TS(6 + 20 * L);
        load_pk<28>(A + 4, os + 128);
        static_for<0, 8>([&](auto I) {
          constexpr int kb = I.value;
          if constexpr ((kb & 1) == 0) cons_acquire<ST_WO + kb / 2>(sbase, L);
          if constexpr (kb > 0) ensure_pk<4>(A + 4 * kb, os + kb * 128, tag);
          wg_fence();
          static_for<0, 4>([&](auto K) {
            constexpr int k = K.value;
            wgmma_n64<kb == 0 && k == 0, 0>(acc, A[4 * kb + k], st_desc<ST_WO + kb / 2, 2048, 8192, 1024, 1>(4 * (kb & 1) + k));
          });
          wg_commit();
          if constexpr ((kb & 1) == 0 && kb > 0) { wg_wait<1>(); cons_release<ST_WO + kb / 2 - 1>(sbase, lane); }
        });
        wg_wait<0>();
        TS(7 + 20 * L);
        fence_acc(acc);
#pragma unroll
        for (int k = 0; k < 32; k++) keep(A[k]);
        cons_release<ST_WO + 3>(sbase, lane);
        ensure_pk<4>(xr, xp, 1u);
#pragma unroll
        for (int i = 0; i < 4; i++) {
          acc[8 * i + 0] += bf_lo(xr[i].x); acc[8 * i + 1] += bf_hi(xr[i].x); acc[8 * i + 2] += bf_lo(xr[i].y); acc[8 * i + 3] += bf_hi(xr[i].y);
          acc[8 * i + 4] += bf_lo(xr[i].z); acc[8 * i + 5] += bf_hi(xr[i].z); acc[8 * i + 6] += bf_lo(xr[i].w); acc[8 * i + 7] += bf_hi(xr[i].w);
          uint4 o = pack8(&acc[8 * i]);
          o.x = set_tag(o.x, 0u);
          st_ll(xp + i * 32, o);
        }
        uint4 st = local_stats(acc);
        st.x = set_tag(st.x, tag);
        if (qc == 0) st_ll(g_stats + ((c * 8 + slab) * 8 + j) * 8 + qr, st);
      }
      TS(8 + 20 * L);
      if (L == 0) { STOP_AT(2); } else { STOP_AT(12); }
      uint4 hs[14];
      {
        PHASE_VARS;
        float acc[128];
        uint4 A[3][4];
        const uint4* xs = g_xraw + ((c * 8 + slab) * 32) * 32 + lane;
        const uint4* sp = g_stats + ((c * 8 + slab) * 8 + 2 * qc) * 8 + qr;
        const uint32_t sm = areg + t128 * 16;
        uint32_t rl2, rh2, bl2, bh2;
        float cl, ch;
        {
          uint4 p[2];
          load_pk<4>(A[0], xs);
          p[0] = ld_ll(sp); p[1] = ld_ll(sp + 8);
          for (uint32_t n = 0; !ok_pk<2>(p, tag) && n < SPIN_LIMIT; n++) { load_pk<4>(A[0], xs); p[0] = ld_ll(sp); p[1] = ld_ll(sp + 8); }
          TS(9 + 20 * L);
          load_pk<4>(A[1], xs + 128);
          float ml, rl, mh, rh;
          combine_stats(p[0], p[1], ml, rl, mh, rh);
          rl2 = pack2(rl, rl); rh2 = pack2(rh, rh);
          const float rlb = bf_lo(rl2), rhb = bf_lo(rh2);
          bl2 = pack2(-ml * rlb, -ml * rlb); bh2 = pack2(-mh * rhb, -mh * rhb);
          cl = rl / rlb; cl *= cl; ch = rh / rhb; ch *= ch;
        }
        auto normalise = [&](uint4 (&xb)[4], int kb) {
#pragma unroll
          for (int k = 0; k < 4; k++) {
            xb[k].x = hfma2(xb[k].x, rl2, bl2); xb[k].y = hfma2(xb[k].y, rh2, bh2);
            xb[k].z = hfma2(xb[k].z, rl2, bl2); xb[k].w = hfma2(xb[k].w, rh2, bh2);
            sts128(sm + (kb * 4 + k) * 2048, xb[k]);
          }
        };
        ensure_pk<4>(A[0], xs, 0u);
        normalise(A[0], 0);
        static_for<0, 8>([&](auto I) {
          constexpr int kb = I.value;
          cons_acquire<ST_G1 + kb>(sbase, L);
          wg_fence();
          static_for<0, 4>([&](auto K) { constexpr int k = K.value; wgmma_n256<kb == 0 && k == 0, 0>(acc, A[kb % 3][k], st_desc<ST_G1 + kb, 2048, 8192, 1024, 1>(k)); });
          wg_commit();
          if constexpr (kb > 0) {
            wg_wait<1>();
            keep4(A[(kb + 2) % 3]);
            cons_release<ST_G1 + kb - 1>(sbase, lane);
          }
          if constexpr (kb + 1 < 8) ensure_pk<4>(A[(kb + 1) % 3], xs + (kb + 1) * 128, 0u);
          if constexpr (kb + 2 < 8) load_pk<4>(A[(kb + 2) % 3], xs + (kb + 2) * 128);
          if constexpr (kb + 1 < 8) normalise(A[(kb + 1) % 3], kb + 1);
        });
        wg_wait<0>();
        TS(10 + 20 * L);
        fence_acc(acc);
        keep4(A[1]);
        cons_release<ST_G1 + 7>(sbase, lane);
        uint4 B[2][4];
#pragma unroll
        for (int k = 0; k < 4; k++) B[0][k] = lds128(sm + k * 2048);
#pragma unroll
        for (int s = 0; s < 8; s++) hs[s] = glu8<32>(&acc[64 * (s >> 2) + 8 * (s & 3)], cl, ch);
        float acc2[96];
        const uint32_t hdst = mapa(sm, cbit ^ 1);
        const uint32_t hbar1 = mapa(bars + BAR_HRECV + 16 * g, cbit ^ 1);
        if (t128 == 0) { mbar_expect_tx(bars + BAR_HRECV + 16 * g, 8 * 2048); mbar_expect_tx(bars + BAR_HRECV + 16 * g + 8, 6 * 2048); }
        static_for<0, 8>([&](auto I) {
          constexpr int kb = I.value;
          cons_acquire<ST_G2 + kb>(sbase, L);
          wg_fence();
          static_for<0, 4>([&](auto K) {
            constexpr int k = K.value;
            wgmma_n128<kb == 0 && k == 0, 0>(acc2, B[kb & 1][k], st_desc<ST_G2 + kb, 2048, 8192, 1024, 1>(k));
            wgmma_n64<kb == 0 && k == 0, 64>(acc2, B[kb & 1][k], st_desc<ST_G2 + kb, 1024, 4096, 512, 2>(k) + (16384 >> 4));
          });
          wg_commit();
          if constexpr (kb > 0) {
            wg_wait<1>();
            keep4(B[(kb + 1) & 1]);
            cons_release<ST_G2 + kb - 1>(sbase, lane);
          }
          if constexpr (kb + 1 < 8) {
#pragma unroll
            for (int k = 0; k < 4; k++) B[(kb + 1) & 1][k] = lds128(sm + ((kb + 1) * 4 + k) * 2048);
          }
          if constexpr (kb == 3) {
            __syncwarp();
            if (lane == 0) mbar_arrive_remote(mapa(bars + BAR_HREADY + 8 * g, cbit ^ 1));
          }
          if constexpr (kb >= 4) {
            if constexpr (kb == 4) mbar_wait(bars + BAR_HREADY + 8 * g, L);
            st_async128(hdst + (2 * kb - 8) * 2048, hs[2 * kb - 8], hbar1);
            st_async128(hdst + (2 * kb - 7) * 2048, hs[2 * kb - 7], hbar1);
          }
        });
        wg_wait<0>();
        TS(11 + 20 * L);
        fence_acc(acc2);
        keep4(B[1]);
        cons_release<ST_G2 + 7>(sbase, lane);
#pragma unroll
        for (int s = 0; s < 4; s++) hs[8 + s] = glu8<32>(&acc2[8 * s], cl, ch);
#pragma unroll
        for (int s = 0; s < 2; s++) hs[12 + s] = glu8<16>(&acc2[64 + 8 * s], cl, ch);
      }
      {
        PHASE_VARS;
        TS(12 + 20 * L);
        const uint32_t hdst = mapa(areg + t128 * 16, cbit ^ 1);
        const uint32_t hbar2 = mapa(bars + BAR_HRECV + 16 * g + 8, cbit ^ 1);
        uint4* pd = g_part + ((((c * 4 + w) * 2 + cbit) * 4 + ca) * 2 + g) * 16 * 32 + lane;
        uint4 hb[7];
        float a0[32], a1[32], a2[32], a3[32];
        auto publish = [&](float (&a)[32], int q, int s0, int s1) {
#pragma unroll
          for (int s = s0; s < s1; s++) {
            uint4 o = pack8(&a[8 * s]);
            o.x = set_tag(o.x, tag);
            st_ll(pd + (4 * q + s) * 32, o);
          }
        };
        static_for<0, 16>([&](auto I) {
          constexpr int i = I.value, q = dn_q(i), par = dn_par(i), kh = dn_kh(i);
          auto mm = [&](auto K) {
            constexpr int k = decltype(K)::value;
            constexpr bool init = (k == 0 && par == 0 && kh == 0);
            constexpr uint64_t db = st_desc<ST_DN + i, 2048, 8192, 1024, 1>(k);
            if constexpr (q == 0) { if constexpr (par) wgmma_n64<init, 0>(a0, hb[k], db); else wgmma_n64<init, 0>(a0, hs[7 * kh + k], db); }
            if constexpr (q == 1) { if constexpr (par) wgmma_n64<init, 0>(a1, hb[k], db); else wgmma_n64<init, 0>(a1, hs[7 * kh + k], db); }
            if constexpr (q == 2) { if constexpr (par) wgmma_n64<init, 0>(a2, hb[k], db); else wgmma_n64<init, 0>(a2, hs[7 * kh + k], db); }
            if constexpr (q == 3) { if constexpr (par) wgmma_n64<init, 0>(a3, hb[k], db); else wgmma_n64<init, 0>(a3, hs[7 * kh + k], db); }
          };
          cons_acquire<ST_DN + i>(sbase, L);
          wg_fence();
          mm(IC<0>{}); mm(IC<1>{}); mm(IC<2>{}); mm(IC<3>{}); mm(IC<4>{}); mm(IC<5>{}); mm(IC<6>{});
          wg_commit();
          if constexpr (i > 0) { wg_wait<1>(); cons_release<ST_DN + i - 1>(sbase, lane); }
          if constexpr (i < 3) {
            st_async128(hdst + (8 + 2 * i) * 2048, hs[8 + 2 * i], hbar2);
            st_async128(hdst + (9 + 2 * i) * 2048, hs[9 + 2 * i], hbar2);
          }
          constexpr int n = i + 1;
          if constexpr (n < 16 && dn_par(n) && n != 4 && n != 7) {
            if constexpr (n == 2) { mbar_wait(bars + BAR_HRECV + 16 * g, L); TS(13 + 20 * L); }
            if constexpr (n == 6) { mbar_wait(bars + BAR_HRECV + 16 * g + 8, L); TS(14 + 20 * L); }
#pragma unroll
            for (int k = 0; k < 7; k++) { if constexpr (n != 2) keep(hb[k]); hb[k] = lds128(areg + t128 * 16 + (7 * dn_kh(n) + k) * 2048); }
          }
          if constexpr (i == 7) { fence_acc(a0); publish(a0, 0, 0, 4); }
          if constexpr (i == 8) { fence_acc(a1); publish(a1, 1, 0, 2); }
          if constexpr (i == 9) publish(a1, 1, 2, 4);
          if constexpr (i == 12) { fence_acc(a2); publish(a2, 2, 0, 2); }
          if constexpr (i == 13) publish(a2, 2, 2, 4);
        });
        wg_wait<0>();
        TS(15 + 20 * L);
        fence_acc(a3);
#pragma unroll
        for (int k = 0; k < 7; k++) { keep(hb[k]); keep(hs[7 + k]); }
        cons_release<NSTAGE - 1>(sbase, lane);
        publish(a3, 3, 0, 4);
      }
      {
        PHASE_VARS;
        const int oslab = 4 * g + ca;
        const uint4* xq = g_xraw + ((c * 8 + oslab) * 32 + 16 * cbit + 4 * w) * 32 + lane;
        const uint4* ps = g_part + ((((c * 4 + ca) * 2 + cbit) * 4) * 2 + g) * 16 * 32 + (4 * w) * 32 + lane;
        uint4 xr[4], P[4][4];
        float v[32];
        load_pk<4>(xr, xq);
#pragma unroll
        for (int src = 0; src < 4; src++) load_pk<4>(P[src], ps + src * (2 * 16 * 32));
#pragma unroll
        for (int src = 0; src < 4; src++) ensure_pk<4>(P[src], ps + src * (2 * 16 * 32), tag);
        TS(16 + 20 * L);
        ensure_pk<4>(xr, xq, 0u);
#pragma unroll
        for (int i = 0; i < 4; i++) {
          v[8 * i + 0] = bf_lo(xr[i].x); v[8 * i + 1] = bf_hi(xr[i].x); v[8 * i + 2] = bf_lo(xr[i].y); v[8 * i + 3] = bf_hi(xr[i].y);
          v[8 * i + 4] = bf_lo(xr[i].z); v[8 * i + 5] = bf_hi(xr[i].z); v[8 * i + 6] = bf_lo(xr[i].w); v[8 * i + 7] = bf_hi(xr[i].w);
          float d[8] = {0, 0, 0, 0, 0, 0, 0, 0};
#pragma unroll
          for (int src = 0; src < 4; src++) {
            const uint4 p = P[src][i];
            d[0] += bf_lo(p.x); d[1] += bf_hi(p.x); d[2] += bf_lo(p.y); d[3] += bf_hi(p.y);
            d[4] += bf_lo(p.z); d[5] += bf_hi(p.z); d[6] += bf_lo(p.w); d[7] += bf_hi(p.w);
          }
#pragma unroll
          for (int k = 0; k < 8; k++) v[8 * i + k] += d[k];
        }
        if (L == 0) {
          owner_ln_publish(sbase, v, 1u, 0u);
        } else {
          uint32_t* op = reinterpret_cast<uint32_t*>(out + (size_t)(slab_row0(c, g, ca) + 2 * qr) * 512 + (16 * cbit + 4 * w) * 16 + qc * 2);
#pragma unroll
          for (int i = 0; i < 4; i++) {
            op[i * 8] = pack2(v[8 * i], v[8 * i + 1]);
            op[16 * 256 + i * 8] = pack2(v[8 * i + 2], v[8 * i + 3]);
            op[i * 8 + 4] = pack2(v[8 * i + 4], v[8 * i + 5]);
            op[16 * 256 + i * 8 + 4] = pack2(v[8 * i + 6], v[8 * i + 7]);
          }
        }
      }
      TS(17 + 20 * L);
      if (L == 0) { STOP_AT(3); }
    }
    TG(62);
    asm volatile("barrier.cluster.arrive.release.aligned;\nbarrier.cluster.wait.acquire.aligned; // consumer" ::: "memory");
    TG(63);
  }
}

typedef CUresult (*EncodeFn)(CUtensorMap*, CUtensorMapDataType, cuuint32_t, void*, const cuuint64_t*, const cuuint64_t*,
                             const cuuint32_t*, const cuuint32_t*, CUtensorMapInterleave, CUtensorMapSwizzle,
                             CUtensorMapL2promotion, CUtensorMapFloatOOBfill);

void encode(EncodeFn fn, CUtensorMap* m, int rank, const void* base, const cuuint64_t* dims, const cuuint64_t* strides,
            const cuuint32_t* box, CUtensorMapSwizzle sw) {
  cuuint32_t es[5] = {1, 1, 1, 1, 1};
  fn(m, CU_TENSOR_MAP_DATA_TYPE_BFLOAT16, (cuuint32_t)rank, const_cast<void*>(base), dims, strides, box, es,
     CU_TENSOR_MAP_INTERLEAVE_NONE, sw, CU_TENSOR_MAP_L2_PROMOTION_L2_128B, CU_TENSOR_MAP_FLOAT_OOB_FILL_NONE);
}

}

extern "C" void kernel_launch(void* const* d_in, const int* in_sizes, int n_in, void* d_out, int out_size) {
  (void)in_sizes; (void)n_in; (void)out_size;
  const __nv_bfloat16* x = (const __nv_bfloat16*)d_in[0];
  const char* wqkv = (const char*)d_in[1];
  const char* wo = (const char*)d_in[2];
  const char* wg = (const char*)d_in[4];
  const char* wu = (const char*)d_in[5];
  const char* wd = (const char*)d_in[6];

  static EncodeFn fn = nullptr;
  if (!fn) {
    void* p = nullptr;
    cudaDriverEntryPointQueryResult st;
    cudaGetDriverEntryPoint("cuTensorMapEncodeTiled", &p, cudaEnableDefault, &st);
    fn = (EncodeFn)p;
    cudaFuncSetAttribute(fused_kernel, cudaFuncAttributeMaxDynamicSharedMemorySize, SMEM_BYTES);
  }
  CUtensorMap m_qkv, m_wo, m_gu2, m_gu1, m_guh, m_wd112, m_wd80, m_wd32;
  {
    cuuint64_t dims[3] = {512, 512, 3}, str[2] = {3072, 1024};
    cuuint32_t box[3] = {64, 64, 3};
    encode(fn, &m_qkv, 3, wqkv, dims, str, box, CU_TENSOR_MAP_SWIZZLE_128B);
  }
  {
    cuuint64_t dims[2] = {512, 512}, str[1] = {1024};
    cuuint32_t box[2] = {64, 128};
    encode(fn, &m_wo, 2, wo, dims, str, box, CU_TENSOR_MAP_SWIZZLE_128B);
  }
  {
    const char* lo = wg < wu ? wg : wu;
    cuuint64_t diff = (cuuint64_t)(wg < wu ? wu - wg : wg - wu);
    cuuint64_t dims[4] = {1792, 512, 2, 2}, str[3] = {3584, diff, 128};
    cuuint32_t box2[4] = {64, 64, 2, 2}, box1[4] = {64, 64, 2, 1}, boxh[3] = {32, 64, 2};
    encode(fn, &m_gu2, 4, lo, dims, str, box2, CU_TENSOR_MAP_SWIZZLE_128B);
    encode(fn, &m_gu1, 4, lo, dims, str, box1, CU_TENSOR_MAP_SWIZZLE_128B);
    encode(fn, &m_guh, 3, lo, dims, str, boxh, CU_TENSOR_MAP_SWIZZLE_64B);
  }
  {
    cuuint64_t dims[2] = {512, 1792}, str[1] = {1024};
    cuuint32_t b112[2] = {64, 112}, b80[2] = {64, 80}, b32[2] = {64, 32};
    encode(fn, &m_wd112, 2, wd, dims, str, b112, CU_TENSOR_MAP_SWIZZLE_128B);
    encode(fn, &m_wd80, 2, wd, dims, str, b80, CU_TENSOR_MAP_SWIZZLE_128B);
    encode(fn, &m_wd32, 2, wd, dims, str, b32, CU_TENSOR_MAP_SWIZZLE_128B);
  }
  cudaLaunchConfig_t cfg = {};
  cfg.gridDim = dim3(128);
  cfg.blockDim = dim3(NTHREADS);
  cfg.dynamicSmemBytes = SMEM_BYTES;
  cfg.stream = cudaStreamPerThread;
  cudaLaunchAttribute at[1];
  at[0].id = cudaLaunchAttributeClusterDimension;
  at[0].val.clusterDim.x = 2; at[0].val.clusterDim.y = 1; at[0].val.clusterDim.z = 1;
  cfg.attrs = at; cfg.numAttrs = 1;
  cudaLaunchKernelEx(&cfg, fused_kernel, m_qkv, m_wo, m_gu2, m_gu1, m_guh, m_wd112, m_wd80, m_wd32, x, (__nv_bfloat16*)d_out, wo, wg, wu, wd
  );
}
```

```cpp
#include <cuda_runtime.h>
#include <cuda_bf16.h>
#include <cuda.h>
#include <stdint.h>

namespace {

constexpr int NTHREADS = 384;
constexpr int GRAN = 8192;
constexpr int NGRAN = 12;
constexpr int SM_AREG = NGRAN * GRAN;
constexpr int SM_MISC = SM_AREG + 131072;
constexpr int SM_TSTAT = SM_MISC + 256;
constexpr int SMEM_BYTES = SM_TSTAT + 2048;
constexpr int BAR_FULL = 0, BAR_EMPTY = 96, BAR_HRECV = 192, BAR_HREADY = 224, BAR_TSTAT = 240;

__device__ uint4 g_xn[16 * 8 * 32 * 32];
__device__ uint4 g_xraw[16 * 8 * 32 * 32];
__device__ uint4 g_o[16 * 8 * 32 * 32];
__device__ uint4 g_stats[16 * 8 * 8 * 8];
__device__ uint4 g_halo[2 * 32 * 8 * 8 * 32];
__device__ uint4 g_part[16 * 4 * 2 * 4 * 2 * 16 * 32];

#define TS(n)
#define TG(n)
#define OPAQUE(x) asm volatile("" : "+r"(x))
#define PHASE_VARS                                                                                   \
  int tid_ = threadIdx.x, bid_ = blockIdx.x;                                                         \
  OPAQUE(tid_); OPAQUE(bid_);                                                                        \
  const int lane = tid_ & 31, warp = tid_ >> 5, g = warp >> 2, w = warp & 3, t128 = tid_ & 127;      \
  const int qr = lane >> 2, qc = lane & 3, slab = warp;                                              \
  const int c = bid_ >> 3, j = bid_ & 7, ca = j >> 1, cbit = j & 1;                                  \
  const uint32_t areg = sbase + SM_AREG + g * 65536;                                                 \
  (void)g; (void)j; (void)w; (void)t128; (void)qr; (void)qc; (void)slab; (void)c; (void)ca; (void)cbit; (void)areg; (void)lane
#define STOP_AT(n)
#define PSTOP_AT(n)

__device__ __forceinline__ uint32_t smem_u32(const void* p) { return (uint32_t)__cvta_generic_to_shared(p); }
__device__ __forceinline__ void mbar_init(uint32_t bar, uint32_t cnt) {
  asm volatile("mbarrier.init.shared::cta.b64 [%0], %1;" ::"r"(bar), "r"(cnt) : "memory");
}
__device__ __forceinline__ void mbar_expect_tx(uint32_t bar, uint32_t bytes) {
  asm volatile("mbarrier.arrive.expect_tx.shared::cta.b64 _, [%0], %1;" ::"r"(bar), "r"(bytes) : "memory");
}
__device__ __forceinline__ void mbar_arrive(uint32_t bar) {
  asm volatile("mbarrier.arrive.shared::cta.b64 _, [%0];" ::"r"(bar) : "memory");
}
__device__ __forceinline__ void mbar_arrive_remote(uint32_t cluster_addr) {
  asm volatile("mbarrier.arrive.relaxed.cluster.shared::cluster.b64 _, [%0];" ::"r"(cluster_addr) : "memory");
}
__device__ __forceinline__ bool mbar_try(uint32_t bar, uint32_t parity) {
  uint32_t ok;
  asm volatile("{\n.reg .pred p;\nmbarrier.try_wait.parity.shared::cta.b64 p, [%1], %2;\nselp.u32 %0, 1, 0, p;\n}"
               : "=r"(ok) : "r"(bar), "r"(parity) : "memory");
  return ok != 0;
}
__device__ __forceinline__ bool mbar_test(uint32_t bar, uint32_t parity) {
  uint32_t ok;
  asm volatile("{\n.reg .pred p;\nmbarrier.test_wait.parity.shared::cta.b64 p, [%1], %2;\nselp.u32 %0, 1, 0, p;\n}"
               : "=r"(ok) : "r"(bar), "r"(parity) : "memory");
  return ok != 0;
}
constexpr uint32_t SPIN_LIMIT = 1u << 16;
constexpr uint32_t SMEM_ORIGIN = 1024;
__device__ __forceinline__ void mbar_wait(uint32_t bar, uint32_t parity) {
  for (uint32_t n = 0; !mbar_try(bar, parity) && n < SPIN_LIMIT; n++) {}
}
__device__ __forceinline__ uint32_t mapa(uint32_t addr, uint32_t rank) {
  uint32_t r;
  asm volatile("mapa.shared::cluster.u32 %0, %1, %2;" : "=r"(r) : "r"(addr), "r"(rank));
  return r;
}
__device__ __forceinline__ void cluster_sync_all() {
  asm volatile("barrier.cluster.arrive.release.aligned;\nbarrier.cluster.wait.acquire.aligned;" ::: "memory");
}

__device__ __forceinline__ void tma_2d(uint32_t dst, const CUtensorMap* m, uint32_t bar, int c0, int c1) {
  asm volatile("cp.async.bulk.tensor.2d.shared::cluster.global.mbarrier::complete_tx::bytes [%0], [%1, {%3, %4}], [%2];"
               ::"r"(dst), "l"(m), "r"(bar), "r"(c0), "r"(c1) : "memory");
}
__device__ __forceinline__ void tma_3d(uint32_t dst, const CUtensorMap* m, uint32_t bar, int c0, int c1, int c2) {
  asm volatile("cp.async.bulk.tensor.3d.shared::cluster.global.mbarrier::complete_tx::bytes [%0], [%1, {%3, %4, %5}], [%2];"
               ::"r"(dst), "l"(m), "r"(bar), "r"(c0), "r"(c1), "r"(c2) : "memory");
}
__device__ __forceinline__ void tma_4d(uint32_t dst, const CUtensorMap* m, uint32_t bar, int c0, int c1, int c2, int c3) {
  asm volatile("cp.async.bulk.tensor.4d.shared::cluster.global.mbarrier::complete_tx::bytes [%0], [%1, {%3, %4, %5, %6}], [%2];"
               ::"r"(dst), "l"(m), "r"(bar), "r"(c0), "r"(c1), "r"(c2), "r"(c3) : "memory");
}
__device__ __forceinline__ void l2_prefetch(const void* p, uint32_t bytes) {
  asm volatile("cp.async.bulk.prefetch.L2.global [%0], %1;" ::"l"(p), "r"(bytes) : "memory");
}

__device__ __forceinline__ uint4 ld_ll(const uint4* p) {
  uint4 v;
  asm volatile("ld.relaxed.gpu.global.v4.u32 {%0,%1,%2,%3}, [%4];" : "=r"(v.x), "=r"(v.y), "=r"(v.z), "=r"(v.w) : "l"(p) : "memory");
  return v;
}
__device__ __forceinline__ void st_ll(uint4* p, uint4 v) {
  asm volatile("st.relaxed.gpu.global.v4.u32 [%0], {%1,%2,%3,%4};" ::"l"(p), "r"(v.x), "r"(v.y), "r"(v.z), "r"(v.w) : "memory");
}
__device__ __forceinline__ uint4 lds128(uint32_t a) {
  uint4 v;
  asm volatile("ld.shared.v4.u32 {%0,%1,%2,%3}, [%4];" : "=r"(v.x), "=r"(v.y), "=r"(v.z), "=r"(v.w) : "r"(a) : "memory");
  return v;
}
__device__ __forceinline__ void sts128(uint32_t a, uint4 v) {
  asm volatile("st.shared.v4.u32 [%0], {%1,%2,%3,%4};" ::"r"(a), "r"(v.x), "r"(v.y), "r"(v.z), "r"(v.w) : "memory");
}
__device__ __forceinline__ void st_async128(uint32_t cluster_addr, uint4 v, uint32_t cluster_bar) {
  asm volatile("st.async.weak.shared::cluster.mbarrier::complete_tx::bytes.v4.b32 [%0], {%1,%2,%3,%4}, [%5];"
               ::"r"(cluster_addr), "r"(v.x), "r"(v.y), "r"(v.z), "r"(v.w), "r"(cluster_bar) : "memory");
}
__device__ __forceinline__ uint32_t pack2(float lo, float hi) {
  uint32_t r;
  asm("cvt.rn.bf16x2.f32 %0, %1, %2;" : "=r"(r) : "f"(hi), "f"(lo));
  return r;
}
__device__ __forceinline__ float bf_lo(uint32_t w) { return __uint_as_float(w << 16); }
__device__ __forceinline__ float bf_hi(uint32_t w) { return __uint_as_float(w & 0xffff0000u); }
__device__ __forceinline__ uint32_t set_tag(uint32_t w, uint32_t tag) { return (w & ~1u) | tag; }
__device__ __forceinline__ uint32_t movm(uint32_t a) {
  uint32_t d;
  asm("movmatrix.sync.aligned.m8n8.trans.b16 %0, %1;" : "=r"(d) : "r"(a));
  return d;
}
__device__ __forceinline__ void mma16816(float (&d)[4], const uint4& a, uint32_t b0, uint32_t b1) {
  asm("mma.sync.aligned.m16n8k16.row.col.f32.bf16.bf16.f32 {%0,%1,%2,%3}, {%4,%5,%6,%7}, {%8,%9}, {%0,%1,%2,%3};"
               : "+f"(d[0]), "+f"(d[1]), "+f"(d[2]), "+f"(d[3])
               : "r"(a.x), "r"(a.y), "r"(a.z), "r"(a.w), "r"(b0), "r"(b1));
}
__device__ __forceinline__ void mma1688(float (&d)[4], uint32_t a0, uint32_t a1, uint32_t b0) {
  asm("mma.sync.aligned.m16n8k8.row.col.f32.bf16.bf16.f32 {%0,%1,%2,%3}, {%4,%5}, {%6}, {%0,%1,%2,%3};"
      : "+f"(d[0]), "+f"(d[1]), "+f"(d[2]), "+f"(d[3])
      : "r"(a0), "r"(a1), "r"(b0));
}
__device__ __forceinline__ void mma16816_z(float (&d)[4], const uint4& a, uint32_t b0, uint32_t b1) {
  asm("mma.sync.aligned.m16n8k16.row.col.f32.bf16.bf16.f32 {%0,%1,%2,%3}, {%4,%5,%6,%7}, {%8,%9}, {%10,%10,%10,%10};"
      : "=f"(d[0]), "=f"(d[1]), "=f"(d[2]), "=f"(d[3])
      : "r"(a.x), "r"(a.y), "r"(a.z), "r"(a.w), "r"(b0), "r"(b1), "f"(0.f));
}
__device__ __forceinline__ float ex2(float x) {
  float y;
  asm("ex2.approx.ftz.f32 %0, %1;" : "=f"(y) : "f"(x));
  return y;
}
__device__ __forceinline__ float rcp(float x) {
  float y;
  asm("rcp.approx.ftz.f32 %0, %1;" : "=f"(y) : "f"(x));
  return y;
}
__device__ __forceinline__ void cp_async16(uint32_t dst, const void* src) {
  asm volatile("cp.async.cg.shared.global [%0], [%1], 16;" ::"r"(dst), "l"(src) : "memory");
}
__device__ __forceinline__ void cp_commit() { asm volatile("cp.async.commit_group;" ::: "memory"); }
template <int N> __device__ __forceinline__ void cp_wait() { asm volatile("cp.async.wait_group %0;" ::"n"(N) : "memory"); }
__device__ __forceinline__ void bar_wg(int id) { asm volatile("bar.sync %0, 128;" ::"r"(id) : "memory"); }
__device__ __forceinline__ void wg_fence() { asm volatile("wgmma.fence.sync.aligned;" ::: "memory"); }
__device__ __forceinline__ void wg_commit() { asm volatile("wgmma.commit_group.sync.aligned;" ::: "memory"); }
template <int N> __device__ __forceinline__ void wg_wait() { asm volatile("wgmma.wait_group.sync.aligned %0;" ::"n"(N) : "memory"); }
__device__ __forceinline__ void keep(const uint4& a) { asm volatile("" ::"r"(a.x), "r"(a.y), "r"(a.z), "r"(a.w) : "memory"); }
template <int T> __device__ __forceinline__ void zero_acc(float (&d)[T]) {
#pragma unroll
  for (int i = 0; i < T; i++) d[i] = 0.f;
}
template <int T> __device__ __forceinline__ void fence_acc(float (&d)[T]) {
#pragma unroll
  for (int i = 0; i < T; i++) asm volatile("" : "+f"(d[i])::"memory");
}

template <int O, int T> __device__ __forceinline__ void wgmma_rs_n64(float (&d)[T], const uint4& a, uint64_t db) {
  asm volatile("{\n.reg .pred p;\nsetp.ne.b32 p, 1, 0;\n"
    "wgmma.mma_async.sync.aligned.m64n64k16.f32.bf16.bf16 "
    "{%0, %1, %2, %3, %4, %5, %6, %7, %8, %9, %10, %11, %12, %13, %14, %15, "
    "%16, %17, %18, %19, %20, %21, %22, %23, %24, %25, %26, %27, %28, %29, %30, %31}, "
    "{%32, %33, %34, %35}, %36, p, 1, 1, 1;\n}\n"
    : "+f"(d[O + 0]), "+f"(d[O + 1]), "+f"(d[O + 2]), "+f"(d[O + 3]), "+f"(d[O + 4]), "+f"(d[O + 5]), "+f"(d[O + 6]), "+f"(d[O + 7]),
      "+f"(d[O + 8]), "+f"(d[O + 9]), "+f"(d[O + 10]), "+f"(d[O + 11]), "+f"(d[O + 12]), "+f"(d[O + 13]), "+f"(d[O + 14]), "+f"(d[O + 15]),
      "+f"(d[O + 16]), "+f"(d[O + 17]), "+f"(d[O + 18]), "+f"(d[O + 19]), "+f"(d[O + 20]), "+f"(d[O + 21]), "+f"(d[O + 22]), "+f"(d[O + 23]),
      "+f"(d[O + 24]), "+f"(d[O + 25]), "+f"(d[O + 26]), "+f"(d[O + 27]), "+f"(d[O + 28]), "+f"(d[O + 29]), "+f"(d[O + 30]), "+f"(d[O + 31])
    : "r"(a.x), "r"(a.y), "r"(a.z), "r"(a.w), "l"(db));
}
template <int O, int T> __device__ __forceinline__ void wgmma_rs_n64_init(float (&d)[T], const uint4& a, uint64_t db) {
  asm volatile("{\n.reg .pred p;\nsetp.ne.b32 p, 0, 0;\n"
    "wgmma.mma_async.sync.aligned.m64n64k16.f32.bf16.bf16 "
    "{%0, %1, %2, %3, %4, %5, %6, %7, %8, %9, %10, %11, %12, %13, %14, %15, "
    "%16, %17, %18, %19, %20, %21, %22, %23, %24, %25, %26, %27, %28, %29, %30, %31}, "
    "{%32, %33, %34, %35}, %36, p, 1, 1, 1;\n}\n"
    : "=f"(d[O + 0]), "=f"(d[O + 1]), "=f"(d[O + 2]), "=f"(d[O + 3]), "=f"(d[O + 4]), "=f"(d[O + 5]), "=f"(d[O + 6]), "=f"(d[O + 7]),
      "=f"(d[O + 8]), "=f"(d[O + 9]), "=f"(d[O + 10]), "=f"(d[O + 11]), "=f"(d[O + 12]), "=f"(d[O + 13]), "=f"(d[O + 14]), "=f"(d[O + 15]),
      "=f"(d[O + 16]), "=f"(d[O + 17]), "=f"(d[O + 18]), "=f"(d[O + 19]), "=f"(d[O + 20]), "=f"(d[O + 21]), "=f"(d[O + 22]), "=f"(d[O + 23]),
      "=f"(d[O + 24]), "=f"(d[O + 25]), "=f"(d[O + 26]), "=f"(d[O + 27]), "=f"(d[O + 28]), "=f"(d[O + 29]), "=f"(d[O + 30]), "=f"(d[O + 31])
    : "r"(a.x), "r"(a.y), "r"(a.z), "r"(a.w), "l"(db));
}
template <bool INIT, int O, int T> __device__ __forceinline__ void wgmma_n64(float (&d)[T], const uint4& a, uint64_t db) {
  if constexpr (INIT) wgmma_rs_n64_init<O>(d, a, db); else wgmma_rs_n64<O>(d, a, db);
}
template <int O, int T> __device__ __forceinline__ void wgmma_rs_n128(float (&d)[T], const uint4& a, uint64_t db) {
  asm volatile("{\n.reg .pred p;\nsetp.ne.b32 p, 1, 0;\n"
    "wgmma.mma_async.sync.aligned.m64n128k16.f32.bf16.bf16 "
    "{%0, %1, %2, %3, %4, %5, %6, %7, %8, %9, %10, %11, %12, %13, %14, %15, "
    "%16, %17, %18, %19, %20, %21, %22, %23, %24, %25, %26, %27, %28, %29, %30, %31, "
    "%32, %33, %34, %35, %36, %37, %38, %39, %40, %41, %42, %43, %44, %45, %46, %47, "
    "%48, %49, %50, %51, %52, %53, %54, %55, %56, %57, %58, %59, %60, %61, %62, %63}, "
    "{%64, %65, %66, %67}, %68, p, 1, 1, 1;\n}\n"
    : "+f"(d[O + 0]), "+f"(d[O + 1]), "+f"(d[O + 2]), "+f"(d[O + 3]), "+f"(d[O + 4]), "+f"(d[O + 5]), "+f"(d[O + 6]), "+f"(d[O + 7]),
      "+f"(d[O + 8]), "+f"(d[O + 9]), "+f"(d[O + 10]), "+f"(d[O + 11]), "+f"(d[O + 12]), "+f"(d[O + 13]), "+f"(d[O + 14]), "+f"(d[O + 15]),
      "+f"(d[O + 16]), "+f"(d[O + 17]), "+f"(d[O + 18]), "+f"(d[O + 19]), "+f"(d[O + 20]), "+f"(d[O + 21]), "+f"(d[O + 22]), "+f"(d[O + 23]),
      "+f"(d[O + 24]), "+f"(d[O + 25]), "+f"(d[O + 26]), "+f"(d[O + 27]), "+f"(d[O + 28]), "+f"(d[O + 29]), "+f"(d[O + 30]), "+f"(d[O + 31]),
      "+f"(d[O + 32]), "+f"(d[O + 33]), "+f"(d[O + 34]), "+f"(d[O + 35]), "+f"(d[O + 36]), "+f"(d[O + 37]), "+f"(d[O + 38]), "+f"(d[O + 39]),
      "+f"(d[O + 40]), "+f"(d[O + 41]), "+f"(d[O + 42]), "+f"(d[O + 43]), "+f"(d[O + 44]), "+f"(d[O + 45]), "+f"(d[O + 46]), "+f"(d[O + 47]),
      "+f"(d[O + 48]), "+f"(d[O + 49]), "+f"(d[O + 50]), "+f"(d[O + 51]), "+f"(d[O + 52]), "+f"(d[O + 53]), "+f"(d[O + 54]), "+f"(d[O + 55]),
      "+f"(d[O + 56]), "+f"(d[O + 57]), "+f"(d[O + 58]), "+f"(d[O + 59]), "+f"(d[O + 60]), "+f"(d[O + 61]), "+f"(d[O + 62]), "+f"(d[O + 63])
    : "r"(a.x), "r"(a.y), "r"(a.z), "r"(a.w), "l"(db));
}
template <int O, int T> __device__ __forceinline__ void wgmma_rs_n128_init(float (&d)[T], const uint4& a, uint64_t db) {
  asm volatile("{\n.reg .pred p;\nsetp.ne.b32 p, 0, 0;\n"
    "wgmma.mma_async.sync.aligned.m64n128k16.f32.bf16.bf16 "
    "{%0, %1, %2, %3, %4, %5, %6, %7, %8, %9, %10, %11, %12, %13, %14, %15, "
    "%16, %17, %18, %19, %20, %21, %22, %23, %24, %25, %26, %27, %28, %29, %30, %31, "
    "%32, %33, %34, %35, %36, %37, %38, %39, %40, %41, %42, %43, %44, %45, %46, %47, "
    "%48, %49, %50, %51, %52, %53, %54, %55, %56, %57, %58, %59, %60, %61, %62, %63}, "
    "{%64, %65, %66, %67}, %68, p, 1, 1, 1;\n}\n"
    : "=f"(d[O + 0]), "=f"(d[O + 1]), "=f"(d[O + 2]), "=f"(d[O + 3]), "=f"(d[O + 4]), "=f"(d[O + 5]), "=f"(d[O + 6]), "=f"(d[O + 7]),
      "=f"(d[O + 8]), "=f"(d[O + 9]), "=f"(d[O + 10]), "=f"(d[O + 11]), "=f"(d[O + 12]), "=f"(d[O + 13]), "=f"(d[O + 14]), "=f"(d[O + 15]),
      "=f"(d[O + 16]), "=f"(d[O + 17]), "=f"(d[O + 18]), "=f"(d[O + 19]), "=f"(d[O + 20]), "=f"(d[O + 21]), "=f"(d[O + 22]), "=f"(d[O + 23]),
      "=f"(d[O + 24]), "=f"(d[O + 25]), "=f"(d[O + 26]), "=f"(d[O + 27]), "=f"(d[O + 28]), "=f"(d[O + 29]), "=f"(d[O + 30]), "=f"(d[O + 31]),
      "=f"(d[O + 32]), "=f"(d[O + 33]), "=f"(d[O + 34]), "=f"(d[O + 35]), "=f"(d[O + 36]), "=f"(d[O + 37]), "=f"(d[O + 38]), "=f"(d[O + 39]),
      "=f"(d[O + 40]), "=f"(d[O + 41]), "=f"(d[O + 42]), "=f"(d[O + 43]), "=f"(d[O + 44]), "=f"(d[O + 45]), "=f"(d[O + 46]), "=f"(d[O + 47]),
      "=f"(d[O + 48]), "=f"(d[O + 49]), "=f"(d[O + 50]), "=f"(d[O + 51]), "=f"(d[O + 52]), "=f"(d[O + 53]), "=f"(d[O + 54]), "=f"(d[O + 55]),
      "=f"(d[O + 56]), "=f"(d[O + 57]), "=f"(d[O + 58]), "=f"(d[O + 59]), "=f"(d[O + 60]), "=f"(d[O + 61]), "=f"(d[O + 62]), "=f"(d[O + 63])
    : "r"(a.x), "r"(a.y), "r"(a.z), "r"(a.w), "l"(db));
}
template <bool INIT, int O, int T> __device__ __forceinline__ void wgmma_n128(float (&d)[T], const uint4& a, uint64_t db) {
  if constexpr (INIT) wgmma_rs_n128_init<O>(d, a, db); else wgmma_rs_n128<O>(d, a, db);
}
template <int O, int T> __device__ __forceinline__ void wgmma_rs_n192(float (&d)[T], const uint4& a, uint64_t db) {
  asm volatile("{\n.reg .pred p;\nsetp.ne.b32 p, 1, 0;\n"
    "wgmma.mma_async.sync.aligned.m64n192k16.f32.bf16.bf16 "
    "{%0, %1, %2, %3, %4, %5, %6, %7, %8, %9, %10, %11, %12, %13, %14, %15, "
    "%16, %17, %18, %19, %20, %21, %22, %23, %24, %25, %26, %27, %28, %29, %30, %31, "
    "%32, %33, %34, %35, %36, %37, %38, %39, %40, %41, %42, %43, %44, %45, %46, %47, "
    "%48, %49, %50, %51, %52, %53, %54, %55, %56, %57, %58, %59, %60, %61, %62, %63, "
    "%64, %65, %66, %67, %68, %69, %70, %71, %72, %73, %74, %75, %76, %77, %78, %79, "
    "%80, %81, %82, %83, %84, %85, %86, %87, %88, %89, %90, %91, %92, %93, %94, %95}, "
    "{%96, %97, %98, %99}, %100, p, 1, 1, 1;\n}\n"
    : "+f"(d[O + 0]), "+f"(d[O + 1]), "+f"(d[O + 2]), "+f"(d[O + 3]), "+f"(d[O + 4]), "+f"(d[O + 5]), "+f"(d[O + 6]), "+f"(d[O + 7]),
      "+f"(d[O + 8]), "+f"(d[O + 9]), "+f"(d[O + 10]), "+f"(d[O + 11]), "+f"(d[O + 12]), "+f"(d[O + 13]), "+f"(d[O + 14]), "+f"(d[O + 15]),
      "+f"(d[O + 16]), "+f"(d[O + 17]), "+f"(d[O + 18]), "+f"(d[O + 19]), "+f"(d[O + 20]), "+f"(d[O + 21]), "+f"(d[O + 22]), "+f"(d[O + 23]),
      "+f"(d[O + 24]), "+f"(d[O + 25]), "+f"(d[O + 26]), "+f"(d[O + 27]), "+f"(d[O + 28]), "+f"(d[O + 29]), "+f"(d[O + 30]), "+f"(d[O + 31]),
      "+f"(d[O + 32]), "+f"(d[O + 33]), "+f"(d[O + 34]), "+f"(d[O + 35]), "+f"(d[O + 36]), "+f"(d[O + 37]), "+f"(d[O + 38]), "+f"(d[O + 39]),
      "+f"(d[O + 40]), "+f"(d[O + 41]), "+f"(d[O + 42]), "+f"(d[O + 43]), "+f"(d[O + 44]), "+f"(d[O + 45]), "+f"(d[O + 46]), "+f"(d[O + 47]),
      "+f"(d[O + 48]), "+f"(d[O + 49]), "+f"(d[O + 50]), "+f"(d[O + 51]), "+f"(d[O + 52]), "+f"(d[O + 53]), "+f"(d[O + 54]), "+f"(d[O + 55]),
      "+f"(d[O + 56]), "+f"(d[O + 57]), "+f"(d[O + 58]), "+f"(d[O + 59]), "+f"(d[O + 60]), "+f"(d[O + 61]), "+f"(d[O + 62]), "+f"(d[O + 63]),
      "+f"(d[O + 64]), "+f"(d[O + 65]), "+f"(d[O + 66]), "+f"(d[O + 67]), "+f"(d[O + 68]), "+f"(d[O + 69]), "+f"(d[O + 70]), "+f"(d[O + 71]),
      "+f"(d[O + 72]), "+f"(d[O + 73]), "+f"(d[O + 74]), "+f"(d[O + 75]), "+f"(d[O + 76]), "+f"(d[O + 77]), "+f"(d[O + 78]), "+f"(d[O + 79]),
      "+f"(d[O + 80]), "+f"(d[O + 81]), "+f"(d[O + 82]), "+f"(d[O + 83]), "+f"(d[O + 84]), "+f"(d[O + 85]), "+f"(d[O + 86]), "+f"(d[O + 87]),
      "+f"(d[O + 88]), "+f"(d[O + 89]), "+f"(d[O + 90]), "+f"(d[O + 91]), "+f"(d[O + 92]), "+f"(d[O + 93]), "+f"(d[O + 94]), "+f"(d[O + 95])
    : "r"(a.x), "r"(a.y), "r"(a.z), "r"(a.w), "l"(db));
}
template <int O, int T> __device__ __forceinline__ void wgmma_rs_n192_init(float (&d)[T], const uint4& a, uint64_t db) {
  asm volatile("{\n.reg .pred p;\nsetp.ne.b32 p, 0, 0;\n"
    "wgmma.mma_async.sync.aligned.m64n192k16.f32.bf16.bf16 "
    "{%0, %1, %2, %3, %4, %5, %6, %7, %8, %9, %10, %11, %12, %13, %14, %15, "
    "%16, %17, %18, %19, %20, %21, %22, %23, %24, %25, %26, %27, %28, %29, %30, %31, "
    "%32, %33, %34, %35, %36, %37, %38, %39, %40, %41, %42, %43, %44, %45, %46, %47, "
    "%48, %49, %50, %51, %52, %53, %54, %55, %56, %57, %58, %59, %60, %61, %62, %63, "
    "%64, %65, %66, %67, %68, %69, %70, %71, %72, %73, %74, %75, %76, %77, %78, %79, "
    "%80, %81, %82, %83, %84, %85, %86, %87, %88, %89, %90, %91, %92, %93, %94, %95}, "
    "{%96, %97, %98, %99}, %100, p, 1, 1, 1;\n}\n"
    : "=f"(d[O + 0]), "=f"(d[O + 1]), "=f"(d[O + 2]), "=f"(d[O + 3]), "=f"(d[O + 4]), "=f"(d[O + 5]), "=f"(d[O + 6]), "=f"(d[O + 7]),
      "=f"(d[O + 8]), "=f"(d[O + 9]), "=f"(d[O + 10]), "=f"(d[O + 11]), "=f"(d[O + 12]), "=f"(d[O + 13]), "=f"(d[O + 14]), "=f"(d[O + 15]),
      "=f"(d[O + 16]), "=f"(d[O + 17]), "=f"(d[O + 18]), "=f"(d[O + 19]), "=f"(d[O + 20]), "=f"(d[O + 21]), "=f"(d[O + 22]), "=f"(d[O + 23]),
      "=f"(d[O + 24]), "=f"(d[O + 25]), "=f"(d[O + 26]), "=f"(d[O + 27]), "=f"(d[O + 28]), "=f"(d[O + 29]), "=f"(d[O + 30]), "=f"(d[O + 31]),
      "=f"(d[O + 32]), "=f"(d[O + 33]), "=f"(d[O + 34]), "=f"(d[O + 35]), "=f"(d[O + 36]), "=f"(d[O + 37]), "=f"(d[O + 38]), "=f"(d[O + 39]),
      "=f"(d[O + 40]), "=f"(d[O + 41]), "=f"(d[O + 42]), "=f"(d[O + 43]), "=f"(d[O + 44]), "=f"(d[O + 45]), "=f"(d[O + 46]), "=f"(d[O + 47]),
      "=f"(d[O + 48]), "=f"(d[O + 49]), "=f"(d[O + 50]), "=f"(d[O + 51]), "=f"(d[O + 52]), "=f"(d[O + 53]), "=f"(d[O + 54]), "=f"(d[O + 55]),
      "=f"(d[O + 56]), "=f"(d[O + 57]), "=f"(d[O + 58]), "=f"(d[O + 59]), "=f"(d[O + 60]), "=f"(d[O + 61]), "=f"(d[O + 62]), "=f"(d[O + 63]),
      "=f"(d[O + 64]), "=f"(d[O + 65]), "=f"(d[O + 66]), "=f"(d[O + 67]), "=f"(d[O + 68]), "=f"(d[O + 69]), "=f"(d[O + 70]), "=f"(d[O + 71]),
      "=f"(d[O + 72]), "=f"(d[O + 73]), "=f"(d[O + 74]), "=f"(d[O + 75]), "=f"(d[O + 76]), "=f"(d[O + 77]), "=f"(d[O + 78]), "=f"(d[O + 79]),
      "=f"(d[O + 80]), "=f"(d[O + 81]), "=f"(d[O + 82]), "=f"(d[O + 83]), "=f"(d[O + 84]), "=f"(d[O + 85]), "=f"(d[O + 86]), "=f"(d[O + 87]),
      "=f"(d[O + 88]), "=f"(d[O + 89]), "=f"(d[O + 90]), "=f"(d[O + 91]), "=f"(d[O + 92]), "=f"(d[O + 93]), "=f"(d[O + 94]), "=f"(d[O + 95])
    : "r"(a.x), "r"(a.y), "r"(a.z), "r"(a.w), "l"(db));
}
template <bool INIT, int O, int T> __device__ __forceinline__ void wgmma_n192(float (&d)[T], const uint4& a, uint64_t db) {
  if constexpr (INIT) wgmma_rs_n192_init<O>(d, a, db); else wgmma_rs_n192<O>(d, a, db);
}
template <int O, int T> __device__ __forceinline__ void wgmma_rs_n256(float (&d)[T], const uint4& a, uint64_t db) {
  asm volatile("{\n.reg .pred p;\nsetp.ne.b32 p, 1, 0;\n"
    "wgmma.mma_async.sync.aligned.m64n256k16.f32.bf16.bf16 "
    "{%0, %1, %2, %3, %4, %5, %6, %7, %8, %9, %10, %11, %12, %13, %14, %15, "
    "%16, %17, %18, %19, %20, %21, %22, %23, %24, %25, %26, %27, %28, %29, %30, %31, "
    "%32, %33, %34, %35, %36, %37, %38, %39, %40, %41, %42, %43, %44, %45, %46, %47, "
    "%48, %49, %50, %51, %52, %53, %54, %55, %56, %57, %58, %59, %60, %61, %62, %63, "
    "%64, %65, %66, %67, %68, %69, %70, %71, %72, %73, %74, %75, %76, %77, %78, %79, "
    "%80, %81, %82, %83, %84, %85, %86, %87, %88, %89, %90, %91, %92, %93, %94, %95, "
    "%96, %97, %98, %99, %100, %101, %102, %103, %104, %105, %106, %107, %108, %109, %110, %111, "
    "%112, %113, %114, %115, %116, %117, %118, %119, %120, %121, %122, %123, %124, %125, %126, %127}, "
    "{%128, %129, %130, %131}, %132, p, 1, 1, 1;\n}\n"
    : "+f"(d[O + 0]), "+f"(d[O + 1]), "+f"(d[O + 2]), "+f"(d[O + 3]), "+f"(d[O + 4]), "+f"(d[O + 5]), "+f"(d[O + 6]), "+f"(d[O + 7]),
      "+f"(d[O + 8]), "+f"(d[O + 9]), "+f"(d[O + 10]), "+f"(d[O + 11]), "+f"(d[O + 12]), "+f"(d[O + 13]), "+f"(d[O + 14]), "+f"(d[O + 15]),
      "+f"(d[O + 16]), "+f"(d[O + 17]), "+f"(d[O + 18]), "+f"(d[O + 19]), "+f"(d[O + 20]), "+f"(d[O + 21]), "+f"(d[O + 22]), "+f"(d[O + 23]),
      "+f"(d[O + 24]), "+f"(d[O + 25]), "+f"(d[O + 26]), "+f"(d[O + 27]), "+f"(d[O + 28]), "+f"(d[O + 29]), "+f"(d[O + 30]), "+f"(d[O + 31]),
      "+f"(d[O + 32]), "+f"(d[O + 33]), "+f"(d[O + 34]), "+f"(d[O + 35]), "+f"(d[O + 36]), "+f"(d[O + 37]), "+f"(d[O + 38]), "+f"(d[O + 39]),
      "+f"(d[O + 40]), "+f"(d[O + 41]), "+f"(d[O + 42]), "+f"(d[O + 43]), "+f"(d[O + 44]), "+f"(d[O + 45]), "+f"(d[O + 46]), "+f"(d[O + 47]),
      "+f"(d[O + 48]), "+f"(d[O + 49]), "+f"(d[O + 50]), "+f"(d[O + 51]), "+f"(d[O + 52]), "+f"(d[O + 53]), "+f"(d[O + 54]), "+f"(d[O + 55]),
      "+f"(d[O + 56]), "+f"(d[O + 57]), "+f"(d[O + 58]), "+f"(d[O + 59]), "+f"(d[O + 60]), "+f"(d[O + 61]), "+f"(d[O + 62]), "+f"(d[O + 63]),
      "+f"(d[O + 64]), "+f"(d[O + 65]), "+f"(d[O + 66]), "+f"(d[O + 67]), "+f"(d[O + 68]), "+f"(d[O + 69]), "+f"(d[O + 70]), "+f"(d[O + 71]),
      "+f"(d[O + 72]), "+f"(d[O + 73]), "+f"(d[O + 74]), "+f"(d[O + 75]), "+f"(d[O + 76]), "+f"(d[O + 77]), "+f"(d[O + 78]), "+f"(d[O + 79]),
      "+f"(d[O + 80]), "+f"(d[O + 81]), "+f"(d[O + 82]), "+f"(d[O + 83]), "+f"(d[O + 84]), "+f"(d[O + 85]), "+f"(d[O + 86]), "+f"(d[O + 87]),
      "+f"(d[O + 88]), "+f"(d[O + 89]), "+f"(d[O + 90]), "+f"(d[O + 91]), "+f"(d[O + 92]), "+f"(d[O + 93]), "+f"(d[O + 94]), "+f"(d[O + 95]),
      "+f"(d[O + 96]), "+f"(d[O + 97]), "+f"(d[O + 98]), "+f"(d[O + 99]), "+f"(d[O + 100]), "+f"(d[O + 101]), "+f"(d[O + 102]), "+f"(d[O + 103]),
      "+f"(d[O + 104]), "+f"(d[O + 105]), "+f"(d[O + 106]), "+f"(d[O + 107]), "+f"(d[O + 108]), "+f"(d[O + 109]), "+f"(d[O + 110]), "+f"(d[O + 111]),
      "+f"(d[O + 112]), "+f"(d[O + 113]), "+f"(d[O + 114]), "+f"(d[O + 115]), "+f"(d[O + 116]), "+f"(d[O + 117]), "+f"(d[O + 118]), "+f"(d[O + 119]),
      "+f"(d[O + 120]), "+f"(d[O + 121]), "+f"(d[O + 122]), "+f"(d[O + 123]), "+f"(d[O + 124]), "+f"(d[O + 125]), "+f"(d[O + 126]), "+f"(d[O + 127])
    : "r"(a.x), "r"(a.y), "r"(a.z), "r"(a.w), "l"(db));
}
template <int O, int T> __device__ __forceinline__ void wgmma_rs_n256_init(float (&d)[T], const uint4& a, uint64_t db) {
  asm volatile("{\n.reg .pred p;\nsetp.ne.b32 p, 0, 0;\n"
    "wgmma.mma_async.sync.aligned.m64n256k16.f32.bf16.bf16 "
    "{%0, %1, %2, %3, %4, %5, %6, %7, %8, %9, %10, %11, %12, %13, %14, %15, "
    "%16, %17, %18, %19, %20, %21, %22, %23, %24, %25, %26, %27, %28, %29, %30, %31, "
    "%32, %33, %34, %35, %36, %37, %38, %39, %40, %41, %42, %43, %44, %45, %46, %47, "
    "%48, %49, %50, %51, %52, %53, %54, %55, %56, %57, %58, %59, %60, %61, %62, %63, "
    "%64, %65, %66, %67, %68, %69, %70, %71, %72, %73, %74, %75, %76, %77, %78, %79, "
    "%80, %81, %82, %83, %84, %85, %86, %87, %88, %89, %90, %91, %92, %93, %94, %95, "
    "%96, %97, %98, %99, %100, %101, %102, %103, %104, %105, %106, %107, %108, %109, %110, %111, "
    "%112, %113, %114, %115, %116, %117, %118, %119, %120, %121, %122, %123, %124, %125, %126, %127}, "
    "{%128, %129, %130, %131}, %132, p, 1, 1, 1;\n}\n"
    : "=f"(d[O + 0]), "=f"(d[O + 1]), "=f"(d[O + 2]), "=f"(d[O + 3]), "=f"(d[O + 4]), "=f"(d[O + 5]), "=f"(d[O + 6]), "=f"(d[O + 7]),
      "=f"(d[O + 8]), "=f"(d[O + 9]), "=f"(d[O + 10]), "=f"(d[O + 11]), "=f"(d[O + 12]), "=f"(d[O + 13]), "=f"(d[O + 14]), "=f"(d[O + 15]),
      "=f"(d[O + 16]), "=f"(d[O + 17]), "=f"(d[O + 18]), "=f"(d[O + 19]), "=f"(d[O + 20]), "=f"(d[O + 21]), "=f"(d[O + 22]), "=f"(d[O + 23]),
      "=f"(d[O + 24]), "=f"(d[O + 25]), "=f"(d[O + 26]), "=f"(d[O + 27]), "=f"(d[O + 28]), "=f"(d[O + 29]), "=f"(d[O + 30]), "=f"(d[O + 31]),
      "=f"(d[O + 32]), "=f"(d[O + 33]), "=f"(d[O + 34]), "=f"(d[O + 35]), "=f"(d[O + 36]), "=f"(d[O + 37]), "=f"(d[O + 38]), "=f"(d[O + 39]),
      "=f"(d[O + 40]), "=f"(d[O + 41]), "=f"(d[O + 42]), "=f"(d[O + 43]), "=f"(d[O + 44]), "=f"(d[O + 45]), "=f"(d[O + 46]), "=f"(d[O + 47]),
      "=f"(d[O + 48]), "=f"(d[O + 49]), "=f"(d[O + 50]), "=f"(d[O + 51]), "=f"(d[O + 52]), "=f"(d[O + 53]), "=f"(d[O + 54]), "=f"(d[O + 55]),
      "=f"(d[O + 56]), "=f"(d[O + 57]), "=f"(d[O + 58]), "=f"(d[O + 59]), "=f"(d[O + 60]), "=f"(d[O + 61]), "=f"(d[O + 62]), "=f"(d[O + 63]),
      "=f"(d[O + 64]), "=f"(d[O + 65]), "=f"(d[O + 66]), "=f"(d[O + 67]), "=f"(d[O + 68]), "=f"(d[O + 69]), "=f"(d[O + 70]), "=f"(d[O + 71]),
      "=f"(d[O + 72]), "=f"(d[O + 73]), "=f"(d[O + 74]), "=f"(d[O + 75]), "=f"(d[O + 76]), "=f"(d[O + 77]), "=f"(d[O + 78]), "=f"(d[O + 79]),
      "=f"(d[O + 80]), "=f"(d[O + 81]), "=f"(d[O + 82]), "=f"(d[O + 83]), "=f"(d[O + 84]), "=f"(d[O + 85]), "=f"(d[O + 86]), "=f"(d[O + 87]),
      "=f"(d[O + 88]), "=f"(d[O + 89]), "=f"(d[O + 90]), "=f"(d[O + 91]), "=f"(d[O + 92]), "=f"(d[O + 93]), "=f"(d[O + 94]), "=f"(d[O + 95]),
      "=f"(d[O + 96]), "=f"(d[O + 97]), "=f"(d[O + 98]), "=f"(d[O + 99]), "=f"(d[O + 100]), "=f"(d[O + 101]), "=f"(d[O + 102]), "=f"(d[O + 103]),
      "=f"(d[O + 104]), "=f"(d[O + 105]), "=f"(d[O + 106]), "=f"(d[O + 107]), "=f"(d[O + 108]), "=f"(d[O + 109]), "=f"(d[O + 110]), "=f"(d[O + 111]),
      "=f"(d[O + 112]), "=f"(d[O + 113]), "=f"(d[O + 114]), "=f"(d[O + 115]), "=f"(d[O + 116]), "=f"(d[O + 117]), "=f"(d[O + 118]), "=f"(d[O + 119]),
      "=f"(d[O + 120]), "=f"(d[O + 121]), "=f"(d[O + 122]), "=f"(d[O + 123]), "=f"(d[O + 124]), "=f"(d[O + 125]), "=f"(d[O + 126]), "=f"(d[O + 127])
    : "r"(a.x), "r"(a.y), "r"(a.z), "r"(a.w), "l"(db));
}
template <bool INIT, int O, int T> __device__ __forceinline__ void wgmma_n256(float (&d)[T], const uint4& a, uint64_t db) {
  if constexpr (INIT) wgmma_rs_n256_init<O>(d, a, db); else wgmma_rs_n256<O>(d, a, db);
}

template <int N> __device__ __forceinline__ void load_pk(uint4* a, const uint4* p) {
#pragma unroll
  for (int i = 0; i < N; i++) a[i] = ld_ll(p + i * 32);
}
__device__ __forceinline__ uint32_t xor_or(uint32_t a, uint32_t b, uint32_t t) {
  uint32_t r;
  asm("lop3.b32 %0, %1, %2, %3, 0x7E;" : "=r"(r) : "r"(a), "r"(b), "r"(t));
  return r;
}
template <int N> __device__ __forceinline__ bool ok_pk(const uint4* a, uint32_t tag) {
  static_assert(N % 2 == 0, "");
  uint32_t x = xor_or(a[0].x, a[1].x, tag);
#pragma unroll
  for (int i = 2; i < N; i += 2) x |= xor_or(a[i].x, a[i + 1].x, tag);
  return __all_sync(0xffffffffu, (x & 1u) == 0u);
}
template <int N> __device__ __forceinline__ void ensure_pk(uint4* a, const uint4* p, uint32_t tag) {
  if (ok_pk<N>(a, tag)) return;
  uint32_t n = 0;
  do { load_pk<N>(a, p); } while (!ok_pk<N>(a, tag) && ++n < SPIN_LIMIT);
}

constexpr int NSTAGE = 44;
constexpr int ST_WO = 8, ST_G1 = 12, ST_G2 = 20, ST_DN = 28;
__host__ __device__ constexpr int st_len(int s) { return s < ST_WO ? 3 : s < ST_G1 ? 2 : s < ST_G2 ? 4 : s < ST_DN ? 3 : 2; }
__host__ __device__ constexpr int st_g0(int s) {
  int pos = 0, g0 = 0;
  for (int i = 0; i <= s; i++) {
    if (pos + st_len(i) > NGRAN) pos = 0;
    g0 = pos;
    pos += st_len(i);
  }
  return g0;
}
__host__ __device__ constexpr int cnt_first(int g, int s) {
  int n = 0;
  for (int i = 0; i < s; i++) n += (st_g0(i) == g);
  return n;
}
__host__ __device__ constexpr int cnt_cover(int g, int s) {
  int n = 0;
  for (int i = 0; i < s; i++) n += (g >= st_g0(i) && g < st_g0(i) + st_len(i));
  return n;
}
__host__ __device__ constexpr uint32_t flip_mask(int s0, int s1) {
  uint32_t m = 0;
  for (int i = s0; i < s1; i++) m ^= ((1u << st_len(i)) - 1u) << st_g0(i);
  return m;
}
__host__ __device__ constexpr int dn_q(int i) { return i < 3 ? 0 : i < 6 ? 1 : i == 6 ? 0 : i == 7 ? 1 : i < 12 ? 2 : 3; }
__host__ __device__ constexpr int dn_par(int i) { return i < 8 ? (i == 2 || i == 4 || i >= 6) : (i & 1); }
__host__ __device__ constexpr int dn_kh(int i) { return i < 8 ? (i == 1 || i >= 5) : ((i & 3) >= 2); }
template <int I> struct IC { static constexpr int value = I; };
template <int B, int E, typename F> __device__ __forceinline__ void static_for(F&& f) {
  if constexpr (B < E) { f(IC<B>{}); static_for<B + 1, E>(f); }
}
template <int S> __device__ __forceinline__ void cons_acquire(uint32_t sbase, uint32_t L) {
  constexpr int g0 = st_g0(S);
  constexpr uint32_t p0 = cnt_first(g0, S) & 1, odd = cnt_first(g0, NSTAGE) & 1;
  mbar_wait(sbase + SM_MISC + BAR_FULL + 8 * g0, p0 ^ (L & odd));
}
template <int S> __device__ __forceinline__ bool cons_probe(uint32_t sbase, uint32_t L) {
  constexpr int g0 = st_g0(S);
  constexpr uint32_t p0 = cnt_first(g0, S) & 1, odd = cnt_first(g0, NSTAGE) & 1;
  return mbar_test(sbase + SM_MISC + BAR_FULL + 8 * g0, p0 ^ (L & odd));
}
template <int S> __device__ __forceinline__ void cons_release(uint32_t sbase, int lane) {
  if (lane < st_len(S)) mbar_arrive(sbase + SM_MISC + BAR_EMPTY + 8 * st_g0(S) + 8 * lane);
}
__device__ __forceinline__ bool elect_one() {
  uint32_t p;
  asm volatile("{\n.reg .pred P;\nelect.sync _|P, 0xffffffff;\nselp.u32 %0, 1, 0, P;\n}" : "=r"(p));
  return p != 0;
}
struct ProdRing { uint32_t pos, par; };
template <int N> __device__ __forceinline__ uint32_t prod_acquire(uint32_t sbase, ProdRing& r) {
  if (r.pos + N > NGRAN) r.pos = 0;
  const uint32_t g0 = r.pos;
#pragma unroll
  for (uint32_t i = 0; i < N; i++) mbar_wait(sbase + SM_MISC + BAR_EMPTY + 8 * (g0 + i), ((r.par >> (g0 + i)) & 1u) ^ 1u);
  r.par ^= ((1u << N) - 1u) << g0;
  r.pos = g0 + N;
  return g0;
}
template <int S> __device__ __forceinline__ void prod_acquire_static(uint32_t sbase, uint32_t L) {
  constexpr int g0 = st_g0(S);
  static_for<0, st_len(S)>([&](auto I) {
    constexpr int g = g0 + I.value;
    constexpr uint32_t p0 = cnt_cover(g, S) & 1, odd = cnt_cover(g, NSTAGE) & 1;
    mbar_wait(sbase + SM_MISC + BAR_EMPTY + 8 * g, p0 ^ (L & odd) ^ 1u);
  });
}
template <int S, int KSTEP_BYTES, int LBO, int SBO, int SWZ> __device__ __forceinline__ constexpr uint64_t st_desc(int k) {
  return (uint64_t)((SMEM_ORIGIN + st_g0(S) * GRAN + k * KSTEP_BYTES) >> 4) | ((uint64_t)(LBO >> 4) << 16) |
         ((uint64_t)(SBO >> 4) << 32) | ((uint64_t)SWZ << 62);
}

__device__ __forceinline__ void combine_stats(const uint4& p0, const uint4& p1, float& mean_lo, float& rstd_lo, float& mean_hi, float& rstd_hi) {
  float m0 = __uint_as_float(p0.x), q0 = __uint_as_float(p0.y), m0h = __uint_as_float(p0.z), q0h = __uint_as_float(p0.w);
  float m1 = __uint_as_float(p1.x), q1 = __uint_as_float(p1.y), m1h = __uint_as_float(p1.z), q1h = __uint_as_float(p1.w);
  float s = m0 + m1, sh = m0h + m1h;
  s += __shfl_xor_sync(0xffffffffu, s, 1); sh += __shfl_xor_sync(0xffffffffu, sh, 1);
  s += __shfl_xor_sync(0xffffffffu, s, 2); sh += __shfl_xor_sync(0xffffffffu, sh, 2);
  mean_lo = s * 0.125f; mean_hi = sh * 0.125f;
  float d0 = m0 - mean_lo, d1 = m1 - mean_lo, d0h = m0h - mean_hi, d1h = m1h - mean_hi;
  float t = q0 + q1 + 64.f * (d0 * d0 + d1 * d1), th = q0h + q1h + 64.f * (d0h * d0h + d1h * d1h);
  t += __shfl_xor_sync(0xffffffffu, t, 1); th += __shfl_xor_sync(0xffffffffu, th, 1);
  t += __shfl_xor_sync(0xffffffffu, t, 2); th += __shfl_xor_sync(0xffffffffu, th, 2);
  rstd_lo = rsqrtf(t * (1.f / 512.f) + 1e-5f);
  rstd_hi = rsqrtf(th * (1.f / 512.f) + 1e-5f);
}
__device__ __forceinline__ uint4 local_stats(const float (&v)[32]) {
  float s = 0.f, sh = 0.f;
#pragma unroll
  for (int i = 0; i < 4; i++) {
    s += (v[8 * i + 0] + v[8 * i + 1]) + (v[8 * i + 4] + v[8 * i + 5]);
    sh += (v[8 * i + 2] + v[8 * i + 3]) + (v[8 * i + 6] + v[8 * i + 7]);
  }
  s += __shfl_xor_sync(0xffffffffu, s, 1); sh += __shfl_xor_sync(0xffffffffu, sh, 1);
  s += __shfl_xor_sync(0xffffffffu, s, 2); sh += __shfl_xor_sync(0xffffffffu, sh, 2);
  float m = s * (1.f / 64.f), mh = sh * (1.f / 64.f);
  float q = 0.f, qh = 0.f;
#pragma unroll
  for (int i = 0; i < 4; i++) {
    float a = v[8 * i + 0] - m, b = v[8 * i + 1] - m, c = v[8 * i + 4] - m, d = v[8 * i + 5] - m;
    q += (a * a + b * b) + (c * c + d * d);
    float e = v[8 * i + 2] - mh, f = v[8 * i + 3] - mh, g = v[8 * i + 6] - mh, h = v[8 * i + 7] - mh;
    qh += (e * e + f * f) + (g * g + h * h);
  }
  q += __shfl_xor_sync(0xffffffffu, q, 1); qh += __shfl_xor_sync(0xffffffffu, qh, 1);
  q += __shfl_xor_sync(0xffffffffu, q, 2); qh += __shfl_xor_sync(0xffffffffu, qh, 2);
  return make_uint4(__float_as_uint(m), __float_as_uint(q), __float_as_uint(mh), __float_as_uint(qh));
}

__device__ __forceinline__ int slab_row0(int c, int g, int w) { return 1024 * g + 64 * c + 32 * (w >> 1) + (w & 1); }

__device__ __forceinline__ void owner_ln_publish(uint32_t sbase, const float (&v)[32], uint32_t tphase, uint32_t tag_xn) {
  PHASE_VARS;
  const uint32_t bars = sbase + SM_MISC;
  const int oslab = 4 * g + ca;
  const int step0 = 16 * cbit + 4 * w;
  TS(40 + 4 * tphase);
  uint4 st = local_stats(v);
  const uint32_t tb = bars + BAR_TSTAT + 8 * g;
  const uint32_t slot = sbase + SM_TSTAT + g * 1024 + (4 * cbit + w) * 128 + qr * 16;
  if (t128 == 0) mbar_expect_tx(tb, 1024);
  if (qc == 0) {
    st_async128(mapa(slot, 0), st, mapa(tb, 0));
    st_async128(mapa(slot, 1), st, mapa(tb, 1));
  }
  uint4* xn = g_xn + ((c * 8 + oslab) * 32 + step0) * 32 + lane;
  uint4* xr = g_xraw + ((c * 8 + oslab) * 32 + step0) * 32 + lane;
  TS(41 + 4 * tphase);
  mbar_wait(tb, tphase);
  TS(42 + 4 * tphase);
  const uint32_t rd = sbase + SM_TSTAT + g * 1024 + qc * 256 + qr * 16;
  uint4 p0 = lds128(rd), p1 = lds128(rd + 128);
  float ml, rl, mh, rh;
  combine_stats(p0, p1, ml, rl, mh, rh);
  const float bl = -ml * rl, bh = -mh * rh;
#pragma unroll
  for (int i = 0; i < 4; i++) {
    uint4 o;
    o.x = set_tag(pack2(fmaf(v[8 * i + 0], rl, bl), fmaf(v[8 * i + 1], rl, bl)), tag_xn);
    o.y = pack2(fmaf(v[8 * i + 2], rh, bh), fmaf(v[8 * i + 3], rh, bh));
    o.z = pack2(fmaf(v[8 * i + 4], rl, bl), fmaf(v[8 * i + 5], rl, bl));
    o.w = pack2(fmaf(v[8 * i + 6], rh, bh), fmaf(v[8 * i + 7], rh, bh));
    st_ll(xn + i * 32, o);
  }
#pragma unroll
  for (int i = 0; i < 4; i++) {
    uint4 o;
    o.x = set_tag(pack2(v[8 * i + 0], v[8 * i + 1]), 1u);
    o.y = pack2(v[8 * i + 2], v[8 * i + 3]);
    o.z = pack2(v[8 * i + 4], v[8 * i + 5]);
    o.w = pack2(v[8 * i + 6], v[8 * i + 7]);
    st_ll(xr + i * 32, o);
  }
}

__device__ __forceinline__ uint4 pack8(const float* a) {
  return make_uint4(pack2(a[0], a[1]), pack2(a[2], a[3]), pack2(a[4], a[5]), pack2(a[6], a[7]));
}
template <int U> __device__ __forceinline__ uint4 glu8(const float* g, float cl, float ch) {
  return make_uint4(pack2(g[0] * cl * g[U], g[1] * cl * g[U + 1]), pack2(g[2] * ch * g[U + 2], g[3] * ch * g[U + 3]),
                    pack2(g[4] * cl * g[U + 4], g[5] * cl * g[U + 5]), pack2(g[6] * ch * g[U + 6], g[7] * ch * g[U + 7]));
}
__device__ __forceinline__ uint32_t hfma2(uint32_t a, uint32_t b, uint32_t c) {
  uint32_t d;
  asm("fma.rn.bf16x2 %0, %1, %2, %3;" : "=r"(d) : "r"(a), "r"(b), "r"(c));
  return d;
}
__device__ __forceinline__ void keep4(const uint4 (&a)[4]) { keep(a[0]); keep(a[1]); keep(a[2]); keep(a[3]); }

#define STAGGER 0

__global__ void __launch_bounds__(NTHREADS, 1)
fused_kernel(const __grid_constant__ CUtensorMap m_qkv, const __grid_constant__ CUtensorMap m_wo,
             const __grid_constant__ CUtensorMap m_gu2, const __grid_constant__ CUtensorMap m_gu1,
             const __grid_constant__ CUtensorMap m_guh, const __grid_constant__ CUtensorMap m_wd112,
             const __grid_constant__ CUtensorMap m_wd80, const __grid_constant__ CUtensorMap m_wd32,
             const __nv_bfloat16* __restrict__ x_in,
             __nv_bfloat16* __restrict__ out, const char* __restrict__ w_o, const char* __restrict__ w_g,
             const char* __restrict__ w_u, const char* __restrict__ w_d
) {
  extern __shared__ __align__(1024) unsigned char smem_raw[];
  const uint32_t sbase = smem_u32(smem_raw);
  const uint32_t bars = sbase + SM_MISC;
  if ((sbase & 0xFFFFFFu) != SMEM_ORIGIN) return;
  TG(60);

  if (threadIdx.x == 0) {
    for (int i = 0; i < NGRAN; i++) { mbar_init(bars + BAR_FULL + 8 * i, 1); mbar_init(bars + BAR_EMPTY + 8 * i, 8); }
    for (int i = 0; i < 4; i++) mbar_init(bars + BAR_HRECV + 8 * i, 1);
    for (int i = 0; i < 2; i++) { mbar_init(bars + BAR_HREADY + 8 * i, 4); mbar_init(bars + BAR_TSTAT + 8 * i, 1); }
    asm volatile("fence.mbarrier_init.release.cluster;" ::: "memory");
  }
  __syncthreads();
  asm volatile("barrier.cluster.arrive.release.aligned;" ::: "memory");

  if (threadIdx.x >= 256) {
    asm volatile("setmaxnreg.dec.sync.aligned.u32 40;");
    const int warp = threadIdx.x >> 5, lane = threadIdx.x & 31;
    const int j = blockIdx.x & 7, b = j & 1;
    if (warp == 8) {
      ProdRing r{0u, 0u};
      const int cb0 = 224 * j + 32 * b, hb0 = 224 * j + 192 * (b ^ 1);
      const int jp = j ^ 1, cbp = 224 * jp + 32 * (b ^ 1), hbp = 224 * jp + 192 * b;
#pragma unroll 1
      for (uint32_t L = 0; L < 2; L++) {
        r.pos = 0;
        PSTOP_AT(L == 0 ? 0 : 3);
#pragma unroll 1
        for (int kb = 0; kb < 8; kb++) {
          const uint32_t g0 = prod_acquire<3>(sbase, r);
          if (elect_one()) {
            mbar_expect_tx(bars + BAR_FULL + 8 * g0, 24576);
            tma_3d(sbase + g0 * GRAN, &m_qkv, bars + BAR_FULL + 8 * g0, 64 * j, 64 * kb, 0);
          }
        }
        PSTOP_AT(10 * L + 1);
#pragma unroll 1
        for (int i = 0; i < 4; i++) {
          const uint32_t g0 = prod_acquire<2>(sbase, r);
          if (elect_one()) {
            mbar_expect_tx(bars + BAR_FULL + 8 * g0, 16384);
            tma_2d(sbase + g0 * GRAN, &m_wo, bars + BAR_FULL + 8 * g0, 64 * j, 128 * i);
          }
        }
        PSTOP_AT(10 * L + 2);
#pragma unroll 1
        for (int kb = 0; kb < 8; kb++) {
          const uint32_t g0 = prod_acquire<4>(sbase, r);
          if (elect_one()) {
            mbar_expect_tx(bars + BAR_FULL + 8 * g0, 32768);
            tma_4d(sbase + g0 * GRAN, &m_gu2, bars + BAR_FULL + 8 * g0, cb0, 64 * kb, 0, 0);
          }
        }
#pragma unroll 1
        for (int kb = 0; kb < 8; kb++) {
          const uint32_t g0 = prod_acquire<3>(sbase, r);
          if (elect_one()) {
            mbar_expect_tx(bars + BAR_FULL + 8 * g0, 24576);
            tma_4d(sbase + g0 * GRAN, &m_gu1, bars + BAR_FULL + 8 * g0, cb0 + 128, 64 * kb, 0, 0);
            tma_3d(sbase + g0 * GRAN + 16384, &m_guh, bars + BAR_FULL + 8 * g0, hb0, 64 * kb, 0);
          }
        }
        static_for<0, 16>([&](auto I) {
          constexpr int i = I.value, g0 = st_g0(ST_DN + i);
          prod_acquire_static<ST_DN + i>(sbase, L);
          if (elect_one()) {
            const uint32_t dst = sbase + g0 * GRAN, fb = bars + BAR_FULL + 8 * g0;
            const int n0 = 256 * b + 64 * dn_q(i);
            mbar_expect_tx(fb, 14336);
            if constexpr (dn_kh(i) == 0) {
              tma_2d(dst, &m_wd112, fb, n0, dn_par(i) ? cbp : cb0);
            } else {
              tma_2d(dst, &m_wd80, fb, n0, (dn_par(i) ? cbp : cb0) + 112);
              tma_2d(dst + 10240, &m_wd32, fb, n0, dn_par(i) ? hbp : hb0);
            }
          }
        });
        r.par ^= flip_mask(ST_DN, NSTAGE);
      }
    } else if (warp == 9) {
      const int cta = blockIdx.x;
      if (lane == 0) l2_prefetch(w_o + cta * 4096, 4096);
      if (lane == 1) l2_prefetch(w_g + cta * 14336, 14336);
      if (lane == 2) l2_prefetch(w_u + cta * 14336, 14336);
      if (lane == 3) l2_prefetch(w_d + cta * 14336, 14336);
    }
    __syncwarp();
    asm volatile("barrier.cluster.wait.acquire.aligned; // producer" ::: "memory");
    asm volatile("barrier.cluster.arrive.release.aligned;\nbarrier.cluster.wait.acquire.aligned; // producer" ::: "memory");
  } else {
    asm volatile("setmaxnreg.inc.sync.aligned.u32 232;");
    TS(0);
    TG(61);

    {
      PHASE_VARS;
      const int step0 = 16 * cbit + 4 * w;
      float v[32];
      const uint32_t* xp = reinterpret_cast<const uint32_t*>(x_in + (size_t)(slab_row0(c, g, ca) + 2 * qr) * 512 + step0 * 16 + qc * 2);
      uint32_t xw[16];
#pragma unroll
      for (int i = 0; i < 4; i++) {
        xw[4 * i] = __ldg(xp + i * 8); xw[4 * i + 1] = __ldg(xp + 16 * 256 + i * 8);
        xw[4 * i + 2] = __ldg(xp + i * 8 + 4); xw[4 * i + 3] = __ldg(xp + 16 * 256 + i * 8 + 4);
      }
      asm volatile("barrier.cluster.wait.acquire.aligned; // consumer" ::: "memory");
      if (STAGGER > 0 && g == 1) {
        const long long t0 = clock64();
        while (clock64() - t0 < STAGGER) {}
      }
#pragma unroll
      for (int i = 0; i < 16; i++) { v[2 * i] = bf_lo(xw[i]); v[2 * i + 1] = bf_hi(xw[i]); }
      owner_ln_publish(sbase, v, 0u, 1u);
    }
    STOP_AT(0);
    TS(1);

#pragma unroll 1
    for (uint32_t L = 0; L < 2; L++) {
      const uint32_t tag = L ^ 1;
      {
        PHASE_VARS;
        uint4 qf[4], kf[4], vf[4], pp[4];
        const int blk = 16 * g + c;
        const uint4* halo_src = g_halo + ((((L * 32 + (blk > 0 ? blk - 1 : 0)) * 8 + j) * 2 + (w & 1)) * 4) * 32 + lane;
        {
          float acc[96];
          uint4 A[3][4];
          const uint4* xs = g_xn + ((c * 8 + slab) * 32) * 32 + lane;
          bar_wg(1 + g);
          load_pk<4>(A[0], xs);
          ensure_pk<4>(A[0], xs, tag);
          TS(2 + 20 * L);
          load_pk<4>(A[1], xs + 128);
          cons_acquire<0>(sbase, L);
          static_for<0, 8>([&](auto I) {
            constexpr int kb = I.value;
            wg_fence();
            static_for<0, 4>([&](auto K) { constexpr int k = K.value; wgmma_n192<kb == 0 && k == 0, 0>(acc, A[kb % 3][k], st_desc<kb, 2048, 8192, 1024, 1>(k)); });
            wg_commit();
            bool full = true;
            if constexpr (kb + 1 < 8) full = cons_probe<kb + 1>(sbase, L);
            if constexpr (kb > 0) {
              wg_wait<1>();
              keep4(A[(kb + 2) % 3]);
              cons_release<kb - 1>(sbase, lane);
            }
            if constexpr (kb + 1 < 8) {
              const bool ok = ok_pk<4>(A[(kb + 1) % 3], tag);
              if (!(ok && full)) { ensure_pk<4>(A[(kb + 1) % 3], xs + (kb + 1) * 128, tag); cons_acquire<kb + 1>(sbase, L); }
            }
            if constexpr (kb + 2 < 8) load_pk<4>(A[(kb + 2) % 3], xs + (kb + 2) * 128);
          });
          wg_wait<0>();
          TS(3 + 20 * L);
          fence_acc(acc);
          keep4(A[1]);
          cons_release<7>(sbase, lane);
#pragma unroll
          for (int h = 0; h < 4; h++) {
            kf[h] = pack8(&acc[32 + 8 * h]);
            const uint4 t = pack8(&acc[64 + 8 * h]);
            vf[h] = make_uint4(movm(t.x), movm(t.y), movm(t.z), movm(t.w));
            pp[h] = make_uint4(kf[h].y, kf[h].w, vf[h].y, vf[h].w);
          }
          if (w >= 2 && blk < 31) {
            uint4* hd = g_halo + ((((L * 32 + blk) * 8 + j) * 2 + (w & 1)) * 4) * 32 + lane;
#pragma unroll
            for (int h = 0; h < 4; h++) { uint4 t = pp[h]; t.x |= 1u; st_ll(hd + h * 32, t); }
          }
#pragma unroll
          for (int h = 0; h < 4; h++) sts128(areg + (28 + h) * 2048 + t128 * 16, pp[h]);
          if (w < 2 && blk > 0) load_pk<4>(pp, halo_src);
#pragma unroll
          for (int h = 0; h < 4; h++) qf[h] = pack8(&acc[8 * h]);
        }
        bar_wg(1 + g);
        const bool first = (w < 2) && (blk == 0);
        if (w >= 2) {
#pragma unroll
          for (int h = 0; h < 4; h++) pp[h] = lds128(areg + (28 + h) * 2048 + (t128 - 64) * 16);
        }
        bar_wg(1 + g);
        if (w < 2 && blk > 0) {
          ensure_pk<4>(pp, halo_src, 1u);
          uint4* hz = const_cast<uint4*>(halo_src);
#pragma unroll
          for (int h = 0; h < 4; h++) st_ll(hz + h * 32, make_uint4(0, 0, 0, 0));
        }
        TS(4 + 20 * L);
        const bool n0 = 2 * qc <= qr, n1 = 2 * qc + 1 <= qr;
        const uint32_t msk = (n0 ? 0xffffu : 0u) | (n1 ? 0xffff0000u : 0u);
        const float sc = 0.25f * 1.4426950408889634f;
        const float NEG = -1e30f;
        uint4* od = g_o + ((c * 8 + slab) * 32 + 4 * j) * 32 + lane;
        float l0[4], l1[4], h0[4], h1[4], ml[4], mh[4];
#pragma unroll
        for (int h = 0; h < 4; h++) {
          float sp[4], s0[4], s1[4];
          mma16816_z(sp, qf[h], pp[h].x, pp[h].y);
          mma16816_z(s0, qf[h], kf[h].x, kf[h].z);
          mma16816_z(s1, qf[h], kf[h].y, kf[h].w);
          if (first) { sp[0] = NEG; sp[1] = NEG; }
          l0[h] = n0 ? s0[0] : sp[0]; l1[h] = n1 ? s0[1] : sp[1];
          h0[h] = n0 ? s1[2] : s0[2]; h1[h] = n1 ? s1[3] : s0[3];
          ml[h] = fmaxf(l0[h], l1[h]); mh[h] = fmaxf(h0[h], h1[h]);
        }
#pragma unroll
        for (int h = 0; h < 4; h++) { ml[h] = fmaxf(ml[h], __shfl_xor_sync(0xffffffffu, ml[h], 1)); mh[h] = fmaxf(mh[h], __shfl_xor_sync(0xffffffffu, mh[h], 1)); }
#pragma unroll
        for (int h = 0; h < 4; h++) { ml[h] = fmaxf(ml[h], __shfl_xor_sync(0xffffffffu, ml[h], 2)); mh[h] = fmaxf(mh[h], __shfl_xor_sync(0xffffffffu, mh[h], 2)); }
        float sl[4], sh[4];
#pragma unroll
        for (int h = 0; h < 4; h++) {
          const float bl = -ml[h] * sc, bh = -mh[h] * sc;
          l0[h] = ex2(fmaf(l0[h], sc, bl)); l1[h] = ex2(fmaf(l1[h], sc, bl));
          h0[h] = ex2(fmaf(h0[h], sc, bh)); h1[h] = ex2(fmaf(h1[h], sc, bh));
          sl[h] = l0[h] + l1[h]; sh[h] = h0[h] + h1[h];
        }
#pragma unroll
        for (int h = 0; h < 4; h++) { sl[h] += __shfl_xor_sync(0xffffffffu, sl[h], 1); sh[h] += __shfl_xor_sync(0xffffffffu, sh[h], 1); }
#pragma unroll
        for (int h = 0; h < 4; h++) { sl[h] += __shfl_xor_sync(0xffffffffu, sl[h], 2); sh[h] += __shfl_xor_sync(0xffffffffu, sh[h], 2); }
#pragma unroll
        for (int h = 0; h < 4; h++) {
          const float il = rcp(sl[h]), ih = rcp(sh[h]);
          const uint32_t pl = pack2(l0[h] * il, l1[h] * il), ph = pack2(h0[h] * ih, h1[h] * ih);
          const uint4 P = make_uint4(pl & msk, ph & ~msk, 0u, ph & msk);
          float o0[4], o1[4];
          mma16816_z(o0, P, vf[h].x, vf[h].y);
          mma16816_z(o1, P, vf[h].z, vf[h].w);
          mma1688(o0, pl & ~msk, 0u, pp[h].z);
          mma1688(o1, pl & ~msk, 0u, pp[h].w);
          st_ll(od + h * 32, make_uint4(set_tag(pack2(o0[0], o0[1]), tag), pack2(o0[2], o0[3]), pack2(o1[0], o1[1]), pack2(o1[2], o1[3])));
        }
      }
      TS(5 + 20 * L);
      if (L == 0) { STOP_AT(1); } else { STOP_AT(11); }
      {
        PHASE_VARS;
        float acc[32];
        uint4 A[32], xr[4];
        const uint4* os = g_o + ((c * 8 + slab) * 32) * 32 + lane;
        uint4* xp = g_xraw + ((c * 8 + slab) * 32 + 4 * j) * 32 + lane;
        load_pk<4>(xr, xp);
        load_pk<4>(A, os);
        ensure_pk<4>(A, os, tag);
        TS(6 + 20 * L);
        load_pk<28>(A + 4, os + 128);
        static_for<0, 8>([&](auto I) {
          constexpr int kb = I.value;
          if constexpr ((kb & 1) == 0) cons_acquire<ST_WO + kb / 2>(sbase, L);
          if constexpr (kb > 0) ensure_pk<4>(A + 4 * kb, os + kb * 128, tag);
          wg_fence();
          static_for<0, 4>([&](auto K) {
            constexpr int k = K.value;
            wgmma_n64<kb == 0 && k == 0, 0>(acc, A[4 * kb + k], st_desc<ST_WO + kb / 2, 2048, 8192, 1024, 1>(4 * (kb & 1) + k));
          });
          wg_commit();
          if constexpr ((kb & 1) == 0 && kb > 0) { wg_wait<1>(); cons_release<ST_WO + kb / 2 - 1>(sbase, lane); }
        });
        wg_wait<0>();
        TS(7 + 20 * L);
        fence_acc(acc);
#pragma unroll
        for (int k = 0; k < 32; k++) keep(A[k]);
        cons_release<ST_WO + 3>(sbase, lane);
        ensure_pk<4>(xr, xp, 1u);
#pragma unroll
        for (int i = 0; i < 4; i++) {
          acc[8 * i + 0] += bf_lo(xr[i].x); acc[8 * i + 1] += bf_hi(xr[i].x); acc[8 * i + 2] += bf_lo(xr[i].y); acc[8 * i + 3] += bf_hi(xr[i].y);
          acc[8 * i + 4] += bf_lo(xr[i].z); acc[8 * i + 5] += bf_hi(xr[i].z); acc[8 * i + 6] += bf_lo(xr[i].w); acc[8 * i + 7] += bf_hi(xr[i].w);
          uint4 o = pack8(&acc[8 * i]);
          o.x = set_tag(o.x, 0u);
          st_ll(xp + i * 32, o);
        }
        uint4 st = local_stats(acc);
        st.x = set_tag(st.x, tag);
        if (qc == 0) st_ll(g_stats + ((c * 8 + slab) * 8 + j) * 8 + qr, st);
      }
      TS(8 + 20 * L);
      if (L == 0) { STOP_AT(2); } else { STOP_AT(12); }
      uint4 hs[14];
      {
        PHASE_VARS;
        float acc[128];
        uint4 A[3][4];
        const uint4* xs = g_xraw + ((c * 8 + slab) * 32) * 32 + lane;
        const uint4* sp = g_stats + ((c * 8 + slab) * 8 + 2 * qc) * 8 + qr;
        const uint32_t sm = areg + t128 * 16;
        uint32_t rl2, rh2, bl2, bh2;
        float cl, ch;
        {
          uint4 p[2];
          load_pk<4>(A[0], xs);
          p[0] = ld_ll(sp); p[1] = ld_ll(sp + 8);
          for (uint32_t n = 0; !ok_pk<2>(p, tag) && n < SPIN_LIMIT; n++) { load_pk<4>(A[0], xs); p[0] = ld_ll(sp); p[1] = ld_ll(sp + 8); }
          TS(9 + 20 * L);
          load_pk<4>(A[1], xs + 128);
          float ml, rl, mh, rh;
          combine_stats(p[0], p[1], ml, rl, mh, rh);
          rl2 = pack2(rl, rl); rh2 = pack2(rh, rh);
          const float rlb = bf_lo(rl2), rhb = bf_lo(rh2);
          bl2 = pack2(-ml * rlb, -ml * rlb); bh2 = pack2(-mh * rhb, -mh * rhb);
          cl = rl / rlb; cl *= cl; ch = rh / rhb; ch *= ch;
        }
        auto normalise = [&](uint4 (&xb)[4], int kb) {
#pragma unroll
          for (int k = 0; k < 4; k++) {
            xb[k].x = hfma2(xb[k].x, rl2, bl2); xb[k].y = hfma2(xb[k].y, rh2, bh2);
            xb[k].z = hfma2(xb[k].z, rl2, bl2); xb[k].w = hfma2(xb[k].w, rh2, bh2);
            sts128(sm + (kb * 4 + k) * 2048, xb[k]);
          }
        };
        ensure_pk<4>(A[0], xs, 0u);
        normalise(A[0], 0);
        cons_acquire<ST_G1>(sbase, L);
        static_for<0, 8>([&](auto I) {
          constexpr int kb = I.value;
          wg_fence();
          static_for<0, 4>([&](auto K) { constexpr int k = K.value; wgmma_n256<kb == 0 && k == 0, 0>(acc, A[kb % 3][k], st_desc<ST_G1 + kb, 2048, 8192, 1024, 1>(k)); });
          wg_commit();
          bool full = true;
          if constexpr (kb + 1 < 8) full = cons_probe<ST_G1 + kb + 1>(sbase, L);
          if constexpr (kb > 0) {
            wg_wait<1>();
            keep4(A[(kb + 2) % 3]);
            cons_release<ST_G1 + kb - 1>(sbase, lane);
          }
          if constexpr (kb + 1 < 8) {
            const bool ok = ok_pk<4>(A[(kb + 1) % 3], 0u);
            if (!(ok && full)) { ensure_pk<4>(A[(kb + 1) % 3], xs + (kb + 1) * 128, 0u); cons_acquire<ST_G1 + kb + 1>(sbase, L); }
          }
          if constexpr (kb + 2 < 8) load_pk<4>(A[(kb + 2) % 3], xs + (kb + 2) * 128);
          if constexpr (kb + 1 < 8) normalise(A[(kb + 1) % 3], kb + 1);
        });
        wg_wait<0>();
        TS(10 + 20 * L);
        fence_acc(acc);
        keep4(A[1]);
        cons_release<ST_G1 + 7>(sbase, lane);
        uint4 B[2][4];
#pragma unroll
        for (int k = 0; k < 4; k++) B[0][k] = lds128(sm + k * 2048);
#pragma unroll
        for (int s = 0; s < 8; s++) hs[s] = glu8<32>(&acc[64 * (s >> 2) + 8 * (s & 3)], cl, ch);
        float acc2[96];
        const uint32_t hdst = mapa(sm, cbit ^ 1);
        const uint32_t hbar1 = mapa(bars + BAR_HRECV + 16 * g, cbit ^ 1);
        if (t128 == 0) { mbar_expect_tx(bars + BAR_HRECV + 16 * g, 8 * 2048); mbar_expect_tx(bars + BAR_HRECV + 16 * g + 8, 6 * 2048); }
        cons_acquire<ST_G2>(sbase, L);
        static_for<0, 8>([&](auto I) {
          constexpr int kb = I.value;
          wg_fence();
          static_for<0, 4>([&](auto K) {
            constexpr int k = K.value;
            wgmma_n128<kb == 0 && k == 0, 0>(acc2, B[kb & 1][k], st_desc<ST_G2 + kb, 2048, 8192, 1024, 1>(k));
            wgmma_n64<kb == 0 && k == 0, 64>(acc2, B[kb & 1][k], st_desc<ST_G2 + kb, 1024, 4096, 512, 2>(k) + (16384 >> 4));
          });
          wg_commit();
          bool full = true;
          if constexpr (kb + 1 < 8) full = cons_probe<ST_G2 + kb + 1>(sbase, L);
          if constexpr (kb > 0) {
            wg_wait<1>();
            keep4(B[(kb + 1) & 1]);
            cons_release<ST_G2 + kb - 1>(sbase, lane);
          }
          if constexpr (kb + 1 < 8) {
#pragma unroll
            for (int k = 0; k < 4; k++) B[(kb + 1) & 1][k] = lds128(sm + ((kb + 1) * 4 + k) * 2048);
            if (!full) cons_acquire<ST_G2 + kb + 1>(sbase, L);
          }
          if constexpr (kb == 3) {
            __syncwarp();
            if (lane == 0) mbar_arrive_remote(mapa(bars + BAR_HREADY + 8 * g, cbit ^ 1));
          }
          if constexpr (kb >= 4) {
            if constexpr (kb == 4) mbar_wait(bars + BAR_HREADY + 8 * g, L);
            st_async128(hdst + (2 * kb - 8) * 2048, hs[2 * kb - 8], hbar1);
            st_async128(hdst + (2 * kb - 7) * 2048, hs[2 * kb - 7], hbar1);
          }
        });
        wg_wait<0>();
        TS(11 + 20 * L);
        fence_acc(acc2);
        keep4(B[1]);
        cons_release<ST_G2 + 7>(sbase, lane);
#pragma unroll
        for (int s = 0; s < 4; s++) hs[8 + s] = glu8<32>(&acc2[8 * s], cl, ch);
#pragma unroll
        for (int s = 0; s < 2; s++) hs[12 + s] = glu8<16>(&acc2[64 + 8 * s], cl, ch);
      }
      {
        PHASE_VARS;
        TS(12 + 20 * L);
        const uint32_t hdst = mapa(areg + t128 * 16, cbit ^ 1);
        const uint32_t hbar2 = mapa(bars + BAR_HRECV + 16 * g + 8, cbit ^ 1);
        uint4* pd = g_part + ((((c * 4 + w) * 2 + cbit) * 4 + ca) * 2 + g) * 16 * 32 + lane;
        uint4 hb[7];
        float a0[32], a1[32], a2[32], a3[32];
        auto publish = [&](float (&a)[32], int q, int s0, int s1) {
#pragma unroll
          for (int s = s0; s < s1; s++) {
            uint4 o = pack8(&a[8 * s]);
            o.x = set_tag(o.x, tag);
            st_ll(pd + (4 * q + s) * 32, o);
          }
        };
        static_for<0, 16>([&](auto I) {
          constexpr int i = I.value, q = dn_q(i), par = dn_par(i), kh = dn_kh(i);
          auto mm = [&](auto K) {
            constexpr int k = decltype(K)::value;
            constexpr bool init = (k == 0 && par == 0 && kh == 0);
            constexpr uint64_t db = st_desc<ST_DN + i, 2048, 8192, 1024, 1>(k);
            if constexpr (q == 0) { if constexpr (par) wgmma_n64<init, 0>(a0, hb[k], db); else wgmma_n64<init, 0>(a0, hs[7 * kh + k], db); }
            if constexpr (q == 1) { if constexpr (par) wgmma_n64<init, 0>(a1, hb[k], db); else wgmma_n64<init, 0>(a1, hs[7 * kh + k], db); }
            if constexpr (q == 2) { if constexpr (par) wgmma_n64<init, 0>(a2, hb[k], db); else wgmma_n64<init, 0>(a2, hs[7 * kh + k], db); }
            if constexpr (q == 3) { if constexpr (par) wgmma_n64<init, 0>(a3, hb[k], db); else wgmma_n64<init, 0>(a3, hs[7 * kh + k], db); }
          };
          if constexpr (i == 0) cons_acquire<ST_DN>(sbase, L);
          wg_fence();
          mm(IC<0>{}); mm(IC<1>{}); mm(IC<2>{}); mm(IC<3>{}); mm(IC<4>{}); mm(IC<5>{}); mm(IC<6>{});
          wg_commit();
          bool full = true;
          if constexpr (i < 15) full = cons_probe<ST_DN + i + 1>(sbase, L);
          if constexpr (i > 0) { wg_wait<1>(); cons_release<ST_DN + i - 1>(sbase, lane); }
          if constexpr (i < 3) {
            st_async128(hdst + (8 + 2 * i) * 2048, hs[8 + 2 * i], hbar2);
            st_async128(hdst + (9 + 2 * i) * 2048, hs[9 + 2 * i], hbar2);
          }
          constexpr int n = i + 1;
          if constexpr (n < 16 && dn_par(n) && n != 4 && n != 7) {
            if constexpr (n == 2) { mbar_wait(bars + BAR_HRECV + 16 * g, L); TS(13 + 20 * L); }
            if constexpr (n == 6) { mbar_wait(bars + BAR_HRECV + 16 * g + 8, L); TS(14 + 20 * L); }
#pragma unroll
            for (int k = 0; k < 7; k++) { if constexpr (n != 2) keep(hb[k]); hb[k] = lds128(areg + t128 * 16 + (7 * dn_kh(n) + k) * 2048); }
          }
          if constexpr (i == 7) { fence_acc(a0); publish(a0, 0, 0, 4); }
          if constexpr (i == 8) { fence_acc(a1); publish(a1, 1, 0, 2); }
          if constexpr (i == 9) publish(a1, 1, 2, 4);
          if constexpr (i == 12) { fence_acc(a2); publish(a2, 2, 0, 2); }
          if constexpr (i == 13) publish(a2, 2, 2, 4);
          if constexpr (i < 15) { if (!full) cons_acquire<ST_DN + i + 1>(sbase, L); }
        });
        wg_wait<0>();
        TS(15 + 20 * L);
        fence_acc(a3);
#pragma unroll
        for (int k = 0; k < 7; k++) { keep(hb[k]); keep(hs[7 + k]); }
        cons_release<NSTAGE - 1>(sbase, lane);
        publish(a3, 3, 0, 4);
      }
      {
        PHASE_VARS;
        const int oslab = 4 * g + ca;
        const uint4* xq = g_xraw + ((c * 8 + oslab) * 32 + 16 * cbit + 4 * w) * 32 + lane;
        const uint4* ps = g_part + ((((c * 4 + ca) * 2 + cbit) * 4) * 2 + g) * 16 * 32 + (4 * w) * 32 + lane;
        uint4 xr[4], P[4][4];
        float v[32];
        load_pk<4>(xr, xq);
#pragma unroll
        for (int src = 0; src < 4; src++) load_pk<4>(P[src], ps + src * (2 * 16 * 32));
#pragma unroll
        for (int src = 0; src < 4; src++) ensure_pk<4>(P[src], ps + src * (2 * 16 * 32), tag);
        TS(16 + 20 * L);
        ensure_pk<4>(xr, xq, 0u);
#pragma unroll
        for (int i = 0; i < 4; i++) {
          v[8 * i + 0] = bf_lo(xr[i].x); v[8 * i + 1] = bf_hi(xr[i].x); v[8 * i + 2] = bf_lo(xr[i].y); v[8 * i + 3] = bf_hi(xr[i].y);
          v[8 * i + 4] = bf_lo(xr[i].z); v[8 * i + 5] = bf_hi(xr[i].z); v[8 * i + 6] = bf_lo(xr[i].w); v[8 * i + 7] = bf_hi(xr[i].w);
          float d[8] = {0, 0, 0, 0, 0, 0, 0, 0};
#pragma unroll
          for (int src = 0; src < 4; src++) {
            const uint4 p = P[src][i];
            d[0] += bf_lo(p.x); d[1] += bf_hi(p.x); d[2] += bf_lo(p.y); d[3] += bf_hi(p.y);
            d[4] += bf_lo(p.z); d[5] += bf_hi(p.z); d[6] += bf_lo(p.w); d[7] += bf_hi(p.w);
          }
#pragma unroll
          for (int k = 0; k < 8; k++) v[8 * i + k] += d[k];
        }
        if (L == 0) {
          owner_ln_publish(sbase, v, 1u, 0u);
        } else {
          uint32_t* op = reinterpret_cast<uint32_t*>(out + (size_t)(slab_row0(c, g, ca) + 2 * qr) * 512 + (16 * cbit + 4 * w) * 16 + qc * 2);
#pragma unroll
          for (int i = 0; i < 4; i++) {
            op[i * 8] = pack2(v[8 * i], v[8 * i + 1]);
            op[16 * 256 + i * 8] = pack2(v[8 * i + 2], v[8 * i + 3]);
            op[i * 8 + 4] = pack2(v[8 * i + 4], v[8 * i + 5]);
            op[16 * 256 + i * 8 + 4] = pack2(v[8 * i + 6], v[8 * i + 7]);
          }
        }
      }
      TS(17 + 20 * L);
      if (L == 0) { STOP_AT(3); }
    }
    TG(62);
    asm volatile("barrier.cluster.arrive.release.aligned;\nbarrier.cluster.wait.acquire.aligned; // consumer" ::: "memory");
    TG(63);
  }
}

typedef CUresult (*EncodeFn)(CUtensorMap*, CUtensorMapDataType, cuuint32_t, void*, const cuuint64_t*, const cuuint64_t*,
                             const cuuint32_t*, const cuuint32_t*, CUtensorMapInterleave, CUtensorMapSwizzle,
                             CUtensorMapL2promotion, CUtensorMapFloatOOBfill);

void encode(EncodeFn fn, CUtensorMap* m, int rank, const void* base, const cuuint64_t* dims, const cuuint64_t* strides,
            const cuuint32_t* box, CUtensorMapSwizzle sw) {
  cuuint32_t es[5] = {1, 1, 1, 1, 1};
  fn(m, CU_TENSOR_MAP_DATA_TYPE_BFLOAT16, (cuuint32_t)rank, const_cast<void*>(base), dims, strides, box, es,
     CU_TENSOR_MAP_INTERLEAVE_NONE, sw, CU_TENSOR_MAP_L2_PROMOTION_L2_128B, CU_TENSOR_MAP_FLOAT_OOB_FILL_NONE);
}

}

extern "C" void kernel_launch(void* const* d_in, const int* in_sizes, int n_in, void* d_out, int out_size) {
  (void)in_sizes; (void)n_in; (void)out_size;
  const __nv_bfloat16* x = (const __nv_bfloat16*)d_in[0];
  const char* wqkv = (const char*)d_in[1];
  const char* wo = (const char*)d_in[2];
  const char* wg = (const char*)d_in[4];
  const char* wu = (const char*)d_in[5];
  const char* wd = (const char*)d_in[6];

  static EncodeFn fn = nullptr;
  if (!fn) {
    void* p = nullptr;
    cudaDriverEntryPointQueryResult st;
    cudaGetDriverEntryPoint("cuTensorMapEncodeTiled", &p, cudaEnableDefault, &st);
    fn = (EncodeFn)p;
    cudaFuncSetAttribute(fused_kernel, cudaFuncAttributeMaxDynamicSharedMemorySize, SMEM_BYTES);
  }
  CUtensorMap m_qkv, m_wo, m_gu2, m_gu1, m_guh, m_wd112, m_wd80, m_wd32;
  {
    cuuint64_t dims[3] = {512, 512, 3}, str[2] = {3072, 1024};
    cuuint32_t box[3] = {64, 64, 3};
    encode(fn, &m_qkv, 3, wqkv, dims, str, box, CU_TENSOR_MAP_SWIZZLE_128B);
  }
  {
    cuuint64_t dims[2] = {512, 512}, str[1] = {1024};
    cuuint32_t box[2] = {64, 128};
    encode(fn, &m_wo, 2, wo, dims, str, box, CU_TENSOR_MAP_SWIZZLE_128B);
  }
  {
    const char* lo = wg < wu ? wg : wu;
    cuuint64_t diff = (cuuint64_t)(wg < wu ? wu - wg : wg - wu);
    cuuint64_t dims[4] = {1792, 512, 2, 2}, str[3] = {3584, diff, 128};
    cuuint32_t box2[4] = {64, 64, 2, 2}, box1[4] = {64, 64, 2, 1}, boxh[3] = {32, 64, 2};
    encode(fn, &m_gu2, 4, lo, dims, str, box2, CU_TENSOR_MAP_SWIZZLE_128B);
    encode(fn, &m_gu1, 4, lo, dims, str, box1, CU_TENSOR_MAP_SWIZZLE_128B);
    encode(fn, &m_guh, 3, lo, dims, str, boxh, CU_TENSOR_MAP_SWIZZLE_64B);
  }
  {
    cuuint64_t dims[2] = {512, 1792}, str[1] = {1024};
    cuuint32_t b112[2] = {64, 112}, b80[2] = {64, 80}, b32[2] = {64, 32};
    encode(fn, &m_wd112, 2, wd, dims, str, b112, CU_TENSOR_MAP_SWIZZLE_128B);
    encode(fn, &m_wd80, 2, wd, dims, str, b80, CU_TENSOR_MAP_SWIZZLE_128B);
    encode(fn, &m_wd32, 2, wd, dims, str, b32, CU_TENSOR_MAP_SWIZZLE_128B);
  }
  cudaLaunchConfig_t cfg = {};
  cfg.gridDim = dim3(128);
  cfg.blockDim = dim3(NTHREADS);
  cfg.dynamicSmemBytes = SMEM_BYTES;
  cfg.stream = cudaStreamPerThread;
  cudaLaunchAttribute at[1];
  at[0].id = cudaLaunchAttributeClusterDimension;
  at[0].val.clusterDim.x = 2; at[0].val.clusterDim.y = 1; at[0].val.clusterDim.z = 1;
  cfg.attrs = at; cfg.numAttrs = 1;
  cudaLaunchKernelEx(&cfg, fused_kernel, m_qkv, m_wo, m_gu2, m_gu1, m_guh, m_wd112, m_wd80, m_wd32, x, (__nv_bfloat16*)d_out, wo, wg, wu, wd
  );
}
```

```cpp
#include <cuda_runtime.h>
#include <cuda_bf16.h>
#include <cuda.h>
#include <stdint.h>

namespace {

constexpr int NTHREADS = 384;
constexpr int GRAN = 8192;
constexpr int NGRAN = 12;
constexpr int SM_AREG = NGRAN * GRAN;
constexpr int SM_MISC = SM_AREG + 131072;
constexpr int SM_TSTAT = SM_MISC + 256;
constexpr int SMEM_BYTES = SM_TSTAT + 2048;
constexpr int BAR_FULL = 0, BAR_EMPTY = 96, BAR_HRECV = 192, BAR_HREADY = 224, BAR_TSTAT = 240;

__device__ uint4 g_xn[16 * 8 * 32 * 32];
__device__ uint4 g_xraw[16 * 8 * 32 * 32];
__device__ uint4 g_o[16 * 8 * 32 * 32];
__device__ uint4 g_stats[16 * 8 * 8 * 8];
__device__ uint4 g_halo[2 * 32 * 8 * 8 * 32];
__device__ uint4 g_part[16 * 4 * 2 * 4 * 2 * 16 * 32];

#define TS(n)
#define TG(n)
#define OPAQUE(x) asm volatile("" : "+r"(x))
#define PHASE_VARS                                                                                   \
  int tid_ = threadIdx.x, bid_ = blockIdx.x;                                                         \
  OPAQUE(tid_); OPAQUE(bid_);                                                                        \
  const int lane = tid_ & 31, warp = tid_ >> 5, g = warp >> 2, w = warp & 3, t128 = tid_ & 127;      \
  const int qr = lane >> 2, qc = lane & 3, slab = warp;                                              \
  const int c = bid_ >> 3, j = bid_ & 7, ca = j >> 1, cbit = j & 1;                                  \
  const uint32_t areg = sbase + SM_AREG + g * 65536;                                                 \
  (void)g; (void)j; (void)w; (void)t128; (void)qr; (void)qc; (void)slab; (void)c; (void)ca; (void)cbit; (void)areg; (void)lane
#define STOP_AT(n)
#define PSTOP_AT(n)

__device__ __forceinline__ uint32_t smem_u32(const void* p) { return (uint32_t)__cvta_generic_to_shared(p); }
__device__ __forceinline__ void mbar_init(uint32_t bar, uint32_t cnt) {
  asm volatile("mbarrier.init.shared::cta.b64 [%0], %1;" ::"r"(bar), "r"(cnt) : "memory");
}
__device__ __forceinline__ void mbar_expect_tx(uint32_t bar, uint32_t bytes) {
  asm volatile("mbarrier.arrive.expect_tx.shared::cta.b64 _, [%0], %1;" ::"r"(bar), "r"(bytes) : "memory");
}
__device__ __forceinline__ void mbar_arrive(uint32_t bar) {
  asm volatile("mbarrier.arrive.shared::cta.b64 _, [%0];" ::"r"(bar) : "memory");
}
__device__ __forceinline__ void mbar_arrive_remote(uint32_t cluster_addr) {
  asm volatile("mbarrier.arrive.relaxed.cluster.shared::cluster.b64 _, [%0];" ::"r"(cluster_addr) : "memory");
}
__device__ __forceinline__ bool mbar_try(uint32_t bar, uint32_t parity) {
  uint32_t ok;
  asm volatile("{\n.reg .pred p;\nmbarrier.try_wait.parity.shared::cta.b64 p, [%1], %2;\nselp.u32 %0, 1, 0, p;\n}"
               : "=r"(ok) : "r"(bar), "r"(parity) : "memory");
  return ok != 0;
}
constexpr uint32_t SPIN_LIMIT = 1u << 16;
constexpr uint32_t SMEM_ORIGIN = 1024;
__device__ __forceinline__ void mbar_wait(uint32_t bar, uint32_t parity) {
  for (uint32_t n = 0; !mbar_try(bar, parity) && n < SPIN_LIMIT; n++) {}
}
__device__ __forceinline__ uint32_t mapa(uint32_t addr, uint32_t rank) {
  uint32_t r;
  asm volatile("mapa.shared::cluster.u32 %0, %1, %2;" : "=r"(r) : "r"(addr), "r"(rank));
  return r;
}
__device__ __forceinline__ void cluster_sync_all() {
  asm volatile("barrier.cluster.arrive.release.aligned;\nbarrier.cluster.wait.acquire.aligned;" ::: "memory");
}

__device__ __forceinline__ void tma_2d(uint32_t dst, const CUtensorMap* m, uint32_t bar, int c0, int c1) {
  asm volatile("cp.async.bulk.tensor.2d.shared::cluster.global.mbarrier::complete_tx::bytes [%0], [%1, {%3, %4}], [%2];"
               ::"r"(dst), "l"(m), "r"(bar), "r"(c0), "r"(c1) : "memory");
}
__device__ __forceinline__ void tma_3d(uint32_t dst, const CUtensorMap* m, uint32_t bar, int c0, int c1, int c2) {
  asm volatile("cp.async.bulk.tensor.3d.shared::cluster.global.mbarrier::complete_tx::bytes [%0], [%1, {%3, %4, %5}], [%2];"
               ::"r"(dst), "l"(m), "r"(bar), "r"(c0), "r"(c1), "r"(c2) : "memory");
}
__device__ __forceinline__ void tma_4d(uint32_t dst, const CUtensorMap* m, uint32_t bar, int c0, int c1, int c2, int c3) {
  asm volatile("cp.async.bulk.tensor.4d.shared::cluster.global.mbarrier::complete_tx::bytes [%0], [%1, {%3, %4, %5, %6}], [%2];"
               ::"r"(dst), "l"(m), "r"(bar), "r"(c0), "r"(c1), "r"(c2), "r"(c3) : "memory");
}
__device__ __forceinline__ void l2_prefetch(const void* p, uint32_t bytes) {
  asm volatile("cp.async.bulk.prefetch.L2.global [%0], %1;" ::"l"(p), "r"(bytes) : "memory");
}

__device__ __forceinline__ uint4 ld_ll(const uint4* p) {
  uint4 v;
  asm volatile("ld.relaxed.gpu.global.v4.u32 {%0,%1,%2,%3}, [%4];" : "=r"(v.x), "=r"(v.y), "=r"(v.z), "=r"(v.w) : "l"(p) : "memory");
  return v;
}
__device__ __forceinline__ void st_ll(uint4* p, uint4 v) {
  asm volatile("st.relaxed.gpu.global.v4.u32 [%0], {%1,%2,%3,%4};" ::"l"(p), "r"(v.x), "r"(v.y), "r"(v.z), "r"(v.w) : "memory");
}
__device__ __forceinline__ uint4 lds128(uint32_t a) {
  uint4 v;
  asm volatile("ld.shared.v4.u32 {%0,%1,%2,%3}, [%4];" : "=r"(v.x), "=r"(v.y), "=r"(v.z), "=r"(v.w) : "r"(a) : "memory");
  return v;
}
__device__ __forceinline__ void sts128(uint32_t a, uint4 v) {
  asm volatile("st.shared.v4.u32 [%0], {%1,%2,%3,%4};" ::"r"(a), "r"(v.x), "r"(v.y), "r"(v.z), "r"(v.w) : "memory");
}
__device__ __forceinline__ void st_async128(uint32_t cluster_addr, uint4 v, uint32_t cluster_bar) {
  asm volatile("st.async.weak.shared::cluster.mbarrier::complete_tx::bytes.v4.b32 [%0], {%1,%2,%3,%4}, [%5];"
               ::"r"(cluster_addr), "r"(v.x), "r"(v.y), "r"(v.z), "r"(v.w), "r"(cluster_bar) : "memory");
}
__device__ __forceinline__ uint32_t pack2(float lo, float hi) {
  uint32_t r;
  asm("cvt.rn.bf16x2.f32 %0, %1, %2;" : "=r"(r) : "f"(hi), "f"(lo));
  return r;
}
__device__ __forceinline__ float bf_lo(uint32_t w) { return __uint_as_float(w << 16); }
__device__ __forceinline__ float bf_hi(uint32_t w) { return __uint_as_float(w & 0xffff0000u); }
__device__ __forceinline__ uint32_t set_tag(uint32_t w, uint32_t tag) { return (w & ~1u) | tag; }
__device__ __forceinline__ uint32_t movm(uint32_t a) {
  uint32_t d;
  asm("movmatrix.sync.aligned.m8n8.trans.b16 %0, %1;" : "=r"(d) : "r"(a));
  return d;
}
__device__ __forceinline__ void mma16816(float (&d)[4], const uint4& a, uint32_t b0, uint32_t b1) {
  asm("mma.sync.aligned.m16n8k16.row.col.f32.bf16.bf16.f32 {%0,%1,%2,%3}, {%4,%5,%6,%7}, {%8,%9}, {%0,%1,%2,%3};"
               : "+f"(d[0]), "+f"(d[1]), "+f"(d[2]), "+f"(d[3])
               : "r"(a.x), "r"(a.y), "r"(a.z), "r"(a.w), "r"(b0), "r"(b1));
}
__device__ __forceinline__ void mma1688(float (&d)[4], uint32_t a0, uint32_t a1, uint32_t b0) {
  asm("mma.sync.aligned.m16n8k8.row.col.f32.bf16.bf16.f32 {%0,%1,%2,%3}, {%4,%5}, {%6}, {%0,%1,%2,%3};"
      : "+f"(d[0]), "+f"(d[1]), "+f"(d[2]), "+f"(d[3])
      : "r"(a0), "r"(a1), "r"(b0));
}
__device__ __forceinline__ void mma16816_z(float (&d)[4], const uint4& a, uint32_t b0, uint32_t b1) {
  asm("mma.sync.aligned.m16n8k16.row.col.f32.bf16.bf16.f32 {%0,%1,%2,%3}, {%4,%5,%6,%7}, {%8,%9}, {%10,%10,%10,%10};"
      : "=f"(d[0]), "=f"(d[1]), "=f"(d[2]), "=f"(d[3])
      : "r"(a.x), "r"(a.y), "r"(a.z), "r"(a.w), "r"(b0), "r"(b1), "f"(0.f));
}
__device__ __forceinline__ float ex2(float x) {
  float y;
  asm("ex2.approx.ftz.f32 %0, %1;" : "=f"(y) : "f"(x));
  return y;
}
__device__ __forceinline__ float rcp(float x) {
  float y;
  asm("rcp.approx.ftz.f32 %0, %1;" : "=f"(y) : "f"(x));
  return y;
}
__device__ __forceinline__ void cp_async16(uint32_t dst, const void* src) {
  asm volatile("cp.async.cg.shared.global [%0], [%1], 16;" ::"r"(dst), "l"(src) : "memory");
}
__device__ __forceinline__ void cp_commit() { asm volatile("cp.async.commit_group;" ::: "memory"); }
template <int N> __device__ __forceinline__ void cp_wait() { asm volatile("cp.async.wait_group %0;" ::"n"(N) : "memory"); }
__device__ __forceinline__ void bar_wg(int id) { asm volatile("bar.sync %0, 128;" ::"r"(id) : "memory"); }
__device__ __forceinline__ void wg_fence() { asm volatile("wgmma.fence.sync.aligned;" ::: "memory"); }
__device__ __forceinline__ void wg_commit() { asm volatile("wgmma.commit_group.sync.aligned;" ::: "memory"); }
template <int N> __device__ __forceinline__ void wg_wait() { asm volatile("wgmma.wait_group.sync.aligned %0;" ::"n"(N) : "memory"); }
__device__ __forceinline__ void keep(const uint4& a) { asm volatile("" ::"r"(a.x), "r"(a.y), "r"(a.z), "r"(a.w) : "memory"); }
template <int T> __device__ __forceinline__ void zero_acc(float (&d)[T]) {
#pragma unroll
  for (int i = 0; i < T; i++) d[i] = 0.f;
}
template <int T> __device__ __forceinline__ void fence_acc(float (&d)[T]) {
#pragma unroll
  for (int i = 0; i < T; i++) asm volatile("" : "+f"(d[i])::"memory");
}

template <int O, int T> __device__ __forceinline__ void wgmma_rs_n64(float (&d)[T], const uint4& a, uint64_t db) {
  asm volatile("{\n.reg .pred p;\nsetp.ne.b32 p, 1, 0;\n"
    "wgmma.mma_async.sync.aligned.m64n64k16.f32.bf16.bf16 "
    "{%0, %1, %2, %3, %4, %5, %6, %7, %8, %9, %10, %11, %12, %13, %14, %15, "
    "%16, %17, %18, %19, %20, %21, %22, %23, %24, %25, %26, %27, %28, %29, %30, %31}, "
    "{%32, %33, %34, %35}, %36, p, 1, 1, 1;\n}\n"
    : "+f"(d[O + 0]), "+f"(d[O + 1]), "+f"(d[O + 2]), "+f"(d[O + 3]), "+f"(d[O + 4]), "+f"(d[O + 5]), "+f"(d[O + 6]), "+f"(d[O + 7]),
      "+f"(d[O + 8]), "+f"(d[O + 9]), "+f"(d[O + 10]), "+f"(d[O + 11]), "+f"(d[O + 12]), "+f"(d[O + 13]), "+f"(d[O + 14]), "+f"(d[O + 15]),
      "+f"(d[O + 16]), "+f"(d[O + 17]), "+f"(d[O + 18]), "+f"(d[O + 19]), "+f"(d[O + 20]), "+f"(d[O + 21]), "+f"(d[O + 22]), "+f"(d[O + 23]),
      "+f"(d[O + 24]), "+f"(d[O + 25]), "+f"(d[O + 26]), "+f"(d[O + 27]), "+f"(d[O + 28]), "+f"(d[O + 29]), "+f"(d[O + 30]), "+f"(d[O + 31])
    : "r"(a.x), "r"(a.y), "r"(a.z), "r"(a.w), "l"(db));
}
template <int O, int T> __device__ __forceinline__ void wgmma_rs_n64_init(float (&d)[T], const uint4& a, uint64_t db) {
  asm volatile("{\n.reg .pred p;\nsetp.ne.b32 p, 0, 0;\n"
    "wgmma.mma_async.sync.aligned.m64n64k16.f32.bf16.bf16 "
    "{%0, %1, %2, %3, %4, %5, %6, %7, %8, %9, %10, %11, %12, %13, %14, %15, "
    "%16, %17, %18, %19, %20, %21, %22, %23, %24, %25, %26, %27, %28, %29, %30, %31}, "
    "{%32, %33, %34, %35}, %36, p, 1, 1, 1;\n}\n"
    : "=f"(d[O + 0]), "=f"(d[O + 1]), "=f"(d[O + 2]), "=f"(d[O + 3]), "=f"(d[O + 4]), "=f"(d[O + 5]), "=f"(d[O + 6]), "=f"(d[O + 7]),
      "=f"(d[O + 8]), "=f"(d[O + 9]), "=f"(d[O + 10]), "=f"(d[O + 11]), "=f"(d[O + 12]), "=f"(d[O + 13]), "=f"(d[O + 14]), "=f"(d[O + 15]),
      "=f"(d[O + 16]), "=f"(d[O + 17]), "=f"(d[O + 18]), "=f"(d[O + 19]), "=f"(d[O + 20]), "=f"(d[O + 21]), "=f"(d[O + 22]), "=f"(d[O + 23]),
      "=f"(d[O + 24]), "=f"(d[O + 25]), "=f"(d[O + 26]), "=f"(d[O + 27]), "=f"(d[O + 28]), "=f"(d[O + 29]), "=f"(d[O + 30]), "=f"(d[O + 31])
    : "r"(a.x), "r"(a.y), "r"(a.z), "r"(a.w), "l"(db));
}
template <bool INIT, int O, int T> __device__ __forceinline__ void wgmma_n64(float (&d)[T], const uint4& a, uint64_t db) {
  if constexpr (INIT) wgmma_rs_n64_init<O>(d, a, db); else wgmma_rs_n64<O>(d, a, db);
}
template <int O, int T> __device__ __forceinline__ void wgmma_rs_n128(float (&d)[T], const uint4& a, uint64_t db) {
  asm volatile("{\n.reg .pred p;\nsetp.ne.b32 p, 1, 0;\n"
    "wgmma.mma_async.sync.aligned.m64n128k16.f32.bf16.bf16 "
    "{%0, %1, %2, %3, %4, %5, %6, %7, %8, %9, %10, %11, %12, %13, %14, %15, "
    "%16, %17, %18, %19, %20, %21, %22, %23, %24, %25, %26, %27, %28, %29, %30, %31, "
    "%32, %33, %34, %35, %36, %37, %38, %39, %40, %41, %42, %43, %44, %45, %46, %47, "
    "%48, %49, %50, %51, %52, %53, %54, %55, %56, %57, %58, %59, %60, %61, %62, %63}, "
    "{%64, %65, %66, %67}, %68, p, 1, 1, 1;\n}\n"
    : "+f"(d[O + 0]), "+f"(d[O + 1]), "+f"(d[O + 2]), "+f"(d[O + 3]), "+f"(d[O + 4]), "+f"(d[O + 5]), "+f"(d[O + 6]), "+f"(d[O + 7]),
      "+f"(d[O + 8]), "+f"(d[O + 9]), "+f"(d[O + 10]), "+f"(d[O + 11]), "+f"(d[O + 12]), "+f"(d[O + 13]), "+f"(d[O + 14]), "+f"(d[O + 15]),
      "+f"(d[O + 16]), "+f"(d[O + 17]), "+f"(d[O + 18]), "+f"(d[O + 19]), "+f"(d[O + 20]), "+f"(d[O + 21]), "+f"(d[O + 22]), "+f"(d[O + 23]),
      "+f"(d[O + 24]), "+f"(d[O + 25]), "+f"(d[O + 26]), "+f"(d[O + 27]), "+f"(d[O + 28]), "+f"(d[O + 29]), "+f"(d[O + 30]), "+f"(d[O + 31]),
      "+f"(d[O + 32]), "+f"(d[O + 33]), "+f"(d[O + 34]), "+f"(d[O + 35]), "+f"(d[O + 36]), "+f"(d[O + 37]), "+f"(d[O + 38]), "+f"(d[O + 39]),
      "+f"(d[O + 40]), "+f"(d[O + 41]), "+f"(d[O + 42]), "+f"(d[O + 43]), "+f"(d[O + 44]), "+f"(d[O + 45]), "+f"(d[O + 46]), "+f"(d[O + 47]),
      "+f"(d[O + 48]), "+f"(d[O + 49]), "+f"(d[O + 50]), "+f"(d[O + 51]), "+f"(d[O + 52]), "+f"(d[O + 53]), "+f"(d[O + 54]), "+f"(d[O + 55]),
      "+f"(d[O + 56]), "+f"(d[O + 57]), "+f"(d[O + 58]), "+f"(d[O + 59]), "+f"(d[O + 60]), "+f"(d[O + 61]), "+f"(d[O + 62]), "+f"(d[O + 63])
    : "r"(a.x), "r"(a.y), "r"(a.z), "r"(a.w), "l"(db));
}
template <int O, int T> __device__ __forceinline__ void wgmma_rs_n128_init(float (&d)[T], const uint4& a, uint64_t db) {
  asm volatile("{\n.reg .pred p;\nsetp.ne.b32 p, 0, 0;\n"
    "wgmma.mma_async.sync.aligned.m64n128k16.f32.bf16.bf16 "
    "{%0, %1, %2, %3, %4, %5, %6, %7, %8, %9, %10, %11, %12, %13, %14, %15, "
    "%16, %17, %18, %19, %20, %21, %22, %23, %24, %25, %26, %27, %28, %29, %30, %31, "
    "%32, %33, %34, %35, %36, %37, %38, %39, %40, %41, %42, %43, %44, %45, %46, %47, "
    "%48, %49, %50, %51, %52, %53, %54, %55, %56, %57, %58, %59, %60, %61, %62, %63}, "
    "{%64, %65, %66, %67}, %68, p, 1, 1, 1;\n}\n"
    : "=f"(d[O + 0]), "=f"(d[O + 1]), "=f"(d[O + 2]), "=f"(d[O + 3]), "=f"(d[O + 4]), "=f"(d[O + 5]), "=f"(d[O + 6]), "=f"(d[O + 7]),
      "=f"(d[O + 8]), "=f"(d[O + 9]), "=f"(d[O + 10]), "=f"(d[O + 11]), "=f"(d[O + 12]), "=f"(d[O + 13]), "=f"(d[O + 14]), "=f"(d[O + 15]),
      "=f"(d[O + 16]), "=f"(d[O + 17]), "=f"(d[O + 18]), "=f"(d[O + 19]), "=f"(d[O + 20]), "=f"(d[O + 21]), "=f"(d[O + 22]), "=f"(d[O + 23]),
      "=f"(d[O + 24]), "=f"(d[O + 25]), "=f"(d[O + 26]), "=f"(d[O + 27]), "=f"(d[O + 28]), "=f"(d[O + 29]), "=f"(d[O + 30]), "=f"(d[O + 31]),
      "=f"(d[O + 32]), "=f"(d[O + 33]), "=f"(d[O + 34]), "=f"(d[O + 35]), "=f"(d[O + 36]), "=f"(d[O + 37]), "=f"(d[O + 38]), "=f"(d[O + 39]),
      "=f"(d[O + 40]), "=f"(d[O + 41]), "=f"(d[O + 42]), "=f"(d[O + 43]), "=f"(d[O + 44]), "=f"(d[O + 45]), "=f"(d[O + 46]), "=f"(d[O + 47]),
      "=f"(d[O + 48]), "=f"(d[O + 49]), "=f"(d[O + 50]), "=f"(d[O + 51]), "=f"(d[O + 52]), "=f"(d[O + 53]), "=f"(d[O + 54]), "=f"(d[O + 55]),
      "=f"(d[O + 56]), "=f"(d[O + 57]), "=f"(d[O + 58]), "=f"(d[O + 59]), "=f"(d[O + 60]), "=f"(d[O + 61]), "=f"(d[O + 62]), "=f"(d[O + 63])
    : "r"(a.x), "r"(a.y), "r"(a.z), "r"(a.w), "l"(db));
}
template <bool INIT, int O, int T> __device__ __forceinline__ void wgmma_n128(float (&d)[T], const uint4& a, uint64_t db) {
  if constexpr (INIT) wgmma_rs_n128_init<O>(d, a, db); else wgmma_rs_n128<O>(d, a, db);
}
template <int O, int T> __device__ __forceinline__ void wgmma_rs_n192(float (&d)[T], const uint4& a, uint64_t db) {
  asm volatile("{\n.reg .pred p;\nsetp.ne.b32 p, 1, 0;\n"
    "wgmma.mma_async.sync.aligned.m64n192k16.f32.bf16.bf16 "
    "{%0, %1, %2, %3, %4, %5, %6, %7, %8, %9, %10, %11, %12, %13, %14, %15, "
    "%16, %17, %18, %19, %20, %21, %22, %23, %24, %25, %26, %27, %28, %29, %30, %31, "
    "%32, %33, %34, %35, %36, %37, %38, %39, %40, %41, %42, %43, %44, %45, %46, %47, "
    "%48, %49, %50, %51, %52, %53, %54, %55, %56, %57, %58, %59, %60, %61, %62, %63, "
    "%64, %65, %66, %67, %68, %69, %70, %71, %72, %73, %74, %75, %76, %77, %78, %79, "
    "%80, %81, %82, %83, %84, %85, %86, %87, %88, %89, %90, %91, %92, %93, %94, %95}, "
    "{%96, %97, %98, %99}, %100, p, 1, 1, 1;\n}\n"
    : "+f"(d[O + 0]), "+f"(d[O + 1]), "+f"(d[O + 2]), "+f"(d[O + 3]), "+f"(d[O + 4]), "+f"(d[O + 5]), "+f"(d[O + 6]), "+f"(d[O + 7]),
      "+f"(d[O + 8]), "+f"(d[O + 9]), "+f"(d[O + 10]), "+f"(d[O + 11]), "+f"(d[O + 12]), "+f"(d[O + 13]), "+f"(d[O + 14]), "+f"(d[O + 15]),
      "+f"(d[O + 16]), "+f"(d[O + 17]), "+f"(d[O + 18]), "+f"(d[O + 19]), "+f"(d[O + 20]), "+f"(d[O + 21]), "+f"(d[O + 22]), "+f"(d[O + 23]),
      "+f"(d[O + 24]), "+f"(d[O + 25]), "+f"(d[O + 26]), "+f"(d[O + 27]), "+f"(d[O + 28]), "+f"(d[O + 29]), "+f"(d[O + 30]), "+f"(d[O + 31]),
      "+f"(d[O + 32]), "+f"(d[O + 33]), "+f"(d[O + 34]), "+f"(d[O + 35]), "+f"(d[O + 36]), "+f"(d[O + 37]), "+f"(d[O + 38]), "+f"(d[O + 39]),
      "+f"(d[O + 40]), "+f"(d[O + 41]), "+f"(d[O + 42]), "+f"(d[O + 43]), "+f"(d[O + 44]), "+f"(d[O + 45]), "+f"(d[O + 46]), "+f"(d[O + 47]),
      "+f"(d[O + 48]), "+f"(d[O + 49]), "+f"(d[O + 50]), "+f"(d[O + 51]), "+f"(d[O + 52]), "+f"(d[O + 53]), "+f"(d[O + 54]), "+f"(d[O + 55]),
      "+f"(d[O + 56]), "+f"(d[O + 57]), "+f"(d[O + 58]), "+f"(d[O + 59]), "+f"(d[O + 60]), "+f"(d[O + 61]), "+f"(d[O + 62]), "+f"(d[O + 63]),
      "+f"(d[O + 64]), "+f"(d[O + 65]), "+f"(d[O + 66]), "+f"(d[O + 67]), "+f"(d[O + 68]), "+f"(d[O + 69]), "+f"(d[O + 70]), "+f"(d[O + 71]),
      "+f"(d[O + 72]), "+f"(d[O + 73]), "+f"(d[O + 74]), "+f"(d[O + 75]), "+f"(d[O + 76]), "+f"(d[O + 77]), "+f"(d[O + 78]), "+f"(d[O + 79]),
      "+f"(d[O + 80]), "+f"(d[O + 81]), "+f"(d[O + 82]), "+f"(d[O + 83]), "+f"(d[O + 84]), "+f"(d[O + 85]), "+f"(d[O + 86]), "+f"(d[O + 87]),
      "+f"(d[O + 88]), "+f"(d[O + 89]), "+f"(d[O + 90]), "+f"(d[O + 91]), "+f"(d[O + 92]), "+f"(d[O + 93]), "+f"(d[O + 94]), "+f"(d[O + 95])
    : "r"(a.x), "r"(a.y), "r"(a.z), "r"(a.w), "l"(db));
}
template <int O, int T> __device__ __forceinline__ void wgmma_rs_n192_init(float (&d)[T], const uint4& a, uint64_t db) {
  asm volatile("{\n.reg .pred p;\nsetp.ne.b32 p, 0, 0;\n"
    "wgmma.mma_async.sync.aligned.m64n192k16.f32.bf16.bf16 "
    "{%0, %1, %2, %3, %4, %5, %6, %7, %8, %9, %10, %11, %12, %13, %14, %15, "
    "%16, %17, %18, %19, %20, %21, %22, %23, %24, %25, %26, %27, %28, %29, %30, %31, "
    "%32, %33, %34, %35, %36, %37, %38, %39, %40, %41, %42, %43, %44, %45, %46, %47, "
    "%48, %49, %50, %51, %52, %53, %54, %55, %56, %57, %58, %59, %60, %61, %62, %63, "
    "%64, %65, %66, %67, %68, %69, %70, %71, %72, %73, %74, %75, %76, %77, %78, %79, "
    "%80, %81, %82, %83, %84, %85, %86, %87, %88, %89, %90, %91, %92, %93, %94, %95}, "
    "{%96, %97, %98, %99}, %100, p, 1, 1, 1;\n}\n"
    : "=f"(d[O + 0]), "=f"(d[O + 1]), "=f"(d[O + 2]), "=f"(d[O + 3]), "=f"(d[O + 4]), "=f"(d[O + 5]), "=f"(d[O + 6]), "=f"(d[O + 7]),
      "=f"(d[O + 8]), "=f"(d[O + 9]), "=f"(d[O + 10]), "=f"(d[O + 11]), "=f"(d[O + 12]), "=f"(d[O + 13]), "=f"(d[O + 14]), "=f"(d[O + 15]),
      "=f"(d[O + 16]), "=f"(d[O + 17]), "=f"(d[O + 18]), "=f"(d[O + 19]), "=f"(d[O + 20]), "=f"(d[O + 21]), "=f"(d[O + 22]), "=f"(d[O + 23]),
      "=f"(d[O + 24]), "=f"(d[O + 25]), "=f"(d[O + 26]), "=f"(d[O + 27]), "=f"(d[O + 28]), "=f"(d[O + 29]), "=f"(d[O + 30]), "=f"(d[O + 31]),
      "=f"(d[O + 32]), "=f"(d[O + 33]), "=f"(d[O + 34]), "=f"(d[O + 35]), "=f"(d[O + 36]), "=f"(d[O + 37]), "=f"(d[O + 38]), "=f"(d[O + 39]),
      "=f"(d[O + 40]), "=f"(d[O + 41]), "=f"(d[O + 42]), "=f"(d[O + 43]), "=f"(d[O + 44]), "=f"(d[O + 45]), "=f"(d[O + 46]), "=f"(d[O + 47]),
      "=f"(d[O + 48]), "=f"(d[O + 49]), "=f"(d[O + 50]), "=f"(d[O + 51]), "=f"(d[O + 52]), "=f"(d[O + 53]), "=f"(d[O + 54]), "=f"(d[O + 55]),
      "=f"(d[O + 56]), "=f"(d[O + 57]), "=f"(d[O + 58]), "=f"(d[O + 59]), "=f"(d[O + 60]), "=f"(d[O + 61]), "=f"(d[O + 62]), "=f"(d[O + 63]),
      "=f"(d[O + 64]), "=f"(d[O + 65]), "=f"(d[O + 66]), "=f"(d[O + 67]), "=f"(d[O + 68]), "=f"(d[O + 69]), "=f"(d[O + 70]), "=f"(d[O + 71]),
      "=f"(d[O + 72]), "=f"(d[O + 73]), "=f"(d[O + 74]), "=f"(d[O + 75]), "=f"(d[O + 76]), "=f"(d[O + 77]), "=f"(d[O + 78]), "=f"(d[O + 79]),
      "=f"(d[O + 80]), "=f"(d[O + 81]), "=f"(d[O + 82]), "=f"(d[O + 83]), "=f"(d[O + 84]), "=f"(d[O + 85]), "=f"(d[O + 86]), "=f"(d[O + 87]),
      "=f"(d[O + 88]), "=f"(d[O + 89]), "=f"(d[O + 90]), "=f"(d[O + 91]), "=f"(d[O + 92]), "=f"(d[O + 93]), "=f"(d[O + 94]), "=f"(d[O + 95])
    : "r"(a.x), "r"(a.y), "r"(a.z), "r"(a.w), "l"(db));
}
template <bool INIT, int O, int T> __device__ __forceinline__ void wgmma_n192(float (&d)[T], const uint4& a, uint64_t db) {
  if constexpr (INIT) wgmma_rs_n192_init<O>(d, a, db); else wgmma_rs_n192<O>(d, a, db);
}
template <int O, int T> __device__ __forceinline__ void wgmma_rs_n256(float (&d)[T], const uint4& a, uint64_t db) {
  asm volatile("{\n.reg .pred p;\nsetp.ne.b32 p, 1, 0;\n"
    "wgmma.mma_async.sync.aligned.m64n256k16.f32.bf16.bf16 "
    "{%0, %1, %2, %3, %4, %5, %6, %7, %8, %9, %10, %11, %12, %13, %14, %15, "
    "%16, %17, %18, %19, %20, %21, %22, %23, %24, %25, %26, %27, %28, %29, %30, %31, "
    "%32, %33, %34, %35, %36, %37, %38, %39, %40, %41, %42, %43, %44, %45, %46, %47, "
    "%48, %49, %50, %51, %52, %53, %54, %55, %56, %57, %58, %59, %60, %61, %62, %63, "
    "%64, %65, %66, %67, %68, %69, %70, %71, %72, %73, %74, %75, %76, %77, %78, %79, "
    "%80, %81, %82, %83, %84, %85, %86, %87, %88, %89, %90, %91, %92, %93, %94, %95, "
    "%96, %97, %98, %99, %100, %101, %102, %103, %104, %105, %106, %107, %108, %109, %110, %111, "
    "%112, %113, %114, %115, %116, %117, %118, %119, %120, %121, %122, %123, %124, %125, %126, %127}, "
    "{%128, %129, %130, %131}, %132, p, 1, 1, 1;\n}\n"
    : "+f"(d[O + 0]), "+f"(d[O + 1]), "+f"(d[O + 2]), "+f"(d[O + 3]), "+f"(d[O + 4]), "+f"(d[O + 5]), "+f"(d[O + 6]), "+f"(d[O + 7]),
      "+f"(d[O + 8]), "+f"(d[O + 9]), "+f"(d[O + 10]), "+f"(d[O + 11]), "+f"(d[O + 12]), "+f"(d[O + 13]), "+f"(d[O + 14]), "+f"(d[O + 15]),
      "+f"(d[O + 16]), "+f"(d[O + 17]), "+f"(d[O + 18]), "+f"(d[O + 19]), "+f"(d[O + 20]), "+f"(d[O + 21]), "+f"(d[O + 22]), "+f"(d[O + 23]),
      "+f"(d[O + 24]), "+f"(d[O + 25]), "+f"(d[O + 26]), "+f"(d[O + 27]), "+f"(d[O + 28]), "+f"(d[O + 29]), "+f"(d[O + 30]), "+f"(d[O + 31]),
      "+f"(d[O + 32]), "+f"(d[O + 33]), "+f"(d[O + 34]), "+f"(d[O + 35]), "+f"(d[O + 36]), "+f"(d[O + 37]), "+f"(d[O + 38]), "+f"(d[O + 39]),
      "+f"(d[O + 40]), "+f"(d[O + 41]), "+f"(d[O + 42]), "+f"(d[O + 43]), "+f"(d[O + 44]), "+f"(d[O + 45]), "+f"(d[O + 46]), "+f"(d[O + 47]),
      "+f"(d[O + 48]), "+f"(d[O + 49]), "+f"(d[O + 50]), "+f"(d[O + 51]), "+f"(d[O + 52]), "+f"(d[O + 53]), "+f"(d[O + 54]), "+f"(d[O + 55]),
      "+f"(d[O + 56]), "+f"(d[O + 57]), "+f"(d[O + 58]), "+f"(d[O + 59]), "+f"(d[O + 60]), "+f"(d[O + 61]), "+f"(d[O + 62]), "+f"(d[O + 63]),
      "+f"(d[O + 64]), "+f"(d[O + 65]), "+f"(d[O + 66]), "+f"(d[O + 67]), "+f"(d[O + 68]), "+f"(d[O + 69]), "+f"(d[O + 70]), "+f"(d[O + 71]),
      "+f"(d[O + 72]), "+f"(d[O + 73]), "+f"(d[O + 74]), "+f"(d[O + 75]), "+f"(d[O + 76]), "+f"(d[O + 77]), "+f"(d[O + 78]), "+f"(d[O + 79]),
      "+f"(d[O + 80]), "+f"(d[O + 81]), "+f"(d[O + 82]), "+f"(d[O + 83]), "+f"(d[O + 84]), "+f"(d[O + 85]), "+f"(d[O + 86]), "+f"(d[O + 87]),
      "+f"(d[O + 88]), "+f"(d[O + 89]), "+f"(d[O + 90]), "+f"(d[O + 91]), "+f"(d[O + 92]), "+f"(d[O + 93]), "+f"(d[O + 94]), "+f"(d[O + 95]),
      "+f"(d[O + 96]), "+f"(d[O + 97]), "+f"(d[O + 98]), "+f"(d[O + 99]), "+f"(d[O + 100]), "+f"(d[O + 101]), "+f"(d[O + 102]), "+f"(d[O + 103]),
      "+f"(d[O + 104]), "+f"(d[O + 105]), "+f"(d[O + 106]), "+f"(d[O + 107]), "+f"(d[O + 108]), "+f"(d[O + 109]), "+f"(d[O + 110]), "+f"(d[O + 111]),
      "+f"(d[O + 112]), "+f"(d[O + 113]), "+f"(d[O + 114]), "+f"(d[O + 115]), "+f"(d[O + 116]), "+f"(d[O + 117]), "+f"(d[O + 118]), "+f"(d[O + 119]),
      "+f"(d[O + 120]), "+f"(d[O + 121]), "+f"(d[O + 122]), "+f"(d[O + 123]), "+f"(d[O + 124]), "+f"(d[O + 125]), "+f"(d[O + 126]), "+f"(d[O + 127])
    : "r"(a.x), "r"(a.y), "r"(a.z), "r"(a.w), "l"(db));
}
template <int O, int T> __device__ __forceinline__ void wgmma_rs_n256_init(float (&d)[T], const uint4& a, uint64_t db) {
  asm volatile("{\n.reg .pred p;\nsetp.ne.b32 p, 0, 0;\n"
    "wgmma.mma_async.sync.aligned.m64n256k16.f32.bf16.bf16 "
    "{%0, %1, %2, %3, %4, %5, %6, %7, %8, %9, %10, %11, %12, %13, %14, %15, "
    "%16, %17, %18, %19, %20, %21, %22, %23, %24, %25, %26, %27, %28, %29, %30, %31, "
    "%32, %33, %34, %35, %36, %37, %38, %39, %40, %41, %42, %43, %44, %45, %46, %47, "
    "%48, %49, %50, %51, %52, %53, %54, %55, %56, %57, %58, %59, %60, %61, %62, %63, "
    "%64, %65, %66, %67, %68, %69, %70, %71, %72, %73, %74, %75, %76, %77, %78, %79, "
    "%80, %81, %82, %83, %84, %85, %86, %87, %88, %89, %90, %91, %92, %93, %94, %95, "
    "%96, %97, %98, %99, %100, %101, %102, %103, %104, %105, %106, %107, %108, %109, %110, %111, "
    "%112, %113, %114, %115, %116, %117, %118, %119, %120, %121, %122, %123, %124, %125, %126, %127}, "
    "{%128, %129, %130, %131}, %132, p, 1, 1, 1;\n}\n"
    : "=f"(d[O + 0]), "=f"(d[O + 1]), "=f"(d[O + 2]), "=f"(d[O + 3]), "=f"(d[O + 4]), "=f"(d[O + 5]), "=f"(d[O + 6]), "=f"(d[O + 7]),
      "=f"(d[O + 8]), "=f"(d[O + 9]), "=f"(d[O + 10]), "=f"(d[O + 11]), "=f"(d[O + 12]), "=f"(d[O + 13]), "=f"(d[O + 14]), "=f"(d[O + 15]),
      "=f"(d[O + 16]), "=f"(d[O + 17]), "=f"(d[O + 18]), "=f"(d[O + 19]), "=f"(d[O + 20]), "=f"(d[O + 21]), "=f"(d[O + 22]), "=f"(d[O + 23]),
      "=f"(d[O + 24]), "=f"(d[O + 25]), "=f"(d[O + 26]), "=f"(d[O + 27]), "=f"(d[O + 28]), "=f"(d[O + 29]), "=f"(d[O + 30]), "=f"(d[O + 31]),
      "=f"(d[O + 32]), "=f"(d[O + 33]), "=f"(d[O + 34]), "=f"(d[O + 35]), "=f"(d[O + 36]), "=f"(d[O + 37]), "=f"(d[O + 38]), "=f"(d[O + 39]),
      "=f"(d[O + 40]), "=f"(d[O + 41]), "=f"(d[O + 42]), "=f"(d[O + 43]), "=f"(d[O + 44]), "=f"(d[O + 45]), "=f"(d[O + 46]), "=f"(d[O + 47]),
      "=f"(d[O + 48]), "=f"(d[O + 49]), "=f"(d[O + 50]), "=f"(d[O + 51]), "=f"(d[O + 52]), "=f"(d[O + 53]), "=f"(d[O + 54]), "=f"(d[O + 55]),
      "=f"(d[O + 56]), "=f"(d[O + 57]), "=f"(d[O + 58]), "=f"(d[O + 59]), "=f"(d[O + 60]), "=f"(d[O + 61]), "=f"(d[O + 62]), "=f"(d[O + 63]),
      "=f"(d[O + 64]), "=f"(d[O + 65]), "=f"(d[O + 66]), "=f"(d[O + 67]), "=f"(d[O + 68]), "=f"(d[O + 69]), "=f"(d[O + 70]), "=f"(d[O + 71]),
      "=f"(d[O + 72]), "=f"(d[O + 73]), "=f"(d[O + 74]), "=f"(d[O + 75]), "=f"(d[O + 76]), "=f"(d[O + 77]), "=f"(d[O + 78]), "=f"(d[O + 79]),
      "=f"(d[O + 80]), "=f"(d[O + 81]), "=f"(d[O + 82]), "=f"(d[O + 83]), "=f"(d[O + 84]), "=f"(d[O + 85]), "=f"(d[O + 86]), "=f"(d[O + 87]),
      "=f"(d[O + 88]), "=f"(d[O + 89]), "=f"(d[O + 90]), "=f"(d[O + 91]), "=f"(d[O + 92]), "=f"(d[O + 93]), "=f"(d[O + 94]), "=f"(d[O + 95]),
      "=f"(d[O + 96]), "=f"(d[O + 97]), "=f"(d[O + 98]), "=f"(d[O + 99]), "=f"(d[O + 100]), "=f"(d[O + 101]), "=f"(d[O + 102]), "=f"(d[O + 103]),
      "=f"(d[O + 104]), "=f"(d[O + 105]), "=f"(d[O + 106]), "=f"(d[O + 107]), "=f"(d[O + 108]), "=f"(d[O + 109]), "=f"(d[O + 110]), "=f"(d[O + 111]),
      "=f"(d[O + 112]), "=f"(d[O + 113]), "=f"(d[O + 114]), "=f"(d[O + 115]), "=f"(d[O + 116]), "=f"(d[O + 117]), "=f"(d[O + 118]), "=f"(d[O + 119]),
      "=f"(d[O + 120]), "=f"(d[O + 121]), "=f"(d[O + 122]), "=f"(d[O + 123]), "=f"(d[O + 124]), "=f"(d[O + 125]), "=f"(d[O + 126]), "=f"(d[O + 127])
    : "r"(a.x), "r"(a.y), "r"(a.z), "r"(a.w), "l"(db));
}
template <bool INIT, int O, int T> __device__ __forceinline__ void wgmma_n256(float (&d)[T], const uint4& a, uint64_t db) {
  if constexpr (INIT) wgmma_rs_n256_init<O>(d, a, db); else wgmma_rs_n256<O>(d, a, db);
}

template <int N> __device__ __forceinline__ void load_pk(uint4* a, const uint4* p) {
#pragma unroll
  for (int i = 0; i < N; i++) a[i] = ld_ll(p + i * 32);
}
__device__ __forceinline__ uint32_t xor_or(uint32_t a, uint32_t b, uint32_t t) {
  uint32_t r;
  asm("lop3.b32 %0, %1, %2, %3, 0x7E;" : "=r"(r) : "r"(a), "r"(b), "r"(t));
  return r;
}
template <int N> __device__ __forceinline__ bool ok_pk(const uint4* a, uint32_t tag) {
  static_assert(N % 2 == 0, "");
  uint32_t x = xor_or(a[0].x, a[1].x, tag);
#pragma unroll
  for (int i = 2; i < N; i += 2) x |= xor_or(a[i].x, a[i + 1].x, tag);
  return __all_sync(0xffffffffu, (x & 1u) == 0u);
}
template <int N> __device__ __forceinline__ void ensure_pk(uint4* a, const uint4* p, uint32_t tag) {
  if (ok_pk<N>(a, tag)) return;
  uint32_t n = 0;
  do { load_pk<N>(a, p); } while (!ok_pk<N>(a, tag) && ++n < SPIN_LIMIT);
}

constexpr int NSTAGE = 44;
constexpr int ST_WO = 8, ST_G1 = 12, ST_G2 = 20, ST_DN = 28;
__host__ __device__ constexpr int st_len(int s) { return s < ST_WO ? 3 : s < ST_G1 ? 2 : s < ST_G2 ? 4 : s < ST_DN ? 3 : 2; }
__host__ __device__ constexpr int st_g0(int s) {
  int pos = 0, g0 = 0;
  for (int i = 0; i <= s; i++) {
    if (pos + st_len(i) > NGRAN) pos = 0;
    g0 = pos;
    pos += st_len(i);
  }
  return g0;
}
__host__ __device__ constexpr int cnt_first(int g, int s) {
  int n = 0;
  for (int i = 0; i < s; i++) n += (st_g0(i) == g);
  return n;
}
__host__ __device__ constexpr int cnt_cover(int g, int s) {
  int n = 0;
  for (int i = 0; i < s; i++) n += (g >= st_g0(i) && g < st_g0(i) + st_len(i));
  return n;
}
__host__ __device__ constexpr uint32_t flip_mask(int s0, int s1) {
  uint32_t m = 0;
  for (int i = s0; i < s1; i++) m ^= ((1u << st_len(i)) - 1u) << st_g0(i);
  return m;
}
__host__ __device__ constexpr int dn_q(int i) { return i < 3 ? 0 : i < 6 ? 1 : i == 6 ? 0 : i == 7 ? 1 : i < 12 ? 2 : 3; }
__host__ __device__ constexpr int dn_par(int i) { return i < 8 ? (i == 2 || i == 4 || i >= 6) : (i & 1); }
__host__ __device__ constexpr int dn_kh(int i) { return i < 8 ? (i == 1 || i >= 5) : ((i & 3) >= 2); }
template <int I> struct IC { static constexpr int value = I; };
template <int B, int E, typename F> __device__ __forceinline__ void static_for(F&& f) {
  if constexpr (B < E) { f(IC<B>{}); static_for<B + 1, E>(f); }
}
template <int S> __device__ __forceinline__ void cons_acquire(uint32_t sbase, uint32_t L) {
  constexpr int g0 = st_g0(S);
  constexpr uint32_t p0 = cnt_first(g0, S) & 1, odd = cnt_first(g0, NSTAGE) & 1;
  mbar_wait(sbase + SM_MISC + BAR_FULL + 8 * g0, p0 ^ (L & odd));
}
template <int S> __device__ __forceinline__ void cons_release(uint32_t sbase, int lane) {
  if (lane < st_len(S)) mbar_arrive(sbase + SM_MISC + BAR_EMPTY + 8 * st_g0(S) + 8 * lane);
}
__device__ __forceinline__ bool elect_one() {
  uint32_t p;
  asm volatile("{\n.reg .pred P;\nelect.sync _|P, 0xffffffff;\nselp.u32 %0, 1, 0, P;\n}" : "=r"(p));
  return p != 0;
}
struct ProdRing { uint32_t pos, par; };
template <int N> __device__ __forceinline__ uint32_t prod_acquire(uint32_t sbase, ProdRing& r) {
  if (r.pos + N > NGRAN) r.pos = 0;
  const uint32_t g0 = r.pos;
#pragma unroll
  for (uint32_t i = 0; i < N; i++) mbar_wait(sbase + SM_MISC + BAR_EMPTY + 8 * (g0 + i), ((r.par >> (g0 + i)) & 1u) ^ 1u);
  r.par ^= ((1u << N) - 1u) << g0;
  r.pos = g0 + N;
  return g0;
}
template <int S> __device__ __forceinline__ void prod_acquire_static(uint32_t sbase, uint32_t L) {
  constexpr int g0 = st_g0(S);
  static_for<0, st_len(S)>([&](auto I) {
    constexpr int g = g0 + I.value;
    constexpr uint32_t p0 = cnt_cover(g, S) & 1, odd = cnt_cover(g, NSTAGE) & 1;
    mbar_wait(sbase + SM_MISC + BAR_EMPTY + 8 * g, p0 ^ (L & odd) ^ 1u);
  });
}
template <int S, int KSTEP_BYTES, int LBO, int SBO, int SWZ> __device__ __forceinline__ constexpr uint64_t st_desc(int k) {
  return (uint64_t)((SMEM_ORIGIN + st_g0(S) * GRAN + k * KSTEP_BYTES) >> 4) | ((uint64_t)(LBO >> 4) << 16) |
         ((uint64_t)(SBO >> 4) << 32) | ((uint64_t)SWZ << 62);
}

__device__ __forceinline__ void combine_stats(const uint4& p0, const uint4& p1, float& mean_lo, float& rstd_lo, float& mean_hi, float& rstd_hi) {
  float m0 = __uint_as_float(p0.x), q0 = __uint_as_float(p0.y), m0h = __uint_as_float(p0.z), q0h = __uint_as_float(p0.w);
  float m1 = __uint_as_float(p1.x), q1 = __uint_as_float(p1.y), m1h = __uint_as_float(p1.z), q1h = __uint_as_float(p1.w);
  float s = m0 + m1, sh = m0h + m1h;
  s += __shfl_xor_sync(0xffffffffu, s, 1); sh += __shfl_xor_sync(0xffffffffu, sh, 1);
  s += __shfl_xor_sync(0xffffffffu, s, 2); sh += __shfl_xor_sync(0xffffffffu, sh, 2);
  mean_lo = s * 0.125f; mean_hi = sh * 0.125f;
  float d0 = m0 - mean_lo, d1 = m1 - mean_lo, d0h = m0h - mean_hi, d1h = m1h - mean_hi;
  float t = q0 + q1 + 64.f * (d0 * d0 + d1 * d1), th = q0h + q1h + 64.f * (d0h * d0h + d1h * d1h);
  t += __shfl_xor_sync(0xffffffffu, t, 1); th += __shfl_xor_sync(0xffffffffu, th, 1);
  t += __shfl_xor_sync(0xffffffffu, t, 2); th += __shfl_xor_sync(0xffffffffu, th, 2);
  rstd_lo = rsqrtf(t * (1.f / 512.f) + 1e-5f);
  rstd_hi = rsqrtf(th * (1.f / 512.f) + 1e-5f);
}
__device__ __forceinline__ uint4 local_stats(const float (&v)[32]) {
  float s = 0.f, sh = 0.f;
#pragma unroll
  for (int i = 0; i < 4; i++) {
    s += (v[8 * i + 0] + v[8 * i + 1]) + (v[8 * i + 4] + v[8 * i + 5]);
    sh += (v[8 * i + 2] + v[8 * i + 3]) + (v[8 * i + 6] + v[8 * i + 7]);
  }
  s += __shfl_xor_sync(0xffffffffu, s, 1); sh += __shfl_xor_sync(0xffffffffu, sh, 1);
  s += __shfl_xor_sync(0xffffffffu, s, 2); sh += __shfl_xor_sync(0xffffffffu, sh, 2);
  float m = s * (1.f / 64.f), mh = sh * (1.f / 64.f);
  float q = 0.f, qh = 0.f;
#pragma unroll
  for (int i = 0; i < 4; i++) {
    float a = v[8 * i + 0] - m, b = v[8 * i + 1] - m, c = v[8 * i + 4] - m, d = v[8 * i + 5] - m;
    q += (a * a + b * b) + (c * c + d * d);
    float e = v[8 * i + 2] - mh, f = v[8 * i + 3] - mh, g = v[8 * i + 6] - mh, h = v[8 * i + 7] - mh;
    qh += (e * e + f * f) + (g * g + h * h);
  }
  q += __shfl_xor_sync(0xffffffffu, q, 1); qh += __shfl_xor_sync(0xffffffffu, qh, 1);
  q += __shfl_xor_sync(0xffffffffu, q, 2); qh += __shfl_xor_sync(0xffffffffu, qh, 2);
  return make_uint4(__float_as_uint(m), __float_as_uint(q), __float_as_uint(mh), __float_as_uint(qh));
}

__device__ __forceinline__ int slab_row0(int c, int g, int w) { return 1024 * g + 64 * c + 32 * (w >> 1) + (w & 1); }

__device__ __forceinline__ void owner_ln_publish(uint32_t sbase, const float (&v)[32], uint32_t tphase, uint32_t tag_xn) {
  PHASE_VARS;
  const uint32_t bars = sbase + SM_MISC;
  const int oslab = 4 * g + ca;
  const int step0 = 16 * cbit + 4 * w;
  TS(40 + 4 * tphase);
  uint4 st = local_stats(v);
  const uint32_t tb = bars + BAR_TSTAT + 8 * g;
  const uint32_t slot = sbase + SM_TSTAT + g * 1024 + (4 * cbit + w) * 128 + qr * 16;
  if (t128 == 0) mbar_expect_tx(tb, 1024);
  if (qc == 0) {
    st_async128(mapa(slot, 0), st, mapa(tb, 0));
    st_async128(mapa(slot, 1), st, mapa(tb, 1));
  }
  uint4* xn = g_xn + ((c * 8 + oslab) * 32 + step0) * 32 + lane;
  uint4* xr = g_xraw + ((c * 8 + oslab) * 32 + step0) * 32 + lane;
  TS(41 + 4 * tphase);
  mbar_wait(tb, tphase);
  TS(42 + 4 * tphase);
  const uint32_t rd = sbase + SM_TSTAT + g * 1024 + qc * 256 + qr * 16;
  uint4 p0 = lds128(rd), p1 = lds128(rd + 128);
  float ml, rl, mh, rh;
  combine_stats(p0, p1, ml, rl, mh, rh);
  const float bl = -ml * rl, bh = -mh * rh;
#pragma unroll
  for (int i = 0; i < 4; i++) {
    uint4 o;
    o.x = set_tag(pack2(fmaf(v[8 * i + 0], rl, bl), fmaf(v[8 * i + 1], rl, bl)), tag_xn);
    o.y = pack2(fmaf(v[8 * i + 2], rh, bh), fmaf(v[8 * i + 3], rh, bh));
    o.z = pack2(fmaf(v[8 * i + 4], rl, bl), fmaf(v[8 * i + 5], rl, bl));
    o.w = pack2(fmaf(v[8 * i + 6], rh, bh), fmaf(v[8 * i + 7], rh, bh));
    st_ll(xn + i * 32, o);
  }
#pragma unroll
  for (int i = 0; i < 4; i++) {
    uint4 o;
    o.x = set_tag(pack2(v[8 * i + 0], v[8 * i + 1]), 1u);
    o.y = pack2(v[8 * i + 2], v[8 * i + 3]);
    o.z = pack2(v[8 * i + 4], v[8 * i + 5]);
    o.w = pack2(v[8 * i + 6], v[8 * i + 7]);
    st_ll(xr + i * 32, o);
  }
}

__device__ __forceinline__ uint4 pack8(const float* a) {
  return make_uint4(pack2(a[0], a[1]), pack2(a[2], a[3]), pack2(a[4], a[5]), pack2(a[6], a[7]));
}
template <int U> __device__ __forceinline__ uint4 glu8(const float* g, float cl, float ch) {
  return make_uint4(pack2(g[0] * cl * g[U], g[1] * cl * g[U + 1]), pack2(g[2] * ch * g[U + 2], g[3] * ch * g[U + 3]),
                    pack2(g[4] * cl * g[U + 4], g[5] * cl * g[U + 5]), pack2(g[6] * ch * g[U + 6], g[7] * ch * g[U + 7]));
}
__device__ __forceinline__ uint32_t hfma2(uint32_t a, uint32_t b, uint32_t c) {
  uint32_t d;
  asm("fma.rn.bf16x2 %0, %1, %2, %3;" : "=r"(d) : "r"(a), "r"(b), "r"(c));
  return d;
}
__device__ __forceinline__ void keep4(const uint4 (&a)[4]) { keep(a[0]); keep(a[1]); keep(a[2]); keep(a[3]); }

#define STAGGER 0

__global__ void __launch_bounds__(NTHREADS, 1)
fused_kernel(const __grid_constant__ CUtensorMap m_qkv, const __grid_constant__ CUtensorMap m_wo,
             const __grid_constant__ CUtensorMap m_gu2, const __grid_constant__ CUtensorMap m_gu1,
             const __grid_constant__ CUtensorMap m_guh, const __grid_constant__ CUtensorMap m_wd112,
             const __grid_constant__ CUtensorMap m_wd80, const __grid_constant__ CUtensorMap m_wd32,
             const __nv_bfloat16* __restrict__ x_in,
             __nv_bfloat16* __restrict__ out, const char* __restrict__ w_o, const char* __restrict__ w_g,
             const char* __restrict__ w_u, const char* __restrict__ w_d
) {
  extern __shared__ __align__(1024) unsigned char smem_raw[];
  const uint32_t sbase = smem_u32(smem_raw);
  const uint32_t bars = sbase + SM_MISC;
  if ((sbase & 0xFFFFFFu) != SMEM_ORIGIN) return;
  TG(60);

  if (threadIdx.x == 0) {
    for (int i = 0; i < NGRAN; i++) { mbar_init(bars + BAR_FULL + 8 * i, 1); mbar_init(bars + BAR_EMPTY + 8 * i, 8); }
    for (int i = 0; i < 4; i++) mbar_init(bars + BAR_HRECV + 8 * i, 1);
    for (int i = 0; i < 2; i++) { mbar_init(bars + BAR_HREADY + 8 * i, 4); mbar_init(bars + BAR_TSTAT + 8 * i, 1); }
    asm volatile("fence.mbarrier_init.release.cluster;" ::: "memory");
  }
  __syncthreads();
  asm volatile("barrier.cluster.arrive.release.aligned;" ::: "memory");

  if (threadIdx.x >= 256) {
    asm volatile("setmaxnreg.dec.sync.aligned.u32 40;");
    const int warp = threadIdx.x >> 5, lane = threadIdx.x & 31;
    const int j = blockIdx.x & 7, b = j & 1;
    if (warp == 8) {
      ProdRing r{0u, 0u};
      const int cb0 = 224 * j + 32 * b, hb0 = 224 * j + 192 * (b ^ 1);
      const int jp = j ^ 1, cbp = 224 * jp + 32 * (b ^ 1), hbp = 224 * jp + 192 * b;
#pragma unroll 1
      for (uint32_t L = 0; L < 2; L++) {
        r.pos = 0;
        PSTOP_AT(L == 0 ? 0 : 3);
#pragma unroll 1
        for (int kb = 0; kb < 8; kb++) {
          const uint32_t g0 = prod_acquire<3>(sbase, r);
          if (elect_one()) {
            mbar_expect_tx(bars + BAR_FULL + 8 * g0, 24576);
            tma_3d(sbase + g0 * GRAN, &m_qkv, bars + BAR_FULL + 8 * g0, 64 * j, 64 * kb, 0);
          }
        }
        PSTOP_AT(10 * L + 1);
#pragma unroll 1
        for (int i = 0; i < 4; i++) {
          const uint32_t g0 = prod_acquire<2>(sbase, r);
          if (elect_one()) {
            mbar_expect_tx(bars + BAR_FULL + 8 * g0, 16384);
            tma_2d(sbase + g0 * GRAN, &m_wo, bars + BAR_FULL + 8 * g0, 64 * j, 128 * i);
          }
        }
        PSTOP_AT(10 * L + 2);
#pragma unroll 1
        for (int kb = 0; kb < 8; kb++) {
          const uint32_t g0 = prod_acquire<4>(sbase, r);
          if (elect_one()) {
            mbar_expect_tx(bars + BAR_FULL + 8 * g0, 32768);
            tma_4d(sbase + g0 * GRAN, &m_gu2, bars + BAR_FULL + 8 * g0, cb0, 64 * kb, 0, 0);
          }
        }
#pragma unroll 1
        for (int kb = 0; kb < 8; kb++) {
          const uint32_t g0 = prod_acquire<3>(sbase, r);
          if (elect_one()) {
            mbar_expect_tx(bars + BAR_FULL + 8 * g0, 24576);
            tma_4d(sbase + g0 * GRAN, &m_gu1, bars + BAR_FULL + 8 * g0, cb0 + 128, 64 * kb, 0, 0);
            tma_3d(sbase + g0 * GRAN + 16384, &m_guh, bars + BAR_FULL + 8 * g0, hb0, 64 * kb, 0);
          }
        }
        static_for<0, 16>([&](auto I) {
          constexpr int i = I.value, g0 = st_g0(ST_DN + i);
          prod_acquire_static<ST_DN + i>(sbase, L);
          if (elect_one()) {
            const uint32_t dst = sbase + g0 * GRAN, fb = bars + BAR_FULL + 8 * g0;
            const int n0 = 256 * b + 64 * dn_q(i);
            mbar_expect_tx(fb, 14336);
            if constexpr (dn_kh(i) == 0) {
              tma_2d(dst, &m_wd112, fb, n0, dn_par(i) ? cbp : cb0);
            } else {
              tma_2d(dst, &m_wd80, fb, n0, (dn_par(i) ? cbp : cb0) + 112);
              tma_2d(dst + 10240, &m_wd32, fb, n0, dn_par(i) ? hbp : hb0);
            }
          }
        });
        r.par ^= flip_mask(ST_DN, NSTAGE);
      }
    } else if (warp == 9) {
      const int cta = blockIdx.x;
      if (lane == 0) l2_prefetch(w_o + cta * 4096, 4096);
      if (lane == 1) l2_prefetch(w_g + cta * 14336, 14336);
      if (lane == 2) l2_prefetch(w_u + cta * 14336, 14336);
      if (lane == 3) l2_prefetch(w_d + cta * 14336, 14336);
    }
    __syncwarp();
    asm volatile("barrier.cluster.wait.acquire.aligned; // producer" ::: "memory");
    asm volatile("barrier.cluster.arrive.release.aligned;\nbarrier.cluster.wait.acquire.aligned; // producer" ::: "memory");
  } else {
    asm volatile("setmaxnreg.inc.sync.aligned.u32 232;");
    TS(0);
    TG(61);

    {
      PHASE_VARS;
      const int step0 = 16 * cbit + 4 * w;
      float v[32];
      const uint32_t* xp = reinterpret_cast<const uint32_t*>(x_in + (size_t)(slab_row0(c, g, ca) + 2 * qr) * 512 + step0 * 16 + qc * 2);
      uint32_t xw[16];
#pragma unroll
      for (int i = 0; i < 4; i++) {
        xw[4 * i] = __ldg(xp + i * 8); xw[4 * i + 1] = __ldg(xp + 16 * 256 + i * 8);
        xw[4 * i + 2] = __ldg(xp + i * 8 + 4); xw[4 * i + 3] = __ldg(xp + 16 * 256 + i * 8 + 4);
      }
      asm volatile("barrier.cluster.wait.acquire.aligned; // consumer" ::: "memory");
      if (STAGGER > 0 && g == 1) {
        const long long t0 = clock64();
        while (clock64() - t0 < STAGGER) {}
      }
#pragma unroll
      for (int i = 0; i < 16; i++) { v[2 * i] = bf_lo(xw[i]); v[2 * i + 1] = bf_hi(xw[i]); }
      owner_ln_publish(sbase, v, 0u, 1u);
    }
    STOP_AT(0);
    TS(1);

#pragma unroll 1
    for (uint32_t L = 0; L < 2; L++) {
      const uint32_t tag = L ^ 1;
      {
        PHASE_VARS;
        uint4 qf[4], kf[4], vf[4], pp[4];
        const int blk = 16 * g + c;
        const uint4* halo_src = g_halo + ((((L * 32 + (blk > 0 ? blk - 1 : 0)) * 8 + j) * 2 + (w & 1)) * 4) * 32 + lane;
        {
          float acc[96];
          uint4 A[3][4];
          const uint4* xs = g_xn + ((c * 8 + slab) * 32) * 32 + lane;
          bar_wg(1 + g);
          load_pk<4>(A[0], xs);
          ensure_pk<4>(A[0], xs, tag);
          TS(2 + 20 * L);
          load_pk<4>(A[1], xs + 128); load_pk<4>(A[2], xs + 256);
          static_for<0, 8>([&](auto I) {
            constexpr int kb = I.value;
            cons_acquire<kb>(sbase, L);
            wg_fence();
            static_for<0, 4>([&](auto K) { constexpr int k = K.value; wgmma_n192<kb == 0 && k == 0, 0>(acc, A[kb % 3][k], st_desc<kb, 2048, 8192, 1024, 1>(k)); });
            wg_commit();
            wg_wait<0>();
            keep4(A[kb % 3]);
            cons_release<kb>(sbase, lane);
            if constexpr (kb + 1 < 8) ensure_pk<4>(A[(kb + 1) % 3], xs + (kb + 1) * 128, tag);
            if constexpr (kb + 3 < 8) load_pk<4>(A[kb % 3], xs + (kb + 3) * 128);
          });
          wg_wait<0>();
          TS(3 + 20 * L);
          fence_acc(acc);
#pragma unroll
          for (int h = 0; h < 4; h++) {
            kf[h] = pack8(&acc[32 + 8 * h]);
            const uint4 t = pack8(&acc[64 + 8 * h]);
            vf[h] = make_uint4(movm(t.x), movm(t.y), movm(t.z), movm(t.w));
            pp[h] = make_uint4(kf[h].y, kf[h].w, vf[h].y, vf[h].w);
          }
          if (w >= 2 && blk < 31) {
            uint4* hd = g_halo + ((((L * 32 + blk) * 8 + j) * 2 + (w & 1)) * 4) * 32 + lane;
#pragma unroll
            for (int h = 0; h < 4; h++) { uint4 t = pp[h]; t.x |= 1u; st_ll(hd + h * 32, t); }
          }
#pragma unroll
          for (int h = 0; h < 4; h++) sts128(areg + (28 + h) * 2048 + t128 * 16, pp[h]);
          if (w < 2 && blk > 0) load_pk<4>(pp, halo_src);
#pragma unroll
          for (int h = 0; h < 4; h++) qf[h] = pack8(&acc[8 * h]);
        }
        bar_wg(1 + g);
        const bool first = (w < 2) && (blk == 0);
        if (w >= 2) {
#pragma unroll
          for (int h = 0; h < 4; h++) pp[h] = lds128(areg + (28 + h) * 2048 + (t128 - 64) * 16);
        }
        bar_wg(1 + g);
        if (w < 2 && blk > 0) {
          ensure_pk<4>(pp, halo_src, 1u);
          uint4* hz = const_cast<uint4*>(halo_src);
#pragma unroll
          for (int h = 0; h < 4; h++) st_ll(hz + h * 32, make_uint4(0, 0, 0, 0));
        }
        TS(4 + 20 * L);
        const bool n0 = 2 * qc <= qr, n1 = 2 * qc + 1 <= qr;
        const uint32_t msk = (n0 ? 0xffffu : 0u) | (n1 ? 0xffff0000u : 0u);
        const float sc = 0.25f * 1.4426950408889634f;
        const float NEG = -1e30f;
        uint4* od = g_o + ((c * 8 + slab) * 32 + 4 * j) * 32 + lane;
        float l0[4], l1[4], h0[4], h1[4], ml[4], mh[4];
#pragma unroll
        for (int h = 0; h < 4; h++) {
          float sp[4], s0[4], s1[4];
          mma16816_z(sp, qf[h], pp[h].x, pp[h].y);
          mma16816_z(s0, qf[h], kf[h].x, kf[h].z);
          mma16816_z(s1, qf[h], kf[h].y, kf[h].w);
          if (first) { sp[0] = NEG; sp[1] = NEG; }
          l0[h] = n0 ? s0[0] : sp[0]; l1[h] = n1 ? s0[1] : sp[1];
          h0[h] = n0 ? s1[2] : s0[2]; h1[h] = n1 ? s1[3] : s0[3];
          ml[h] = fmaxf(l0[h], l1[h]); mh[h] = fmaxf(h0[h], h1[h]);
        }
#pragma unroll
        for (int h = 0; h < 4; h++) { ml[h] = fmaxf(ml[h], __shfl_xor_sync(0xffffffffu, ml[h], 1)); mh[h] = fmaxf(mh[h], __shfl_xor_sync(0xffffffffu, mh[h], 1)); }
#pragma unroll
        for (int h = 0; h < 4; h++) { ml[h] = fmaxf(ml[h], __shfl_xor_sync(0xffffffffu, ml[h], 2)); mh[h] = fmaxf(mh[h], __shfl_xor_sync(0xffffffffu, mh[h], 2)); }
        float sl[4], sh[4];
#pragma unroll
        for (int h = 0; h < 4; h++) {
          const float bl = -ml[h] * sc, bh = -mh[h] * sc;
          l0[h] = ex2(fmaf(l0[h], sc, bl)); l1[h] = ex2(fmaf(l1[h], sc, bl));
          h0[h] = ex2(fmaf(h0[h], sc, bh)); h1[h] = ex2(fmaf(h1[h], sc, bh));
          sl[h] = l0[h] + l1[h]; sh[h] = h0[h] + h1[h];
        }
#pragma unroll
        for (int h = 0; h < 4; h++) { sl[h] += __shfl_xor_sync(0xffffffffu, sl[h], 1); sh[h] += __shfl_xor_sync(0xffffffffu, sh[h], 1); }
#pragma unroll
        for (int h = 0; h < 4; h++) { sl[h] += __shfl_xor_sync(0xffffffffu, sl[h], 2); sh[h] += __shfl_xor_sync(0xffffffffu, sh[h], 2); }
#pragma unroll
        for (int h = 0; h < 4; h++) {
          const float il = rcp(sl[h]), ih = rcp(sh[h]);
          const uint32_t pl = pack2(l0[h] * il, l1[h] * il), ph = pack2(h0[h] * ih, h1[h] * ih);
          const uint4 P = make_uint4(pl & msk, ph & ~msk, 0u, ph & msk);
          float o0[4], o1[4];
          mma16816_z(o0, P, vf[h].x, vf[h].y);
          mma16816_z(o1, P, vf[h].z, vf[h].w);
          mma1688(o0, pl & ~msk, 0u, pp[h].z);
          mma1688(o1, pl & ~msk, 0u, pp[h].w);
          st_ll(od + h * 32, make_uint4(set_tag(pack2(o0[0], o0[1]), tag), pack2(o0[2], o0[3]), pack2(o1[0], o1[1]), pack2(o1[2], o1[3])));
        }
      }
      TS(5 + 20 * L);
      if (L == 0) { STOP_AT(1); } else { STOP_AT(11); }
      {
        PHASE_VARS;
        float acc[32];
        uint4 A[32], xr[4];
        const uint4* os = g_o + ((c * 8 + slab) * 32) * 32 + lane;
        uint4* xp = g_xraw + ((c * 8 + slab) * 32 + 4 * j) * 32 + lane;
        load_pk<4>(xr, xp);
        load_pk<4>(A, os);
        ensure_pk<4>(A, os, tag);
        TS(6 + 20 * L);
        load_pk<28>(A + 4, os + 128);
        static_for<0, 8>([&](auto I) {
          constexpr int kb = I.value;
          if constexpr ((kb & 1) == 0) cons_acquire<ST_WO + kb / 2>(sbase, L);
          if constexpr (kb > 0) ensure_pk<4>(A + 4 * kb, os + kb * 128, tag);
          wg_fence();
          static_for<0, 4>([&](auto K) {
            constexpr int k = K.value;
            wgmma_n64<kb == 0 && k == 0, 0>(acc, A[4 * kb + k], st_desc<ST_WO + kb / 2, 2048, 8192, 1024, 1>(4 * (kb & 1) + k));
          });
          wg_commit();
          if constexpr ((kb & 1) == 1) { wg_wait<0>(); cons_release<ST_WO + kb / 2>(sbase, lane); }
        });
        wg_wait<0>();
        TS(7 + 20 * L);
        fence_acc(acc);
#pragma unroll
        for (int k = 0; k < 32; k++) keep(A[k]);
        ensure_pk<4>(xr, xp, 1u);
#pragma unroll
        for (int i = 0; i < 4; i++) {
          acc[8 * i + 0] += bf_lo(xr[i].x); acc[8 * i + 1] += bf_hi(xr[i].x); acc[8 * i + 2] += bf_lo(xr[i].y); acc[8 * i + 3] += bf_hi(xr[i].y);
          acc[8 * i + 4] += bf_lo(xr[i].z); acc[8 * i + 5] += bf_hi(xr[i].z); acc[8 * i + 6] += bf_lo(xr[i].w); acc[8 * i + 7] += bf_hi(xr[i].w);
          uint4 o = pack8(&acc[8 * i]);
          o.x = set_tag(o.x, 0u);
          st_ll(xp + i * 32, o);
        }
        uint4 st = local_stats(acc);
        st.x = set_tag(st.x, tag);
        if (qc == 0) st_ll(g_stats + ((c * 8 + slab) * 8 + j) * 8 + qr, st);
      }
      TS(8 + 20 * L);
      if (L == 0) { STOP_AT(2); } else { STOP_AT(12); }
      uint4 hs[14];
      {
        PHASE_VARS;
        float acc[128];
        uint4 A[3][4];
        const uint4* xs = g_xraw + ((c * 8 + slab) * 32) * 32 + lane;
        const uint4* sp = g_stats + ((c * 8 + slab) * 8 + 2 * qc) * 8 + qr;
        const uint32_t sm = areg + t128 * 16;
        uint32_t rl2, rh2, bl2, bh2;
        float cl, ch;
        {
          uint4 p[2];
          load_pk<4>(A[0], xs);
          p[0] = ld_ll(sp); p[1] = ld_ll(sp + 8);
          for (uint32_t n = 0; !ok_pk<2>(p, tag) && n < SPIN_LIMIT; n++) { load_pk<4>(A[0], xs); p[0] = ld_ll(sp); p[1] = ld_ll(sp + 8); }
          TS(9 + 20 * L);
          load_pk<4>(A[1], xs + 128); load_pk<4>(A[2], xs + 256);
          float ml, rl, mh, rh;
          combine_stats(p[0], p[1], ml, rl, mh, rh);
          rl2 = pack2(rl, rl); rh2 = pack2(rh, rh);
          const float rlb = bf_lo(rl2), rhb = bf_lo(rh2);
          bl2 = pack2(-ml * rlb, -ml * rlb); bh2 = pack2(-mh * rhb, -mh * rhb);
          cl = rl / rlb; cl *= cl; ch = rh / rhb; ch *= ch;
        }
        auto normalise = [&](uint4 (&xb)[4], int kb) {
#pragma unroll
          for (int k = 0; k < 4; k++) {
            xb[k].x = hfma2(xb[k].x, rl2, bl2); xb[k].y = hfma2(xb[k].y, rh2, bh2);
            xb[k].z = hfma2(xb[k].z, rl2, bl2); xb[k].w = hfma2(xb[k].w, rh2, bh2);
            sts128(sm + (kb * 4 + k) * 2048, xb[k]);
          }
        };
        ensure_pk<4>(A[0], xs, 0u);
        normalise(A[0], 0);
        static_for<0, 8>([&](auto I) {
          constexpr int kb = I.value;
          cons_acquire<ST_G1 + kb>(sbase, L);
          wg_fence();
          static_for<0, 4>([&](auto K) { constexpr int k = K.value; wgmma_n256<kb == 0 && k == 0, 0>(acc, A[kb % 3][k], st_desc<ST_G1 + kb, 2048, 8192, 1024, 1>(k)); });
          wg_commit();
          wg_wait<0>();
          keep4(A[kb % 3]);
          cons_release<ST_G1 + kb>(sbase, lane);
          if constexpr (kb + 1 < 8) ensure_pk<4>(A[(kb + 1) % 3], xs + (kb + 1) * 128, 0u);
          if constexpr (kb + 3 < 8) load_pk<4>(A[kb % 3], xs + (kb + 3) * 128);
          if constexpr (kb + 1 < 8) normalise(A[(kb + 1) % 3], kb + 1);
        });
        wg_wait<0>();
        TS(10 + 20 * L);
        fence_acc(acc);
        uint4 B[2][4];
#pragma unroll
        for (int k = 0; k < 4; k++) B[0][k] = lds128(sm + k * 2048);
#pragma unroll
        for (int s = 0; s < 8; s++) hs[s] = glu8<32>(&acc[64 * (s >> 2) + 8 * (s & 3)], cl, ch);
        float acc2[96];
        const uint32_t hdst = mapa(sm, cbit ^ 1);
        const uint32_t hbar1 = mapa(bars + BAR_HRECV + 16 * g, cbit ^ 1);
        if (t128 == 0) { mbar_expect_tx(bars + BAR_HRECV + 16 * g, 8 * 2048); mbar_expect_tx(bars + BAR_HRECV + 16 * g + 8, 6 * 2048); }
        static_for<0, 8>([&](auto I) {
          constexpr int kb = I.value;
          cons_acquire<ST_G2 + kb>(sbase, L);
          wg_fence();
          static_for<0, 4>([&](auto K) {
            constexpr int k = K.value;
            wgmma_n128<kb == 0 && k == 0, 0>(acc2, B[kb & 1][k], st_desc<ST_G2 + kb, 2048, 8192, 1024, 1>(k));
            wgmma_n64<kb == 0 && k == 0, 64>(acc2, B[kb & 1][k], st_desc<ST_G2 + kb, 1024, 4096, 512, 2>(k) + (16384 >> 4));
          });
          wg_commit();
          if constexpr (kb + 1 < 8) {
#pragma unroll
            for (int k = 0; k < 4; k++) B[(kb + 1) & 1][k] = lds128(sm + ((kb + 1) * 4 + k) * 2048);
          }
          wg_wait<0>();
          keep4(B[kb & 1]);
          cons_release<ST_G2 + kb>(sbase, lane);
          if constexpr (kb == 3) {
            __syncwarp();
            if (lane == 0) mbar_arrive_remote(mapa(bars + BAR_HREADY + 8 * g, cbit ^ 1));
          }
          if constexpr (kb >= 4) {
            if constexpr (kb == 4) mbar_wait(bars + BAR_HREADY + 8 * g, L);
            st_async128(hdst + (2 * kb - 8) * 2048, hs[2 * kb - 8], hbar1);
            st_async128(hdst + (2 * kb - 7) * 2048, hs[2 * kb - 7], hbar1);
          }
        });
        wg_wait<0>();
        TS(11 + 20 * L);
        fence_acc(acc2);
#pragma unroll
        for (int s = 0; s < 4; s++) hs[8 + s] = glu8<32>(&acc2[8 * s], cl, ch);
#pragma unroll
        for (int s = 0; s < 2; s++) hs[12 + s] = glu8<16>(&acc2[64 + 8 * s], cl, ch);
      }
      {
        PHASE_VARS;
        TS(12 + 20 * L);
        const uint32_t hdst = mapa(areg + t128 * 16, cbit ^ 1);
        const uint32_t hbar2 = mapa(bars + BAR_HRECV + 16 * g + 8, cbit ^ 1);
        uint4* pd = g_part + ((((c * 4 + w) * 2 + cbit) * 4 + ca) * 2 + g) * 16 * 32 + lane;
        uint4 hb[7];
        float a0[32], a1[32], a2[32], a3[32];
        auto publish = [&](float (&a)[32], int q, int s0, int s1) {
#pragma unroll
          for (int s = s0; s < s1; s++) {
            uint4 o = pack8(&a[8 * s]);
            o.x = set_tag(o.x, tag);
            st_ll(pd + (4 * q + s) * 32, o);
          }
        };
        static_for<0, 16>([&](auto I) {
          constexpr int i = I.value, q = dn_q(i), par = dn_par(i), kh = dn_kh(i);
          auto mm = [&](auto K) {
            constexpr int k = decltype(K)::value;
            constexpr bool init = (k == 0 && par == 0 && kh == 0);
            constexpr uint64_t db = st_desc<ST_DN + i, 2048, 8192, 1024, 1>(k);
            if constexpr (q == 0) { if constexpr (par) wgmma_n64<init, 0>(a0, hb[k], db); else wgmma_n64<init, 0>(a0, hs[7 * kh + k], db); }
            if constexpr (q == 1) { if constexpr (par) wgmma_n64<init, 0>(a1, hb[k], db); else wgmma_n64<init, 0>(a1, hs[7 * kh + k], db); }
            if constexpr (q == 2) { if constexpr (par) wgmma_n64<init, 0>(a2, hb[k], db); else wgmma_n64<init, 0>(a2, hs[7 * kh + k], db); }
            if constexpr (q == 3) { if constexpr (par) wgmma_n64<init, 0>(a3, hb[k], db); else wgmma_n64<init, 0>(a3, hs[7 * kh + k], db); }
          };
          cons_acquire<ST_DN + i>(sbase, L);
          wg_fence();
          mm(IC<0>{}); mm(IC<1>{}); mm(IC<2>{}); mm(IC<3>{}); mm(IC<4>{}); mm(IC<5>{}); mm(IC<6>{});
          wg_commit();
          wg_wait<0>();
          cons_release<ST_DN + i>(sbase, lane);
          if constexpr (i < 3) {
            st_async128(hdst + (8 + 2 * i) * 2048, hs[8 + 2 * i], hbar2);
            st_async128(hdst + (9 + 2 * i) * 2048, hs[9 + 2 * i], hbar2);
          }
          constexpr int n = i + 1;
          if constexpr (n < 16 && dn_par(n) && n != 4 && n != 7) {
            if constexpr (n == 2) { mbar_wait(bars + BAR_HRECV + 16 * g, L); TS(13 + 20 * L); }
            if constexpr (n == 6) { mbar_wait(bars + BAR_HRECV + 16 * g + 8, L); TS(14 + 20 * L); }
#pragma unroll
            for (int k = 0; k < 7; k++) { if constexpr (n != 2) keep(hb[k]); hb[k] = lds128(areg + t128 * 16 + (7 * dn_kh(n) + k) * 2048); }
          }
          if constexpr (i == 6) { fence_acc(a0); publish(a0, 0, 0, 2); }
          if constexpr (i == 7) { fence_acc(a1); publish(a0, 0, 2, 4); }
          if constexpr (i == 8) publish(a1, 1, 0, 2);
          if constexpr (i == 9) publish(a1, 1, 2, 4);
          if constexpr (i == 11) { fence_acc(a2); publish(a2, 2, 0, 2); }
          if constexpr (i == 12) publish(a2, 2, 2, 4);
        });
        wg_wait<0>();
        TS(15 + 20 * L);
        fence_acc(a3);
#pragma unroll
        for (int k = 0; k < 7; k++) { keep(hb[k]); keep(hs[7 + k]); }
        publish(a3, 3, 0, 4);
      }
      {
        PHASE_VARS;
        const int oslab = 4 * g + ca;
        const uint4* xq = g_xraw + ((c * 8 + oslab) * 32 + 16 * cbit + 4 * w) * 32 + lane;
        const uint4* ps = g_part + ((((c * 4 + ca) * 2 + cbit) * 4) * 2 + g) * 16 * 32 + (4 * w) * 32 + lane;
        uint4 xr[4], P[4][4];
        float v[32];
        load_pk<4>(xr, xq);
#pragma unroll
        for (int src = 0; src < 4; src++) load_pk<4>(P[src], ps + src * (2 * 16 * 32));
#pragma unroll
        for (int src = 0; src < 4; src++) ensure_pk<4>(P[src], ps + src * (2 * 16 * 32), tag);
        TS(16 + 20 * L);
        ensure_pk<4>(xr, xq, 0u);
#pragma unroll
        for (int i = 0; i < 4; i++) {
          v[8 * i + 0] = bf_lo(xr[i].x); v[8 * i + 1] = bf_hi(xr[i].x); v[8 * i + 2] = bf_lo(xr[i].y); v[8 * i + 3] = bf_hi(xr[i].y);
          v[8 * i + 4] = bf_lo(xr[i].z); v[8 * i + 5] = bf_hi(xr[i].z); v[8 * i + 6] = bf_lo(xr[i].w); v[8 * i + 7] = bf_hi(xr[i].w);
          float d[8] = {0, 0, 0, 0, 0, 0, 0, 0};
#pragma unroll
          for (int src = 0; src < 4; src++) {
            const uint4 p = P[src][i];
            d[0] += bf_lo(p.x); d[1] += bf_hi(p.x); d[2] += bf_lo(p.y); d[3] += bf_hi(p.y);
            d[4] += bf_lo(p.z); d[5] += bf_hi(p.z); d[6] += bf_lo(p.w); d[7] += bf_hi(p.w);
          }
#pragma unroll
          for (int k = 0; k < 8; k++) v[8 * i + k] += d[k];
        }
        if (L == 0) {
          owner_ln_publish(sbase, v, 1u, 0u);
        } else {
          uint32_t* op = reinterpret_cast<uint32_t*>(out + (size_t)(slab_row0(c, g, ca) + 2 * qr) * 512 + (16 * cbit + 4 * w) * 16 + qc * 2);
#pragma unroll
          for (int i = 0; i < 4; i++) {
            op[i * 8] = pack2(v[8 * i], v[8 * i + 1]);
            op[16 * 256 + i * 8] = pack2(v[8 * i + 2], v[8 * i + 3]);
            op[i * 8 + 4] = pack2(v[8 * i + 4], v[8 * i + 5]);
            op[16 * 256 + i * 8 + 4] = pack2(v[8 * i + 6], v[8 * i + 7]);
          }
        }
      }
      TS(17 + 20 * L);
      if (L == 0) { STOP_AT(3); }
    }
    TG(62);
    asm volatile("barrier.cluster.arrive.release.aligned;\nbarrier.cluster.wait.acquire.aligned; // consumer" ::: "memory");
    TG(63);
  }
}

typedef CUresult (*EncodeFn)(CUtensorMap*, CUtensorMapDataType, cuuint32_t, void*, const cuuint64_t*, const cuuint64_t*,
                             const cuuint32_t*, const cuuint32_t*, CUtensorMapInterleave, CUtensorMapSwizzle,
                             CUtensorMapL2promotion, CUtensorMapFloatOOBfill);

void encode(EncodeFn fn, CUtensorMap* m, int rank, const void* base, const cuuint64_t* dims, const cuuint64_t* strides,
            const cuuint32_t* box, CUtensorMapSwizzle sw) {
  cuuint32_t es[5] = {1, 1, 1, 1, 1};
  fn(m, CU_TENSOR_MAP_DATA_TYPE_BFLOAT16, (cuuint32_t)rank, const_cast<void*>(base), dims, strides, box, es,
     CU_TENSOR_MAP_INTERLEAVE_NONE, sw, CU_TENSOR_MAP_L2_PROMOTION_L2_128B, CU_TENSOR_MAP_FLOAT_OOB_FILL_NONE);
}

}

extern "C" void kernel_launch(void* const* d_in, const int* in_sizes, int n_in, void* d_out, int out_size) {
  (void)in_sizes; (void)n_in; (void)out_size;
  const __nv_bfloat16* x = (const __nv_bfloat16*)d_in[0];
  const char* wqkv = (const char*)d_in[1];
  const char* wo = (const char*)d_in[2];
  const char* wg = (const char*)d_in[4];
  const char* wu = (const char*)d_in[5];
  const char* wd = (const char*)d_in[6];

  static EncodeFn fn = nullptr;
  if (!fn) {
    void* p = nullptr;
    cudaDriverEntryPointQueryResult st;
    cudaGetDriverEntryPoint("cuTensorMapEncodeTiled", &p, cudaEnableDefault, &st);
    fn = (EncodeFn)p;
    cudaFuncSetAttribute(fused_kernel, cudaFuncAttributeMaxDynamicSharedMemorySize, SMEM_BYTES);
  }
  CUtensorMap m_qkv, m_wo, m_gu2, m_gu1, m_guh, m_wd112, m_wd80, m_wd32;
  {
    cuuint64_t dims[3] = {512, 512, 3}, str[2] = {3072, 1024};
    cuuint32_t box[3] = {64, 64, 3};
    encode(fn, &m_qkv, 3, wqkv, dims, str, box, CU_TENSOR_MAP_SWIZZLE_128B);
  }
  {
    cuuint64_t dims[2] = {512, 512}, str[1] = {1024};
    cuuint32_t box[2] = {64, 128};
    encode(fn, &m_wo, 2, wo, dims, str, box, CU_TENSOR_MAP_SWIZZLE_128B);
  }
  {
    const char* lo = wg < wu ? wg : wu;
    cuuint64_t diff = (cuuint64_t)(wg < wu ? wu - wg : wg - wu);
    cuuint64_t dims[4] = {1792, 512, 2, 2}, str[3] = {3584, diff, 128};
    cuuint32_t box2[4] = {64, 64, 2, 2}, box1[4] = {64, 64, 2, 1}, boxh[3] = {32, 64, 2};
    encode(fn, &m_gu2, 4, lo, dims, str, box2, CU_TENSOR_MAP_SWIZZLE_128B);
    encode(fn, &m_gu1, 4, lo, dims, str, box1, CU_TENSOR_MAP_SWIZZLE_128B);
    encode(fn, &m_guh, 3, lo, dims, str, boxh, CU_TENSOR_MAP_SWIZZLE_64B);
  }
  {
    cuuint64_t dims[2] = {512, 1792}, str[1] = {1024};
    cuuint32_t b112[2] = {64, 112}, b80[2] = {64, 80}, b32[2] = {64, 32};
    encode(fn, &m_wd112, 2, wd, dims, str, b112, CU_TENSOR_MAP_SWIZZLE_128B);
    encode(fn, &m_wd80, 2, wd, dims, str, b80, CU_TENSOR_MAP_SWIZZLE_128B);
    encode(fn, &m_wd32, 2, wd, dims, str, b32, CU_TENSOR_MAP_SWIZZLE_128B);
  }
  cudaLaunchConfig_t cfg = {};
  cfg.gridDim = dim3(128);
  cfg.blockDim = dim3(NTHREADS);
  cfg.dynamicSmemBytes = SMEM_BYTES;
  cfg.stream = cudaStreamPerThread;
  cudaLaunchAttribute at[1];
  at[0].id = cudaLaunchAttributeClusterDimension;
  at[0].val.clusterDim.x = 2; at[0].val.clusterDim.y = 1; at[0].val.clusterDim.z = 1;
  cfg.attrs = at; cfg.numAttrs = 1;
  cudaLaunchKernelEx(&cfg, fused_kernel, m_qkv, m_wo, m_gu2, m_gu1, m_guh, m_wd112, m_wd80, m_wd32, x, (__nv_bfloat16*)d_out, wo, wg, wu, wd
  );
}
```

```cpp
#include <cuda_runtime.h>
#include <cuda_bf16.h>
#include <cuda.h>
#include <stdint.h>

namespace {

constexpr int NTHREADS = 384;
constexpr int GRAN = 8192;
constexpr int NGRAN = 12;
constexpr int SM_AREG = NGRAN * GRAN;
constexpr int SM_MISC = SM_AREG + 131072;
constexpr int SM_TSTAT = SM_MISC + 256;
constexpr int SMEM_BYTES = SM_TSTAT + 1024;
constexpr int BAR_FULL = 0, BAR_EMPTY = 96;

__device__ uint4 g_xn[16 * 8 * 32 * 32];
__device__ uint4 g_xraw[16 * 8 * 32 * 32];
__device__ uint4 g_o[16 * 8 * 32 * 32];
__device__ uint4 g_stats[16 * 8 * 8 * 8];
__device__ uint4 g_halo[2 * 32 * 8 * 8 * 32];
__device__ uint4 g_part[16 * 8 * 2 * 4 * 16 * 32];
__device__ uint4 g_h[16 * 8 * 2 * 14 * 128];

#define TS(n)
#define TG(n)
#define OPAQUE(x) asm volatile("" : "+r"(x))
#define PHASE_VARS                                                                                   \
  int tid_ = threadIdx.x, bid_ = blockIdx.x;                                                         \
  OPAQUE(tid_); OPAQUE(bid_);                                                                        \
  const int lane = tid_ & 31, warp = tid_ >> 5, g = warp >> 2, w = warp & 3, t128 = tid_ & 127;      \
  const int qr = lane >> 2, qc = lane & 3, slab = warp;                                              \
  const int c = ((bid_ >> 4) << 1) | (bid_ & 1), j = (bid_ >> 1) & 7, ca = j >> 1, cbit = j & 1;     \
  const uint32_t areg = sbase + SM_AREG + g * 65536;                                                 \
  const uint32_t rel = mapa(sbase + SM_MISC + BAR_EMPTY + 8 * (lane & 7), (bid_ & 1) ^ ((lane >> 3) & 1)); (void)rel; \
  (void)g; (void)j; (void)w; (void)t128; (void)qr; (void)qc; (void)slab; (void)c; (void)ca; (void)cbit; (void)areg; (void)lane
#define STOP_AT(n)
#define PSTOP_AT(n)

__device__ __forceinline__ uint32_t smem_u32(const void* p) { return (uint32_t)__cvta_generic_to_shared(p); }
__device__ __forceinline__ void mbar_init(uint32_t bar, uint32_t cnt) {
  asm volatile("mbarrier.init.shared::cta.b64 [%0], %1;" ::"r"(bar), "r"(cnt) : "memory");
}
__device__ __forceinline__ void mbar_expect_tx(uint32_t bar, uint32_t bytes) {
  asm volatile("mbarrier.arrive.expect_tx.shared::cta.b64 _, [%0], %1;" ::"r"(bar), "r"(bytes) : "memory");
}
__device__ __forceinline__ bool mbar_try(uint32_t bar, uint32_t parity) {
  uint32_t ok;
  asm volatile("{\n.reg .pred p;\nmbarrier.try_wait.parity.shared::cta.b64 p, [%1], %2;\nselp.u32 %0, 1, 0, p;\n}"
               : "=r"(ok) : "r"(bar), "r"(parity) : "memory");
  return ok != 0;
}
constexpr uint32_t SPIN_LIMIT = 1u << 16;
constexpr uint32_t SMEM_ORIGIN = 1024;
__device__ __forceinline__ void mbar_wait(uint32_t bar, uint32_t parity) {
  for (uint32_t n = 0; !mbar_try(bar, parity) && n < SPIN_LIMIT; n++) {}
}
__device__ __forceinline__ uint32_t mapa(uint32_t addr, uint32_t rank) {
  uint32_t r;
  asm volatile("mapa.shared::cluster.u32 %0, %1, %2;" : "=r"(r) : "r"(addr), "r"(rank));
  return r;
}

__device__ __forceinline__ void tma_2d(uint32_t dst, const CUtensorMap* m, uint32_t bar, int c0, int c1) {
  asm volatile("cp.async.bulk.tensor.2d.shared::cluster.global.mbarrier::complete_tx::bytes [%0], [%1, {%3, %4}], [%2];"
               ::"r"(dst), "l"(m), "r"(bar), "r"(c0), "r"(c1) : "memory");
}
__device__ __forceinline__ void tma_3d(uint32_t dst, const CUtensorMap* m, uint32_t bar, int c0, int c1, int c2) {
  asm volatile("cp.async.bulk.tensor.3d.shared::cluster.global.mbarrier::complete_tx::bytes [%0], [%1, {%3, %4, %5}], [%2];"
               ::"r"(dst), "l"(m), "r"(bar), "r"(c0), "r"(c1), "r"(c2) : "memory");
}
__device__ __forceinline__ void tma_4d(uint32_t dst, const CUtensorMap* m, uint32_t bar, int c0, int c1, int c2, int c3) {
  asm volatile("cp.async.bulk.tensor.4d.shared::cluster.global.mbarrier::complete_tx::bytes [%0], [%1, {%3, %4, %5, %6}], [%2];"
               ::"r"(dst), "l"(m), "r"(bar), "r"(c0), "r"(c1), "r"(c2), "r"(c3) : "memory");
}
__device__ __forceinline__ void tma_2d_mc(uint32_t dst, const CUtensorMap* m, uint32_t bar, int c0, int c1, uint16_t mask) {
  asm volatile("cp.async.bulk.tensor.2d.shared::cluster.global.mbarrier::complete_tx::bytes.multicast::cluster [%0], [%1, {%3, %4}], [%2], %5;"
               ::"r"(dst), "l"(m), "r"(bar), "r"(c0), "r"(c1), "h"(mask) : "memory");
}
__device__ __forceinline__ void tma_3d_mc(uint32_t dst, const CUtensorMap* m, uint32_t bar, int c0, int c1, int c2, uint16_t mask) {
  asm volatile("cp.async.bulk.tensor.3d.shared::cluster.global.mbarrier::complete_tx::bytes.multicast::cluster [%0], [%1, {%3, %4, %5}], [%2], %6;"
               ::"r"(dst), "l"(m), "r"(bar), "r"(c0), "r"(c1), "r"(c2), "h"(mask) : "memory");
}
__device__ __forceinline__ void tma_4d_mc(uint32_t dst, const CUtensorMap* m, uint32_t bar, int c0, int c1, int c2, int c3, uint16_t mask) {
  asm volatile("cp.async.bulk.tensor.4d.shared::cluster.global.mbarrier::complete_tx::bytes.multicast::cluster [%0], [%1, {%3, %4, %5, %6}], [%2], %7;"
               ::"r"(dst), "l"(m), "r"(bar), "r"(c0), "r"(c1), "r"(c2), "r"(c3), "h"(mask) : "memory");
}
__device__ __forceinline__ void cp_async16(uint32_t dst, const void* src) {
  asm volatile("cp.async.cg.shared.global [%0], [%1], 16;" ::"r"(dst), "l"(src) : "memory");
}
__device__ __forceinline__ void cp_wait_all() { asm volatile("cp.async.wait_all;" ::: "memory"); }
__device__ __forceinline__ void l2_prefetch(const void* p, uint32_t bytes) {
  asm volatile("cp.async.bulk.prefetch.L2.global [%0], %1;" ::"l"(p), "r"(bytes) : "memory");
}

__device__ __forceinline__ uint4 ld_ll(const uint4* p) {
  uint4 v;
  asm volatile("ld.relaxed.gpu.global.v4.u32 {%0,%1,%2,%3}, [%4];" : "=r"(v.x), "=r"(v.y), "=r"(v.z), "=r"(v.w) : "l"(p) : "memory");
  return v;
}
__device__ __forceinline__ void st_ll(uint4* p, uint4 v) {
  asm volatile("st.relaxed.gpu.global.v4.u32 [%0], {%1,%2,%3,%4};" ::"l"(p), "r"(v.x), "r"(v.y), "r"(v.z), "r"(v.w) : "memory");
}
__device__ __forceinline__ uint4 lds128(uint32_t a) {
  uint4 v;
  asm volatile("ld.shared.v4.u32 {%0,%1,%2,%3}, [%4];" : "=r"(v.x), "=r"(v.y), "=r"(v.z), "=r"(v.w) : "r"(a) : "memory");
  return v;
}
__device__ __forceinline__ void sts128(uint32_t a, uint4 v) {
  asm volatile("st.shared.v4.u32 [%0], {%1,%2,%3,%4};" ::"r"(a), "r"(v.x), "r"(v.y), "r"(v.z), "r"(v.w) : "memory");
}
__device__ __forceinline__ uint32_t pack2(float lo, float hi) {
  uint32_t r;
  asm("cvt.rn.bf16x2.f32 %0, %1, %2;" : "=r"(r) : "f"(hi), "f"(lo));
  return r;
}
__device__ __forceinline__ float bf_lo(uint32_t w) { return __uint_as_float(w << 16); }
__device__ __forceinline__ float bf_hi(uint32_t w) { return __uint_as_float(w & 0xffff0000u); }
__device__ __forceinline__ uint32_t set_tag(uint32_t w, uint32_t tag) { return (w & ~1u) | tag; }
__device__ __forceinline__ uint32_t movm(uint32_t a) {
  uint32_t d;
  asm("movmatrix.sync.aligned.m8n8.trans.b16 %0, %1;" : "=r"(d) : "r"(a));
  return d;
}
__device__ __forceinline__ void mma16816(float (&d)[4], const uint4& a, uint32_t b0, uint32_t b1) {
  asm("mma.sync.aligned.m16n8k16.row.col.f32.bf16.bf16.f32 {%0,%1,%2,%3}, {%4,%5,%6,%7}, {%8,%9}, {%0,%1,%2,%3};"
               : "+f"(d[0]), "+f"(d[1]), "+f"(d[2]), "+f"(d[3])
               : "r"(a.x), "r"(a.y), "r"(a.z), "r"(a.w), "r"(b0), "r"(b1));
}
__device__ __forceinline__ void mma1688(float (&d)[4], uint32_t a0, uint32_t a1, uint32_t b0) {
  asm("mma.sync.aligned.m16n8k8.row.col.f32.bf16.bf16.f32 {%0,%1,%2,%3}, {%4,%5}, {%6}, {%0,%1,%2,%3};"
      : "+f"(d[0]), "+f"(d[1]), "+f"(d[2]), "+f"(d[3])
      : "r"(a0), "r"(a1), "r"(b0));
}
__device__ __forceinline__ void mma16816_z(float (&d)[4], const uint4& a, uint32_t b0, uint32_t b1) {
  asm("mma.sync.aligned.m16n8k16.row.col.f32.bf16.bf16.f32 {%0,%1,%2,%3}, {%4,%5,%6,%7}, {%8,%9}, {%10,%10,%10,%10};"
      : "=f"(d[0]), "=f"(d[1]), "=f"(d[2]), "=f"(d[3])
      : "r"(a.x), "r"(a.y), "r"(a.z), "r"(a.w), "r"(b0), "r"(b1), "f"(0.f));
}
__device__ __forceinline__ float ex2(float x) {
  float y;
  asm("ex2.approx.ftz.f32 %0, %1;" : "=f"(y) : "f"(x));
  return y;
}
__device__ __forceinline__ float rcp(float x) {
  float y;
  asm("rcp.approx.ftz.f32 %0, %1;" : "=f"(y) : "f"(x));
  return y;
}
__device__ __forceinline__ void bar_wg(int id) { asm volatile("bar.sync %0, 128;" ::"r"(id) : "memory"); }
__device__ __forceinline__ void wg_fence() { asm volatile("wgmma.fence.sync.aligned;" ::: "memory"); }
__device__ __forceinline__ void wg_commit() { asm volatile("wgmma.commit_group.sync.aligned;" ::: "memory"); }
template <int N> __device__ __forceinline__ void wg_wait() { asm volatile("wgmma.wait_group.sync.aligned %0;" ::"n"(N) : "memory"); }
__device__ __forceinline__ void keep(const uint4& a) { asm volatile("" ::"r"(a.x), "r"(a.y), "r"(a.z), "r"(a.w) : "memory"); }
template <int T> __device__ __forceinline__ void zero_acc(float (&d)[T]) {
#pragma unroll
  for (int i = 0; i < T; i++) d[i] = 0.f;
}
template <int T> __device__ __forceinline__ void fence_acc(float (&d)[T]) {
#pragma unroll
  for (int i = 0; i < T; i++) asm volatile("" : "+f"(d[i])::"memory");
}

template <int O, int T> __device__ __forceinline__ void wgmma_rs_n64(float (&d)[T], const uint4& a, uint64_t db) {
  asm volatile("{\n.reg .pred p;\nsetp.ne.b32 p, 1, 0;\n"
    "wgmma.mma_async.sync.aligned.m64n64k16.f32.bf16.bf16 "
    "{%0, %1, %2, %3, %4, %5, %6, %7, %8, %9, %10, %11, %12, %13, %14, %15, "
    "%16, %17, %18, %19, %20, %21, %22, %23, %24, %25, %26, %27, %28, %29, %30, %31}, "
    "{%32, %33, %34, %35}, %36, p, 1, 1, 1;\n}\n"
    : "+f"(d[O + 0]), "+f"(d[O + 1]), "+f"(d[O + 2]), "+f"(d[O + 3]), "+f"(d[O + 4]), "+f"(d[O + 5]), "+f"(d[O + 6]), "+f"(d[O + 7]),
      "+f"(d[O + 8]), "+f"(d[O + 9]), "+f"(d[O + 10]), "+f"(d[O + 11]), "+f"(d[O + 12]), "+f"(d[O + 13]), "+f"(d[O + 14]), "+f"(d[O + 15]),
      "+f"(d[O + 16]), "+f"(d[O + 17]), "+f"(d[O + 18]), "+f"(d[O + 19]), "+f"(d[O + 20]), "+f"(d[O + 21]), "+f"(d[O + 22]), "+f"(d[O + 23]),
      "+f"(d[O + 24]), "+f"(d[O + 25]), "+f"(d[O + 26]), "+f"(d[O + 27]), "+f"(d[O + 28]), "+f"(d[O + 29]), "+f"(d[O + 30]), "+f"(d[O + 31])
    : "r"(a.x), "r"(a.y), "r"(a.z), "r"(a.w), "l"(db));
}
template <int O, int T> __device__ __forceinline__ void wgmma_rs_n64_init(float (&d)[T], const uint4& a, uint64_t db) {
  asm volatile("{\n.reg .pred p;\nsetp.ne.b32 p, 0, 0;\n"
    "wgmma.mma_async.sync.aligned.m64n64k16.f32.bf16.bf16 "
    "{%0, %1, %2, %3, %4, %5, %6, %7, %8, %9, %10, %11, %12, %13, %14, %15, "
    "%16, %17, %18, %19, %20, %21, %22, %23, %24, %25, %26, %27, %28, %29, %30, %31}, "
    "{%32, %33, %34, %35}, %36, p, 1, 1, 1;\n}\n"
    : "=f"(d[O + 0]), "=f"(d[O + 1]), "=f"(d[O + 2]), "=f"(d[O + 3]), "=f"(d[O + 4]), "=f"(d[O + 5]), "=f"(d[O + 6]), "=f"(d[O + 7]),
      "=f"(d[O + 8]), "=f"(d[O + 9]), "=f"(d[O + 10]), "=f"(d[O + 11]), "=f"(d[O + 12]), "=f"(d[O + 13]), "=f"(d[O + 14]), "=f"(d[O + 15]),
      "=f"(d[O + 16]), "=f"(d[O + 17]), "=f"(d[O + 18]), "=f"(d[O + 19]), "=f"(d[O + 20]), "=f"(d[O + 21]), "=f"(d[O + 22]), "=f"(d[O + 23]),
      "=f"(d[O + 24]), "=f"(d[O + 25]), "=f"(d[O + 26]), "=f"(d[O + 27]), "=f"(d[O + 28]), "=f"(d[O + 29]), "=f"(d[O + 30]), "=f"(d[O + 31])
    : "r"(a.x), "r"(a.y), "r"(a.z), "r"(a.w), "l"(db));
}
template <bool INIT, int O, int T> __device__ __forceinline__ void wgmma_n64(float (&d)[T], const uint4& a, uint64_t db) {
  if constexpr (INIT) wgmma_rs_n64_init<O>(d, a, db); else wgmma_rs_n64<O>(d, a, db);
}
template <int O, int T> __device__ __forceinline__ void wgmma_rs_n128(float (&d)[T], const uint4& a, uint64_t db) {
  asm volatile("{\n.reg .pred p;\nsetp.ne.b32 p, 1, 0;\n"
    "wgmma.mma_async.sync.aligned.m64n128k16.f32.bf16.bf16 "
    "{%0, %1, %2, %3, %4, %5, %6, %7, %8, %9, %10, %11, %12, %13, %14, %15, "
    "%16, %17, %18, %19, %20, %21, %22, %23, %24, %25, %26, %27, %28, %29, %30, %31, "
    "%32, %33, %34, %35, %36, %37, %38, %39, %40, %41, %42, %43, %44, %45, %46, %47, "
    "%48, %49, %50, %51, %52, %53, %54, %55, %56, %57, %58, %59, %60, %61, %62, %63}, "
    "{%64, %65, %66, %67}, %68, p, 1, 1, 1;\n}\n"
    : "+f"(d[O + 0]), "+f"(d[O + 1]), "+f"(d[O + 2]), "+f"(d[O + 3]), "+f"(d[O + 4]), "+f"(d[O + 5]), "+f"(d[O + 6]), "+f"(d[O + 7]),
      "+f"(d[O + 8]), "+f"(d[O + 9]), "+f"(d[O + 10]), "+f"(d[O + 11]), "+f"(d[O + 12]), "+f"(d[O + 13]), "+f"(d[O + 14]), "+f"(d[O + 15]),
      "+f"(d[O + 16]), "+f"(d[O + 17]), "+f"(d[O + 18]), "+f"(d[O + 19]), "+f"(d[O + 20]), "+f"(d[O + 21]), "+f"(d[O + 22]), "+f"(d[O + 23]),
      "+f"(d[O + 24]), "+f"(d[O + 25]), "+f"(d[O + 26]), "+f"(d[O + 27]), "+f"(d[O + 28]), "+f"(d[O + 29]), "+f"(d[O + 30]), "+f"(d[O + 31]),
      "+f"(d[O + 32]), "+f"(d[O + 33]), "+f"(d[O + 34]), "+f"(d[O + 35]), "+f"(d[O + 36]), "+f"(d[O + 37]), "+f"(d[O + 38]), "+f"(d[O + 39]),
      "+f"(d[O + 40]), "+f"(d[O + 41]), "+f"(d[O + 42]), "+f"(d[O + 43]), "+f"(d[O + 44]), "+f"(d[O + 45]), "+f"(d[O + 46]), "+f"(d[O + 47]),
      "+f"(d[O + 48]), "+f"(d[O + 49]), "+f"(d[O + 50]), "+f"(d[O + 51]), "+f"(d[O + 52]), "+f"(d[O + 53]), "+f"(d[O + 54]), "+f"(d[O + 55]),
      "+f"(d[O + 56]), "+f"(d[O + 57]), "+f"(d[O + 58]), "+f"(d[O + 59]), "+f"(d[O + 60]), "+f"(d[O + 61]), "+f"(d[O + 62]), "+f"(d[O + 63])
    : "r"(a.x), "r"(a.y), "r"(a.z), "r"(a.w), "l"(db));
}
template <int O, int T> __device__ __forceinline__ void wgmma_rs_n128_init(float (&d)[T], const uint4& a, uint64_t db) {
  asm volatile("{\n.reg .pred p;\nsetp.ne.b32 p, 0, 0;\n"
    "wgmma.mma_async.sync.aligned.m64n128k16.f32.bf16.bf16 "
    "{%0, %1, %2, %3, %4, %5, %6, %7, %8, %9, %10, %11, %12, %13, %14, %15, "
    "%16, %17, %18, %19, %20, %21, %22, %23, %24, %25, %26, %27, %28, %29, %30, %31, "
    "%32, %33, %34, %35, %36, %37, %38, %39, %40, %41, %42, %43, %44, %45, %46, %47, "
    "%48, %49, %50, %51, %52, %53, %54, %55, %56, %57, %58, %59, %60, %61, %62, %63}, "
    "{%64, %65, %66, %67}, %68, p, 1, 1, 1;\n}\n"
    : "=f"(d[O + 0]), "=f"(d[O + 1]), "=f"(d[O + 2]), "=f"(d[O + 3]), "=f"(d[O + 4]), "=f"(d[O + 5]), "=f"(d[O + 6]), "=f"(d[O + 7]),
      "=f"(d[O + 8]), "=f"(d[O + 9]), "=f"(d[O + 10]), "=f"(d[O + 11]), "=f"(d[O + 12]), "=f"(d[O + 13]), "=f"(d[O + 14]), "=f"(d[O + 15]),
      "=f"(d[O + 16]), "=f"(d[O + 17]), "=f"(d[O + 18]), "=f"(d[O + 19]), "=f"(d[O + 20]), "=f"(d[O + 21]), "=f"(d[O + 22]), "=f"(d[O + 23]),
      "=f"(d[O + 24]), "=f"(d[O + 25]), "=f"(d[O + 26]), "=f"(d[O + 27]), "=f"(d[O + 28]), "=f"(d[O + 29]), "=f"(d[O + 30]), "=f"(d[O + 31]),
      "=f"(d[O + 32]), "=f"(d[O + 33]), "=f"(d[O + 34]), "=f"(d[O + 35]), "=f"(d[O + 36]), "=f"(d[O + 37]), "=f"(d[O + 38]), "=f"(d[O + 39]),
      "=f"(d[O + 40]), "=f"(d[O + 41]), "=f"(d[O + 42]), "=f"(d[O + 43]), "=f"(d[O + 44]), "=f"(d[O + 45]), "=f"(d[O + 46]), "=f"(d[O + 47]),
      "=f"(d[O + 48]), "=f"(d[O + 49]), "=f"(d[O + 50]), "=f"(d[O + 51]), "=f"(d[O + 52]), "=f"(d[O + 53]), "=f"(d[O + 54]), "=f"(d[O + 55]),
      "=f"(d[O + 56]), "=f"(d[O + 57]), "=f"(d[O + 58]), "=f"(d[O + 59]), "=f"(d[O + 60]), "=f"(d[O + 61]), "=f"(d[O + 62]), "=f"(d[O + 63])
    : "r"(a.x), "r"(a.y), "r"(a.z), "r"(a.w), "l"(db));
}
template <bool INIT, int O, int T> __device__ __forceinline__ void wgmma_n128(float (&d)[T], const uint4& a, uint64_t db) {
  if constexpr (INIT) wgmma_rs_n128_init<O>(d, a, db); else wgmma_rs_n128<O>(d, a, db);
}
template <int O, int T> __device__ __forceinline__ void wgmma_rs_n192(float (&d)[T], const uint4& a, uint64_t db) {
  asm volatile("{\n.reg .pred p;\nsetp.ne.b32 p, 1, 0;\n"
    "wgmma.mma_async.sync.aligned.m64n192k16.f32.bf16.bf16 "
    "{%0, %1, %2, %3, %4, %5, %6, %7, %8, %9, %10, %11, %12, %13, %14, %15, "
    "%16, %17, %18, %19, %20, %21, %22, %23, %24, %25, %26, %27, %28, %29, %30, %31, "
    "%32, %33, %34, %35, %36, %37, %38, %39, %40, %41, %42, %43, %44, %45, %46, %47, "
    "%48, %49, %50, %51, %52, %53, %54, %55, %56, %57, %58, %59, %60, %61, %62, %63, "
    "%64, %65, %66, %67, %68, %69, %70, %71, %72, %73, %74, %75, %76, %77, %78, %79, "
    "%80, %81, %82, %83, %84, %85, %86, %87, %88, %89, %90, %91, %92, %93, %94, %95}, "
    "{%96, %97, %98, %99}, %100, p, 1, 1, 1;\n}\n"
    : "+f"(d[O + 0]), "+f"(d[O + 1]), "+f"(d[O + 2]), "+f"(d[O + 3]), "+f"(d[O + 4]), "+f"(d[O + 5]), "+f"(d[O + 6]), "+f"(d[O + 7]),
      "+f"(d[O + 8]), "+f"(d[O + 9]), "+f"(d[O + 10]), "+f"(d[O + 11]), "+f"(d[O + 12]), "+f"(d[O + 13]), "+f"(d[O + 14]), "+f"(d[O + 15]),
      "+f"(d[O + 16]), "+f"(d[O + 17]), "+f"(d[O + 18]), "+f"(d[O + 19]), "+f"(d[O + 20]), "+f"(d[O + 21]), "+f"(d[O + 22]), "+f"(d[O + 23]),
      "+f"(d[O + 24]), "+f"(d[O + 25]), "+f"(d[O + 26]), "+f"(d[O + 27]), "+f"(d[O + 28]), "+f"(d[O + 29]), "+f"(d[O + 30]), "+f"(d[O + 31]),
      "+f"(d[O + 32]), "+f"(d[O + 33]), "+f"(d[O + 34]), "+f"(d[O + 35]), "+f"(d[O + 36]), "+f"(d[O + 37]), "+f"(d[O + 38]), "+f"(d[O + 39]),
      "+f"(d[O + 40]), "+f"(d[O + 41]), "+f"(d[O + 42]), "+f"(d[O + 43]), "+f"(d[O + 44]), "+f"(d[O + 45]), "+f"(d[O + 46]), "+f"(d[O + 47]),
      "+f"(d[O + 48]), "+f"(d[O + 49]), "+f"(d[O + 50]), "+f"(d[O + 51]), "+f"(d[O + 52]), "+f"(d[O + 53]), "+f"(d[O + 54]), "+f"(d[O + 55]),
      "+f"(d[O + 56]), "+f"(d[O + 57]), "+f"(d[O + 58]), "+f"(d[O + 59]), "+f"(d[O + 60]), "+f"(d[O + 61]), "+f"(d[O + 62]), "+f"(d[O + 63]),
      "+f"(d[O + 64]), "+f"(d[O + 65]), "+f"(d[O + 66]), "+f"(d[O + 67]), "+f"(d[O + 68]), "+f"(d[O + 69]), "+f"(d[O + 70]), "+f"(d[O + 71]),
      "+f"(d[O + 72]), "+f"(d[O + 73]), "+f"(d[O + 74]), "+f"(d[O + 75]), "+f"(d[O + 76]), "+f"(d[O + 77]), "+f"(d[O + 78]), "+f"(d[O + 79]),
      "+f"(d[O + 80]), "+f"(d[O + 81]), "+f"(d[O + 82]), "+f"(d[O + 83]), "+f"(d[O + 84]), "+f"(d[O + 85]), "+f"(d[O + 86]), "+f"(d[O + 87]),
      "+f"(d[O + 88]), "+f"(d[O + 89]), "+f"(d[O + 90]), "+f"(d[O + 91]), "+f"(d[O + 92]), "+f"(d[O + 93]), "+f"(d[O + 94]), "+f"(d[O + 95])
    : "r"(a.x), "r"(a.y), "r"(a.z), "r"(a.w), "l"(db));
}
template <int O, int T> __device__ __forceinline__ void wgmma_rs_n192_init(float (&d)[T], const uint4& a, uint64_t db) {
  asm volatile("{\n.reg .pred p;\nsetp.ne.b32 p, 0, 0;\n"
    "wgmma.mma_async.sync.aligned.m64n192k16.f32.bf16.bf16 "
    "{%0, %1, %2, %3, %4, %5, %6, %7, %8, %9, %10, %11, %12, %13, %14, %15, "
    "%16, %17, %18, %19, %20, %21, %22, %23, %24, %25, %26, %27, %28, %29, %30, %31, "
    "%32, %33, %34, %35, %36, %37, %38, %39, %40, %41, %42, %43, %44, %45, %46, %47, "
    "%48, %49, %50, %51, %52, %53, %54, %55, %56, %57, %58, %59, %60, %61, %62, %63, "
    "%64, %65, %66, %67, %68, %69, %70, %71, %72, %73, %74, %75, %76, %77, %78, %79, "
    "%80, %81, %82, %83, %84, %85, %86, %87, %88, %89, %90, %91, %92, %93, %94, %95}, "
    "{%96, %97, %98, %99}, %100, p, 1, 1, 1;\n}\n"
    : "=f"(d[O + 0]), "=f"(d[O + 1]), "=f"(d[O + 2]), "=f"(d[O + 3]), "=f"(d[O + 4]), "=f"(d[O + 5]), "=f"(d[O + 6]), "=f"(d[O + 7]),
      "=f"(d[O + 8]), "=f"(d[O + 9]), "=f"(d[O + 10]), "=f"(d[O + 11]), "=f"(d[O + 12]), "=f"(d[O + 13]), "=f"(d[O + 14]), "=f"(d[O + 15]),
      "=f"(d[O + 16]), "=f"(d[O + 17]), "=f"(d[O + 18]), "=f"(d[O + 19]), "=f"(d[O + 20]), "=f"(d[O + 21]), "=f"(d[O + 22]), "=f"(d[O + 23]),
      "=f"(d[O + 24]), "=f"(d[O + 25]), "=f"(d[O + 26]), "=f"(d[O + 27]), "=f"(d[O + 28]), "=f"(d[O + 29]), "=f"(d[O + 30]), "=f"(d[O + 31]),
      "=f"(d[O + 32]), "=f"(d[O + 33]), "=f"(d[O + 34]), "=f"(d[O + 35]), "=f"(d[O + 36]), "=f"(d[O + 37]), "=f"(d[O + 38]), "=f"(d[O + 39]),
      "=f"(d[O + 40]), "=f"(d[O + 41]), "=f"(d[O + 42]), "=f"(d[O + 43]), "=f"(d[O + 44]), "=f"(d[O + 45]), "=f"(d[O + 46]), "=f"(d[O + 47]),
      "=f"(d[O + 48]), "=f"(d[O + 49]), "=f"(d[O + 50]), "=f"(d[O + 51]), "=f"(d[O + 52]), "=f"(d[O + 53]), "=f"(d[O + 54]), "=f"(d[O + 55]),
      "=f"(d[O + 56]), "=f"(d[O + 57]), "=f"(d[O + 58]), "=f"(d[O + 59]), "=f"(d[O + 60]), "=f"(d[O + 61]), "=f"(d[O + 62]), "=f"(d[O + 63]),
      "=f"(d[O + 64]), "=f"(d[O + 65]), "=f"(d[O + 66]), "=f"(d[O + 67]), "=f"(d[O + 68]), "=f"(d[O + 69]), "=f"(d[O + 70]), "=f"(d[O + 71]),
      "=f"(d[O + 72]), "=f"(d[O + 73]), "=f"(d[O + 74]), "=f"(d[O + 75]), "=f"(d[O + 76]), "=f"(d[O + 77]), "=f"(d[O + 78]), "=f"(d[O + 79]),
      "=f"(d[O + 80]), "=f"(d[O + 81]), "=f"(d[O + 82]), "=f"(d[O + 83]), "=f"(d[O + 84]), "=f"(d[O + 85]), "=f"(d[O + 86]), "=f"(d[O + 87]),
      "=f"(d[O + 88]), "=f"(d[O + 89]), "=f"(d[O + 90]), "=f"(d[O + 91]), "=f"(d[O + 92]), "=f"(d[O + 93]), "=f"(d[O + 94]), "=f"(d[O + 95])
    : "r"(a.x), "r"(a.y), "r"(a.z), "r"(a.w), "l"(db));
}
template <bool INIT, int O, int T> __device__ __forceinline__ void wgmma_n192(float (&d)[T], const uint4& a, uint64_t db) {
  if constexpr (INIT) wgmma_rs_n192_init<O>(d, a, db); else wgmma_rs_n192<O>(d, a, db);
}
template <int O, int T> __device__ __forceinline__ void wgmma_rs_n256(float (&d)[T], const uint4& a, uint64_t db) {
  asm volatile("{\n.reg .pred p;\nsetp.ne.b32 p, 1, 0;\n"
    "wgmma.mma_async.sync.aligned.m64n256k16.f32.bf16.bf16 "
    "{%0, %1, %2, %3, %4, %5, %6, %7, %8, %9, %10, %11, %12, %13, %14, %15, "
    "%16, %17, %18, %19, %20, %21, %22, %23, %24, %25, %26, %27, %28, %29, %30, %31, "
    "%32, %33, %34, %35, %36, %37, %38, %39, %40, %41, %42, %43, %44, %45, %46, %47, "
    "%48, %49, %50, %51, %52, %53, %54, %55, %56, %57, %58, %59, %60, %61, %62, %63, "
    "%64, %65, %66, %67, %68, %69, %70, %71, %72, %73, %74, %75, %76, %77, %78, %79, "
    "%80, %81, %82, %83, %84, %85, %86, %87, %88, %89, %90, %91, %92, %93, %94, %95, "
    "%96, %97, %98, %99, %100, %101, %102, %103, %104, %105, %106, %107, %108, %109, %110, %111, "
    "%112, %113, %114, %115, %116, %117, %118, %119, %120, %121, %122, %123, %124, %125, %126, %127}, "
    "{%128, %129, %130, %131}, %132, p, 1, 1, 1;\n}\n"
    : "+f"(d[O + 0]), "+f"(d[O + 1]), "+f"(d[O + 2]), "+f"(d[O + 3]), "+f"(d[O + 4]), "+f"(d[O + 5]), "+f"(d[O + 6]), "+f"(d[O + 7]),
      "+f"(d[O + 8]), "+f"(d[O + 9]), "+f"(d[O + 10]), "+f"(d[O + 11]), "+f"(d[O + 12]), "+f"(d[O + 13]), "+f"(d[O + 14]), "+f"(d[O + 15]),
      "+f"(d[O + 16]), "+f"(d[O + 17]), "+f"(d[O + 18]), "+f"(d[O + 19]), "+f"(d[O + 20]), "+f"(d[O + 21]), "+f"(d[O + 22]), "+f"(d[O + 23]),
      "+f"(d[O + 24]), "+f"(d[O + 25]), "+f"(d[O + 26]), "+f"(d[O + 27]), "+f"(d[O + 28]), "+f"(d[O + 29]), "+f"(d[O + 30]), "+f"(d[O + 31]),
      "+f"(d[O + 32]), "+f"(d[O + 33]), "+f"(d[O + 34]), "+f"(d[O + 35]), "+f"(d[O + 36]), "+f"(d[O + 37]), "+f"(d[O + 38]), "+f"(d[O + 39]),
      "+f"(d[O + 40]), "+f"(d[O + 41]), "+f"(d[O + 42]), "+f"(d[O + 43]), "+f"(d[O + 44]), "+f"(d[O + 45]), "+f"(d[O + 46]), "+f"(d[O + 47]),
      "+f"(d[O + 48]), "+f"(d[O + 49]), "+f"(d[O + 50]), "+f"(d[O + 51]), "+f"(d[O + 52]), "+f"(d[O + 53]), "+f"(d[O + 54]), "+f"(d[O + 55]),
      "+f"(d[O + 56]), "+f"(d[O + 57]), "+f"(d[O + 58]), "+f"(d[O + 59]), "+f"(d[O + 60]), "+f"(d[O + 61]), "+f"(d[O + 62]), "+f"(d[O + 63]),
      "+f"(d[O + 64]), "+f"(d[O + 65]), "+f"(d[O + 66]), "+f"(d[O + 67]), "+f"(d[O + 68]), "+f"(d[O + 69]), "+f"(d[O + 70]), "+f"(d[O + 71]),
      "+f"(d[O + 72]), "+f"(d[O + 73]), "+f"(d[O + 74]), "+f"(d[O + 75]), "+f"(d[O + 76]), "+f"(d[O + 77]), "+f"(d[O + 78]), "+f"(d[O + 79]),
      "+f"(d[O + 80]), "+f"(d[O + 81]), "+f"(d[O + 82]), "+f"(d[O + 83]), "+f"(d[O + 84]), "+f"(d[O + 85]), "+f"(d[O + 86]), "+f"(d[O + 87]),
      "+f"(d[O + 88]), "+f"(d[O + 89]), "+f"(d[O + 90]), "+f"(d[O + 91]), "+f"(d[O + 92]), "+f"(d[O + 93]), "+f"(d[O + 94]), "+f"(d[O + 95]),
      "+f"(d[O + 96]), "+f"(d[O + 97]), "+f"(d[O + 98]), "+f"(d[O + 99]), "+f"(d[O + 100]), "+f"(d[O + 101]), "+f"(d[O + 102]), "+f"(d[O + 103]),
      "+f"(d[O + 104]), "+f"(d[O + 105]), "+f"(d[O + 106]), "+f"(d[O + 107]), "+f"(d[O + 108]), "+f"(d[O + 109]), "+f"(d[O + 110]), "+f"(d[O + 111]),
      "+f"(d[O + 112]), "+f"(d[O + 113]), "+f"(d[O + 114]), "+f"(d[O + 115]), "+f"(d[O + 116]), "+f"(d[O + 117]), "+f"(d[O + 118]), "+f"(d[O + 119]),
      "+f"(d[O + 120]), "+f"(d[O + 121]), "+f"(d[O + 122]), "+f"(d[O + 123]), "+f"(d[O + 124]), "+f"(d[O + 125]), "+f"(d[O + 126]), "+f"(d[O + 127])
    : "r"(a.x), "r"(a.y), "r"(a.z), "r"(a.w), "l"(db));
}
template <int O, int T> __device__ __forceinline__ void wgmma_rs_n256_init(float (&d)[T], const uint4& a, uint64_t db) {
  asm volatile("{\n.reg .pred p;\nsetp.ne.b32 p, 0, 0;\n"
    "wgmma.mma_async.sync.aligned.m64n256k16.f32.bf16.bf16 "
    "{%0, %1, %2, %3, %4, %5, %6, %7, %8, %9, %10, %11, %12, %13, %14, %15, "
    "%16, %17, %18, %19, %20, %21, %22, %23, %24, %25, %26, %27, %28, %29, %30, %31, "
    "%32, %33, %34, %35, %36, %37, %38, %39, %40, %41, %42, %43, %44, %45, %46, %47, "
    "%48, %49, %50, %51, %52, %53, %54, %55, %56, %57, %58, %59, %60, %61, %62, %63, "
    "%64, %65, %66, %67, %68, %69, %70, %71, %72, %73, %74, %75, %76, %77, %78, %79, "
    "%80, %81, %82, %83, %84, %85, %86, %87, %88, %89, %90, %91, %92, %93, %94, %95, "
    "%96, %97, %98, %99, %100, %101, %102, %103, %104, %105, %106, %107, %108, %109, %110, %111, "
    "%112, %113, %114, %115, %116, %117, %118, %119, %120, %121, %122, %123, %124, %125, %126, %127}, "
    "{%128, %129, %130, %131}, %132, p, 1, 1, 1;\n}\n"
    : "=f"(d[O + 0]), "=f"(d[O + 1]), "=f"(d[O + 2]), "=f"(d[O + 3]), "=f"(d[O + 4]), "=f"(d[O + 5]), "=f"(d[O + 6]), "=f"(d[O + 7]),
      "=f"(d[O + 8]), "=f"(d[O + 9]), "=f"(d[O + 10]), "=f"(d[O + 11]), "=f"(d[O + 12]), "=f"(d[O + 13]), "=f"(d[O + 14]), "=f"(d[O + 15]),
      "=f"(d[O + 16]), "=f"(d[O + 17]), "=f"(d[O + 18]), "=f"(d[O + 19]), "=f"(d[O + 20]), "=f"(d[O + 21]), "=f"(d[O + 22]), "=f"(d[O + 23]),
      "=f"(d[O + 24]), "=f"(d[O + 25]), "=f"(d[O + 26]), "=f"(d[O + 27]), "=f"(d[O + 28]), "=f"(d[O + 29]), "=f"(d[O + 30]), "=f"(d[O + 31]),
      "=f"(d[O + 32]), "=f"(d[O + 33]), "=f"(d[O + 34]), "=f"(d[O + 35]), "=f"(d[O + 36]), "=f"(d[O + 37]), "=f"(d[O + 38]), "=f"(d[O + 39]),
      "=f"(d[O + 40]), "=f"(d[O + 41]), "=f"(d[O + 42]), "=f"(d[O + 43]), "=f"(d[O + 44]), "=f"(d[O + 45]), "=f"(d[O + 46]), "=f"(d[O + 47]),
      "=f"(d[O + 48]), "=f"(d[O + 49]), "=f"(d[O + 50]), "=f"(d[O + 51]), "=f"(d[O + 52]), "=f"(d[O + 53]), "=f"(d[O + 54]), "=f"(d[O + 55]),
      "=f"(d[O + 56]), "=f"(d[O + 57]), "=f"(d[O + 58]), "=f"(d[O + 59]), "=f"(d[O + 60]), "=f"(d[O + 61]), "=f"(d[O + 62]), "=f"(d[O + 63]),
      "=f"(d[O + 64]), "=f"(d[O + 65]), "=f"(d[O + 66]), "=f"(d[O + 67]), "=f"(d[O + 68]), "=f"(d[O + 69]), "=f"(d[O + 70]), "=f"(d[O + 71]),
      "=f"(d[O + 72]), "=f"(d[O + 73]), "=f"(d[O + 74]), "=f"(d[O + 75]), "=f"(d[O + 76]), "=f"(d[O + 77]), "=f"(d[O + 78]), "=f"(d[O + 79]),
      "=f"(d[O + 80]), "=f"(d[O + 81]), "=f"(d[O + 82]), "=f"(d[O + 83]), "=f"(d[O + 84]), "=f"(d[O + 85]), "=f"(d[O + 86]), "=f"(d[O + 87]),
      "=f"(d[O + 88]), "=f"(d[O + 89]), "=f"(d[O + 90]), "=f"(d[O + 91]), "=f"(d[O + 92]), "=f"(d[O + 93]), "=f"(d[O + 94]), "=f"(d[O + 95]),
      "=f"(d[O + 96]), "=f"(d[O + 97]), "=f"(d[O + 98]), "=f"(d[O + 99]), "=f"(d[O + 100]), "=f"(d[O + 101]), "=f"(d[O + 102]), "=f"(d[O + 103]),
      "=f"(d[O + 104]), "=f"(d[O + 105]), "=f"(d[O + 106]), "=f"(d[O + 107]), "=f"(d[O + 108]), "=f"(d[O + 109]), "=f"(d[O + 110]), "=f"(d[O + 111]),
      "=f"(d[O + 112]), "=f"(d[O + 113]), "=f"(d[O + 114]), "=f"(d[O + 115]), "=f"(d[O + 116]), "=f"(d[O + 117]), "=f"(d[O + 118]), "=f"(d[O + 119]),
      "=f"(d[O + 120]), "=f"(d[O + 121]), "=f"(d[O + 122]), "=f"(d[O + 123]), "=f"(d[O + 124]), "=f"(d[O + 125]), "=f"(d[O + 126]), "=f"(d[O + 127])
    : "r"(a.x), "r"(a.y), "r"(a.z), "r"(a.w), "l"(db));
}
template <bool INIT, int O, int T> __device__ __forceinline__ void wgmma_n256(float (&d)[T], const uint4& a, uint64_t db) {
  if constexpr (INIT) wgmma_rs_n256_init<O>(d, a, db); else wgmma_rs_n256<O>(d, a, db);
}

template <int N> __device__ __forceinline__ void load_pk(uint4* a, const uint4* p) {
#pragma unroll
  for (int i = 0; i < N; i++) a[i] = ld_ll(p + i * 32);
}
__device__ __forceinline__ uint32_t xor_or(uint32_t a, uint32_t b, uint32_t t) {
  uint32_t r;
  asm("lop3.b32 %0, %1, %2, %3, 0x7E;" : "=r"(r) : "r"(a), "r"(b), "r"(t));
  return r;
}
template <int N> __device__ __forceinline__ bool ok_pk(const uint4* a, uint32_t tag) {
  static_assert(N % 2 == 0, "");
  uint32_t x = xor_or(a[0].x, a[1].x, tag);
#pragma unroll
  for (int i = 2; i < N; i += 2) x |= xor_or(a[i].x, a[i + 1].x, tag);
  return __all_sync(0xffffffffu, (x & 1u) == 0u);
}
template <int N> __device__ __forceinline__ void ensure_pk(uint4* a, const uint4* p, uint32_t tag) {
  if (ok_pk<N>(a, tag)) return;
  uint32_t n = 0;
  do { load_pk<N>(a, p); } while (!ok_pk<N>(a, tag) && ++n < SPIN_LIMIT);
}

constexpr int NSTAGE = 44;
constexpr int ST_WO = 8, ST_G1 = 12, ST_G2 = 20, ST_DN = 28;
__host__ __device__ constexpr int st_len(int s) { return s < ST_WO ? 3 : s < ST_G1 ? 2 : s < ST_G2 ? 4 : s < ST_DN ? 3 : 2; }
__host__ __device__ constexpr int st_g0(int s) {
  int pos = 0, g0 = 0;
  for (int i = 0; i <= s; i++) {
    if (pos + st_len(i) > NGRAN) pos = 0;
    g0 = pos;
    pos += st_len(i);
  }
  return g0;
}
__host__ __device__ constexpr int cnt_first(int g, int s) {
  int n = 0;
  for (int i = 0; i < s; i++) n += (st_g0(i) == g);
  return n;
}
__host__ __device__ constexpr int cnt_cover(int g, int s) {
  int n = 0;
  for (int i = 0; i < s; i++) n += (g >= st_g0(i) && g < st_g0(i) + st_len(i));
  return n;
}
__host__ __device__ constexpr uint32_t flip_mask(int s0, int s1) {
  uint32_t m = 0;
  for (int i = s0; i < s1; i++) m ^= ((1u << st_len(i)) - 1u) << st_g0(i);
  return m;
}
__host__ __device__ constexpr int dn_q(int i) { return i < 3 ? 0 : i < 6 ? 1 : i == 6 ? 0 : i == 7 ? 1 : i < 12 ? 2 : 3; }
__host__ __device__ constexpr int dn_par(int i) { return i < 8 ? (i == 2 || i == 4 || i >= 6) : (i & 1); }
__host__ __device__ constexpr int dn_kh(int i) { return i < 8 ? (i == 1 || i >= 5) : ((i & 3) >= 2); }
template <int I> struct IC { static constexpr int value = I; };
template <int B, int E, typename F> __device__ __forceinline__ void static_for(F&& f) {
  if constexpr (B < E) { f(IC<B>{}); static_for<B + 1, E>(f); }
}
template <int S> __device__ __forceinline__ void cons_acquire(uint32_t sbase, uint32_t L) {
  constexpr int g0 = st_g0(S);
  constexpr uint32_t p0 = cnt_first(g0, S) & 1, odd = cnt_first(g0, NSTAGE) & 1;
  mbar_wait(sbase + SM_MISC + BAR_FULL + 8 * g0, p0 ^ (L & odd));
}
template <int S> __device__ __forceinline__ void cons_release(uint32_t rel, int lane) {
  if ((lane & 23) < st_len(S)) asm volatile("mbarrier.arrive.shared::cluster.b64 _, [%0];" ::"r"(rel + 8 * st_g0(S)) : "memory");
}
__device__ __forceinline__ bool elect_one() {
  uint32_t p;
  asm volatile("{\n.reg .pred P;\nelect.sync _|P, 0xffffffff;\nselp.u32 %0, 1, 0, P;\n}" : "=r"(p));
  return p != 0;
}
struct ProdRing { uint32_t pos, par; };
template <int N> __device__ __forceinline__ uint32_t prod_acquire(uint32_t sbase, ProdRing& r) {
  if (r.pos + N > NGRAN) r.pos = 0;
  const uint32_t g0 = r.pos;
#pragma unroll
  for (uint32_t i = 0; i < N; i++) mbar_wait(sbase + SM_MISC + BAR_EMPTY + 8 * (g0 + i), ((r.par >> (g0 + i)) & 1u) ^ 1u);
  r.par ^= ((1u << N) - 1u) << g0;
  r.pos = g0 + N;
  return g0;
}
template <int S> __device__ __forceinline__ void prod_acquire_static(uint32_t sbase, uint32_t L) {
  constexpr int g0 = st_g0(S);
  static_for<0, st_len(S)>([&](auto I) {
    constexpr int g = g0 + I.value;
    constexpr uint32_t p0 = cnt_cover(g, S) & 1, odd = cnt_cover(g, NSTAGE) & 1;
    mbar_wait(sbase + SM_MISC + BAR_EMPTY + 8 * g, p0 ^ (L & odd) ^ 1u);
  });
}
template <int S, int KSTEP_BYTES, int LBO, int SBO, int SWZ> __device__ __forceinline__ constexpr uint64_t st_desc(int k) {
  return (uint64_t)((SMEM_ORIGIN + st_g0(S) * GRAN + k * KSTEP_BYTES) >> 4) | ((uint64_t)(LBO >> 4) << 16) |
         ((uint64_t)(SBO >> 4) << 32) | ((uint64_t)SWZ << 62);
}

__device__ __forceinline__ void combine_stats(const uint4& p0, const uint4& p1, float& mean_lo, float& rstd_lo, float& mean_hi, float& rstd_hi) {
  float m0 = __uint_as_float(p0.x), q0 = __uint_as_float(p0.y), m0h = __uint_as_float(p0.z), q0h = __uint_as_float(p0.w);
  float m1 = __uint_as_float(p1.x), q1 = __uint_as_float(p1.y), m1h = __uint_as_float(p1.z), q1h = __uint_as_float(p1.w);
  float s = m0 + m1, sh = m0h + m1h;
  s += __shfl_xor_sync(0xffffffffu, s, 1); sh += __shfl_xor_sync(0xffffffffu, sh, 1);
  s += __shfl_xor_sync(0xffffffffu, s, 2); sh += __shfl_xor_sync(0xffffffffu, sh, 2);
  mean_lo = s * 0.125f; mean_hi = sh * 0.125f;
  float d0 = m0 - mean_lo, d1 = m1 - mean_lo, d0h = m0h - mean_hi, d1h = m1h - mean_hi;
  float t = q0 + q1 + 64.f * (d0 * d0 + d1 * d1), th = q0h + q1h + 64.f * (d0h * d0h + d1h * d1h);
  t += __shfl_xor_sync(0xffffffffu, t, 1); th += __shfl_xor_sync(0xffffffffu, th, 1);
  t += __shfl_xor_sync(0xffffffffu, t, 2); th += __shfl_xor_sync(0xffffffffu, th, 2);
  rstd_lo = rsqrtf(t * (1.f / 512.f) + 1e-5f);
  rstd_hi = rsqrtf(th * (1.f / 512.f) + 1e-5f);
}
__device__ __forceinline__ uint4 local_stats(const float (&v)[32]) {
  float s = 0.f, sh = 0.f;
#pragma unroll
  for (int i = 0; i < 4; i++) {
    s += (v[8 * i + 0] + v[8 * i + 1]) + (v[8 * i + 4] + v[8 * i + 5]);
    sh += (v[8 * i + 2] + v[8 * i + 3]) + (v[8 * i + 6] + v[8 * i + 7]);
  }
  s += __shfl_xor_sync(0xffffffffu, s, 1); sh += __shfl_xor_sync(0xffffffffu, sh, 1);
  s += __shfl_xor_sync(0xffffffffu, s, 2); sh += __shfl_xor_sync(0xffffffffu, sh, 2);
  float m = s * (1.f / 64.f), mh = sh * (1.f / 64.f);
  float q = 0.f, qh = 0.f;
#pragma unroll
  for (int i = 0; i < 4; i++) {
    float a = v[8 * i + 0] - m, b = v[8 * i + 1] - m, c = v[8 * i + 4] - m, d = v[8 * i + 5] - m;
    q += (a * a + b * b) + (c * c + d * d);
    float e = v[8 * i + 2] - mh, f = v[8 * i + 3] - mh, g = v[8 * i + 6] - mh, h = v[8 * i + 7] - mh;
    qh += (e * e + f * f) + (g * g + h * h);
  }
  q += __shfl_xor_sync(0xffffffffu, q, 1); qh += __shfl_xor_sync(0xffffffffu, qh, 1);
  q += __shfl_xor_sync(0xffffffffu, q, 2); qh += __shfl_xor_sync(0xffffffffu, qh, 2);
  return make_uint4(__float_as_uint(m), __float_as_uint(q), __float_as_uint(mh), __float_as_uint(qh));
}

__device__ __forceinline__ int slab_row0(int c, int g, int w) { return 1024 * g + 64 * c + 32 * (w >> 1) + (w & 1); }

__device__ __forceinline__ void owner_ln_publish(uint32_t sbase, const float (&v)[32], uint32_t tphase, uint32_t tag_xn) {
  PHASE_VARS;
  TS(40 + 4 * tphase);
  uint4 st = local_stats(v);
  if (qc == 0) sts128(sbase + SM_TSTAT + warp * 128 + qr * 16, st);
  uint4* xn = g_xn + ((c * 8 + j) * 32 + 4 * warp) * 32 + lane;
  uint4* xr = g_xraw + ((c * 8 + j) * 32 + 4 * warp) * 32 + lane;
  TS(41 + 4 * tphase);
  asm volatile("bar.sync 3, 256;" ::: "memory");
  TS(42 + 4 * tphase);
  const uint32_t rd = sbase + SM_TSTAT + qc * 256 + qr * 16;
  uint4 p0 = lds128(rd), p1 = lds128(rd + 128);
  float ml, rl, mh, rh;
  combine_stats(p0, p1, ml, rl, mh, rh);
  const float bl = -ml * rl, bh = -mh * rh;
#pragma unroll
  for (int i = 0; i < 4; i++) {
    uint4 o;
    o.x = set_tag(pack2(fmaf(v[8 * i + 0], rl, bl), fmaf(v[8 * i + 1], rl, bl)), tag_xn);
    o.y = pack2(fmaf(v[8 * i + 2], rh, bh), fmaf(v[8 * i + 3], rh, bh));
    o.z = pack2(fmaf(v[8 * i + 4], rl, bl), fmaf(v[8 * i + 5], rl, bl));
    o.w = pack2(fmaf(v[8 * i + 6], rh, bh), fmaf(v[8 * i + 7], rh, bh));
    st_ll(xn + i * 32, o);
  }
#pragma unroll
  for (int i = 0; i < 4; i++) {
    uint4 o;
    o.x = set_tag(pack2(v[8 * i + 0], v[8 * i + 1]), 1u);
    o.y = pack2(v[8 * i + 2], v[8 * i + 3]);
    o.z = pack2(v[8 * i + 4], v[8 * i + 5]);
    o.w = pack2(v[8 * i + 6], v[8 * i + 7]);
    st_ll(xr + i * 32, o);
  }
}

__device__ __forceinline__ uint4 pack8(const float* a) {
  return make_uint4(pack2(a[0], a[1]), pack2(a[2], a[3]), pack2(a[4], a[5]), pack2(a[6], a[7]));
}
template <int U> __device__ __forceinline__ uint4 glu8(const float* g, float cl, float ch) {
  return make_uint4(pack2(g[0] * cl * g[U], g[1] * cl * g[U + 1]), pack2(g[2] * ch * g[U + 2], g[3] * ch * g[U + 3]),
                    pack2(g[4] * cl * g[U + 4], g[5] * cl * g[U + 5]), pack2(g[6] * ch * g[U + 6], g[7] * ch * g[U + 7]));
}
__device__ __forceinline__ uint32_t hfma2(uint32_t a, uint32_t b, uint32_t c) {
  uint32_t d;
  asm("fma.rn.bf16x2 %0, %1, %2, %3;" : "=r"(d) : "r"(a), "r"(b), "r"(c));
  return d;
}
__device__ __forceinline__ void keep4(const uint4 (&a)[4]) { keep(a[0]); keep(a[1]); keep(a[2]); keep(a[3]); }

#define STAGGER 0

__global__ void __launch_bounds__(NTHREADS, 1)
fused_kernel(const __grid_constant__ CUtensorMap m_qkv, const __grid_constant__ CUtensorMap m_wo,
             const __grid_constant__ CUtensorMap m_gu2, const __grid_constant__ CUtensorMap m_gu1,
             const __grid_constant__ CUtensorMap m_guh, const __grid_constant__ CUtensorMap m_wd112,
             const __grid_constant__ CUtensorMap m_wd80, const __grid_constant__ CUtensorMap m_wd32,
             const __nv_bfloat16* __restrict__ x_in,
             __nv_bfloat16* __restrict__ out, const char* __restrict__ w_o, const char* __restrict__ w_g,
             const char* __restrict__ w_u, const char* __restrict__ w_d
) {
  extern __shared__ __align__(1024) unsigned char smem_raw[];
  const uint32_t sbase = smem_u32(smem_raw);
  const uint32_t bars = sbase + SM_MISC;
  if ((sbase & 0xFFFFFFu) != SMEM_ORIGIN) return;
  TG(60);

  uint32_t xw[16];
  if (threadIdx.x < 256) {
    const int bid = blockIdx.x, cc = ((bid >> 4) << 1) | (bid & 1), jj = (bid >> 1) & 7, ln = threadIdx.x & 31;
    const uint32_t* xp = reinterpret_cast<const uint32_t*>(x_in + (size_t)(slab_row0(cc, jj >> 2, jj & 3) + 2 * (ln >> 2)) * 512 + (threadIdx.x >> 5) * 64 + (ln & 3) * 2);
#pragma unroll
    for (int i = 0; i < 4; i++) {
      xw[4 * i] = __ldg(xp + i * 8); xw[4 * i + 1] = __ldg(xp + 16 * 256 + i * 8);
      xw[4 * i + 2] = __ldg(xp + i * 8 + 4); xw[4 * i + 3] = __ldg(xp + 16 * 256 + i * 8 + 4);
    }
  } else if (threadIdx.x == 256) {
    for (int i = 0; i < NGRAN; i++) { mbar_init(bars + BAR_FULL + 8 * i, 1); mbar_init(bars + BAR_EMPTY + 8 * i, 16); }
    asm volatile("fence.mbarrier_init.release.cluster;" ::: "memory");
    const int jj = (blockIdx.x >> 1) & 7;
    for (int kb = 0; kb < 4; kb++) {
      mbar_expect_tx(bars + BAR_FULL + 24 * kb, 24576);
      tma_3d(sbase + 3 * kb * GRAN, &m_qkv, bars + BAR_FULL + 24 * kb, 64 * jj, 64 * kb, 0);
    }
  }
  __syncthreads();
  asm volatile("barrier.cluster.arrive.release.aligned;" ::: "memory");

  if (threadIdx.x >= 256) {
    asm volatile("setmaxnreg.dec.sync.aligned.u32 40;");
    const int warp = threadIdx.x >> 5, lane = threadIdx.x & 31;
    const int j = (blockIdx.x >> 1) & 7, b = j & 1;
    const uint32_t rank = blockIdx.x & 1;
    asm volatile("barrier.cluster.wait.acquire.aligned; // producer" ::: "memory");
    if (warp == 8) {
      ProdRing r{0u, 0xFFFu};
      const int cb0 = 224 * j + 32 * b, hb0 = 224 * j + 192 * (b ^ 1);
      const int jp = j ^ 1, cbp = 224 * jp + 32 * (b ^ 1), hbp = 224 * jp + 192 * b;
#pragma unroll 1
      for (uint32_t L = 0; L < 2; L++) {
        r.pos = 0;
        PSTOP_AT(L == 0 ? 0 : 3);
#pragma unroll 1
        for (int kb = (L == 0 ? 4 : 0); kb < 8; kb++) {
          const uint32_t g0 = prod_acquire<3>(sbase, r);
          if (elect_one()) {
            mbar_expect_tx(bars + BAR_FULL + 8 * g0, 24576);
            if ((kb & 1) == rank) tma_3d_mc(sbase + g0 * GRAN, &m_qkv, bars + BAR_FULL + 8 * g0, 64 * j, 64 * kb, 0, 3);
          }
        }
        PSTOP_AT(10 * L + 1);
#pragma unroll 1
        for (int i = 0; i < 4; i++) {
          const uint32_t g0 = prod_acquire<2>(sbase, r);
          if (elect_one()) {
            mbar_expect_tx(bars + BAR_FULL + 8 * g0, 16384);
            if ((i & 1) == rank) tma_2d_mc(sbase + g0 * GRAN, &m_wo, bars + BAR_FULL + 8 * g0, 64 * j, 128 * i, 3);
          }
        }
        PSTOP_AT(10 * L + 2);
#pragma unroll 1
        for (int kb = 0; kb < 8; kb++) {
          const uint32_t g0 = prod_acquire<4>(sbase, r);
          if (elect_one()) {
            mbar_expect_tx(bars + BAR_FULL + 8 * g0, 32768);
            if ((kb & 1) == rank) tma_4d_mc(sbase + g0 * GRAN, &m_gu2, bars + BAR_FULL + 8 * g0, cb0, 64 * kb, 0, 0, 3);
          }
        }
#pragma unroll 1
        for (int kb = 0; kb < 8; kb++) {
          const uint32_t g0 = prod_acquire<3>(sbase, r);
          if (elect_one()) {
            mbar_expect_tx(bars + BAR_FULL + 8 * g0, 24576);
            if ((kb & 1) == rank) {
              tma_4d_mc(sbase + g0 * GRAN, &m_gu1, bars + BAR_FULL + 8 * g0, cb0 + 128, 64 * kb, 0, 0, 3);
              tma_3d_mc(sbase + g0 * GRAN + 16384, &m_guh, bars + BAR_FULL + 8 * g0, hb0, 64 * kb, 0, 3);
            }
          }
        }
        static_for<0, 16>([&](auto I) {
          constexpr int i = I.value, g0 = st_g0(ST_DN + i);
          prod_acquire_static<ST_DN + i>(sbase, L);
          if (elect_one()) {
            const uint32_t dst = sbase + g0 * GRAN, fb = bars + BAR_FULL + 8 * g0;
            const int n0 = 256 * b + 64 * dn_q(i);
            mbar_expect_tx(fb, 14336);
            if (((i >> 1) & 1) == rank) {
              if constexpr (dn_kh(i) == 0) {
                tma_2d_mc(dst, &m_wd112, fb, n0, dn_par(i) ? cbp : cb0, 3);
              } else {
                tma_2d_mc(dst, &m_wd80, fb, n0, (dn_par(i) ? cbp : cb0) + 112, 3);
                tma_2d_mc(dst + 10240, &m_wd32, fb, n0, dn_par(i) ? hbp : hb0, 3);
              }
            }
          }
        });
        r.par ^= flip_mask(ST_DN, NSTAGE);
      }
    } else if (warp == 9) {
      const int cta = blockIdx.x;
      if (lane == 0) l2_prefetch(w_o + cta * 4096, 4096);
      if (lane == 1) l2_prefetch(w_g + cta * 14336, 14336);
      if (lane == 2) l2_prefetch(w_u + cta * 14336, 14336);
      if (lane == 3) l2_prefetch(w_d + cta * 14336, 14336);
    }
    __syncwarp();
    asm volatile("barrier.cluster.arrive.release.aligned;\nbarrier.cluster.wait.acquire.aligned; // producer" ::: "memory");
  } else {
    asm volatile("setmaxnreg.inc.sync.aligned.u32 232;");
    TS(0);
    TG(61);

    {
      float v[32];
#pragma unroll
      for (int i = 0; i < 16; i++) { v[2 * i] = bf_lo(xw[i]); v[2 * i + 1] = bf_hi(xw[i]); }
      owner_ln_publish(sbase, v, 0u, 1u);
      asm volatile("barrier.cluster.wait.acquire.aligned; // consumer" ::: "memory");
    }
    STOP_AT(0);
    TS(1);

#pragma unroll 1
    for (uint32_t L = 0; L < 2; L++) {
      const uint32_t tag = L ^ 1;
      {
        PHASE_VARS;
        uint4 qf[4], kf[4], vf[4], pp[4];
        const int blk = 16 * g + c;
        const uint4* halo_src = g_halo + ((((L * 32 + (blk > 0 ? blk - 1 : 0)) * 8 + j) * 2 + (w & 1)) * 4) * 32 + lane;
        {
          float acc[96];
          uint4 A[3][4];
          const uint4* xs = g_xn + ((c * 8 + slab) * 32) * 32 + lane;
          bar_wg(1 + g);
          load_pk<4>(A[0], xs);
          ensure_pk<4>(A[0], xs, tag);
          TS(2 + 20 * L);
          load_pk<4>(A[1], xs + 128);
          static_for<0, 8>([&](auto I) {
            constexpr int kb = I.value;
            cons_acquire<kb>(sbase, L);
            wg_fence();
            static_for<0, 4>([&](auto K) { constexpr int k = K.value; wgmma_n192<kb == 0 && k == 0, 0>(acc, A[kb % 3][k], st_desc<kb, 2048, 8192, 1024, 1>(k)); });
            wg_commit();
            if constexpr (kb > 0) {
              wg_wait<1>();
              keep4(A[(kb + 2) % 3]);
              cons_release<kb - 1>(rel, lane);
            }
            if constexpr (kb + 1 < 8) ensure_pk<4>(A[(kb + 1) % 3], xs + (kb + 1) * 128, tag);
            if constexpr (kb + 2 < 8) load_pk<4>(A[(kb + 2) % 3], xs + (kb + 2) * 128);
          });
          wg_wait<0>();
          TS(3 + 20 * L);
          fence_acc(acc);
          keep4(A[1]);
          cons_release<7>(rel, lane);
#pragma unroll
          for (int h = 0; h < 4; h++) {
            kf[h] = pack8(&acc[32 + 8 * h]);
            const uint4 t = pack8(&acc[64 + 8 * h]);
            vf[h] = make_uint4(movm(t.x), movm(t.y), movm(t.z), movm(t.w));
            pp[h] = make_uint4(kf[h].y, kf[h].w, vf[h].y, vf[h].w);
          }
          if (w >= 2 && blk < 31) {
            uint4* hd = g_halo + ((((L * 32 + blk) * 8 + j) * 2 + (w & 1)) * 4) * 32 + lane;
#pragma unroll
            for (int h = 0; h < 4; h++) { uint4 t = pp[h]; t.x |= 1u; st_ll(hd + h * 32, t); }
          }
#pragma unroll
          for (int h = 0; h < 4; h++) sts128(areg + (28 + h) * 2048 + t128 * 16, pp[h]);
          if (w < 2 && blk > 0) load_pk<4>(pp, halo_src);
#pragma unroll
          for (int h = 0; h < 4; h++) qf[h] = pack8(&acc[8 * h]);
        }
        bar_wg(1 + g);
        const bool first = (w < 2) && (blk == 0);
        if (w >= 2) {
#pragma unroll
          for (int h = 0; h < 4; h++) pp[h] = lds128(areg + (28 + h) * 2048 + (t128 - 64) * 16);
        }
        bar_wg(1 + g);
        if (w < 2 && blk > 0) {
          ensure_pk<4>(pp, halo_src, 1u);
          uint4* hz = const_cast<uint4*>(halo_src);
#pragma unroll
          for (int h = 0; h < 4; h++) st_ll(hz + h * 32, make_uint4(0, 0, 0, 0));
        }
        TS(4 + 20 * L);
        const bool n0 = 2 * qc <= qr, n1 = 2 * qc + 1 <= qr;
        const uint32_t msk = (n0 ? 0xffffu : 0u) | (n1 ? 0xffff0000u : 0u);
        const float sc = 0.25f * 1.4426950408889634f;
        const float NEG = -1e30f;
        uint4* od = g_o + ((c * 8 + slab) * 32 + 4 * j) * 32 + lane;
        float l0[4], l1[4], h0[4], h1[4], ml[4], mh[4];
#pragma unroll
        for (int h = 0; h < 4; h++) {
          float sp[4], s0[4], s1[4];
          mma16816_z(sp, qf[h], pp[h].x, pp[h].y);
          mma16816_z(s0, qf[h], kf[h].x, kf[h].z);
          mma16816_z(s1, qf[h], kf[h].y, kf[h].w);
          if (first) { sp[0] = NEG; sp[1] = NEG; }
          l0[h] = n0 ? s0[0] : sp[0]; l1[h] = n1 ? s0[1] : sp[1];
          h0[h] = n0 ? s1[2] : s0[2]; h1[h] = n1 ? s1[3] : s0[3];
          ml[h] = fmaxf(l0[h], l1[h]); mh[h] = fmaxf(h0[h], h1[h]);
        }
#pragma unroll
        for (int h = 0; h < 4; h++) { ml[h] = fmaxf(ml[h], __shfl_xor_sync(0xffffffffu, ml[h], 1)); mh[h] = fmaxf(mh[h], __shfl_xor_sync(0xffffffffu, mh[h], 1)); }
#pragma unroll
        for (int h = 0; h < 4; h++) { ml[h] = fmaxf(ml[h], __shfl_xor_sync(0xffffffffu, ml[h], 2)); mh[h] = fmaxf(mh[h], __shfl_xor_sync(0xffffffffu, mh[h], 2)); }
        float sl[4], sh[4];
#pragma unroll
        for (int h = 0; h < 4; h++) {
          const float bl = -ml[h] * sc, bh = -mh[h] * sc;
          l0[h] = ex2(fmaf(l0[h], sc, bl)); l1[h] = ex2(fmaf(l1[h], sc, bl));
          h0[h] = ex2(fmaf(h0[h], sc, bh)); h1[h] = ex2(fmaf(h1[h], sc, bh));
          sl[h] = l0[h] + l1[h]; sh[h] = h0[h] + h1[h];
        }
#pragma unroll
        for (int h = 0; h < 4; h++) { sl[h] += __shfl_xor_sync(0xffffffffu, sl[h], 1); sh[h] += __shfl_xor_sync(0xffffffffu, sh[h], 1); }
#pragma unroll
        for (int h = 0; h < 4; h++) { sl[h] += __shfl_xor_sync(0xffffffffu, sl[h], 2); sh[h] += __shfl_xor_sync(0xffffffffu, sh[h], 2); }
#pragma unroll
        for (int h = 0; h < 4; h++) {
          const float il = rcp(sl[h]), ih = rcp(sh[h]);
          const uint32_t pl = pack2(l0[h] * il, l1[h] * il), ph = pack2(h0[h] * ih, h1[h] * ih);
          const uint4 P = make_uint4(pl & msk, ph & ~msk, 0u, ph & msk);
          float o0[4], o1[4];
          mma16816_z(o0, P, vf[h].x, vf[h].y);
          mma16816_z(o1, P, vf[h].z, vf[h].w);
          mma1688(o0, pl & ~msk, 0u, pp[h].z);
          mma1688(o1, pl & ~msk, 0u, pp[h].w);
          st_ll(od + h * 32, make_uint4(set_tag(pack2(o0[0], o0[1]), tag), pack2(o0[2], o0[3]), pack2(o1[0], o1[1]), pack2(o1[2], o1[3])));
        }
      }
      TS(5 + 20 * L);
      if (L == 0) { STOP_AT(1); } else { STOP_AT(11); }
      {
        PHASE_VARS;
        float acc[32];
        uint4 A[32], xr[4];
        const uint4* os = g_o + ((c * 8 + slab) * 32) * 32 + lane;
        uint4* xp = g_xraw + ((c * 8 + slab) * 32 + 4 * j) * 32 + lane;
        load_pk<4>(xr, xp);
        load_pk<4>(A, os);
        ensure_pk<4>(A, os, tag);
        TS(6 + 20 * L);
        load_pk<28>(A + 4, os + 128);
        static_for<0, 8>([&](auto I) {
          constexpr int kb = I.value;
          if constexpr ((kb & 1) == 0) cons_acquire<ST_WO + kb / 2>(sbase, L);
          if constexpr (kb > 0) ensure_pk<4>(A + 4 * kb, os + kb * 128, tag);
          wg_fence();
          static_for<0, 4>([&](auto K) {
            constexpr int k = K.value;
            wgmma_n64<kb == 0 && k == 0, 0>(acc, A[4 * kb + k], st_desc<ST_WO + kb / 2, 2048, 8192, 1024, 1>(4 * (kb & 1) + k));
          });
          wg_commit();
          if constexpr ((kb & 1) == 0 && kb > 0) { wg_wait<1>(); cons_release<ST_WO + kb / 2 - 1>(rel, lane); }
        });
        wg_wait<0>();
        TS(7 + 20 * L);
        fence_acc(acc);
#pragma unroll
        for (int k = 0; k < 32; k++) keep(A[k]);
        cons_release<ST_WO + 3>(rel, lane);
        ensure_pk<4>(xr, xp, 1u);
#pragma unroll
        for (int i = 0; i < 4; i++) {
          acc[8 * i + 0] += bf_lo(xr[i].x); acc[8 * i + 1] += bf_hi(xr[i].x); acc[8 * i + 2] += bf_lo(xr[i].y); acc[8 * i + 3] += bf_hi(xr[i].y);
          acc[8 * i + 4] += bf_lo(xr[i].z); acc[8 * i + 5] += bf_hi(xr[i].z); acc[8 * i + 6] += bf_lo(xr[i].w); acc[8 * i + 7] += bf_hi(xr[i].w);
          uint4 o = pack8(&acc[8 * i]);
          o.x = set_tag(o.x, 0u);
          st_ll(xp + i * 32, o);
        }
        uint4 st = local_stats(acc);
        st.x = set_tag(st.x, tag);
        if (qc == 0) st_ll(g_stats + ((c * 8 + slab) * 8 + j) * 8 + qr, st);
      }
      TS(8 + 20 * L);
      if (L == 0) { STOP_AT(2); } else { STOP_AT(12); }
      uint4 hs[14];
      {
        PHASE_VARS;
        float acc[128];
        uint4 A[3][4];
        const uint4* xs = g_xraw + ((c * 8 + slab) * 32) * 32 + lane;
        const uint4* sp = g_stats + ((c * 8 + slab) * 8 + 2 * qc) * 8 + qr;
        const uint32_t sm = areg + t128 * 16;
        uint32_t rl2, rh2, bl2, bh2;
        float cl, ch;
        {
          uint4 p[2];
          load_pk<4>(A[0], xs);
          p[0] = ld_ll(sp); p[1] = ld_ll(sp + 8);
          for (uint32_t n = 0; !ok_pk<2>(p, tag) && n < SPIN_LIMIT; n++) { load_pk<4>(A[0], xs); p[0] = ld_ll(sp); p[1] = ld_ll(sp + 8); }
          TS(9 + 20 * L);
          load_pk<4>(A[1], xs + 128);
          float ml, rl, mh, rh;
          combine_stats(p[0], p[1], ml, rl, mh, rh);
          rl2 = pack2(rl, rl); rh2 = pack2(rh, rh);
          const float rlb = bf_lo(rl2), rhb = bf_lo(rh2);
          bl2 = pack2(-ml * rlb, -ml * rlb); bh2 = pack2(-mh * rhb, -mh * rhb);
          cl = rl / rlb; cl *= cl; ch = rh / rhb; ch *= ch;
        }
        auto normalise = [&](uint4 (&xb)[4], int kb) {
#pragma unroll
          for (int k = 0; k < 4; k++) {
            xb[k].x = hfma2(xb[k].x, rl2, bl2); xb[k].y = hfma2(xb[k].y, rh2, bh2);
            xb[k].z = hfma2(xb[k].z, rl2, bl2); xb[k].w = hfma2(xb[k].w, rh2, bh2);
            sts128(sm + (kb * 4 + k) * 2048, xb[k]);
          }
        };
        ensure_pk<4>(A[0], xs, 0u);
        normalise(A[0], 0);
        static_for<0, 8>([&](auto I) {
          constexpr int kb = I.value;
          cons_acquire<ST_G1 + kb>(sbase, L);
          wg_fence();
          static_for<0, 4>([&](auto K) { constexpr int k = K.value; wgmma_n256<kb == 0 && k == 0, 0>(acc, A[kb % 3][k], st_desc<ST_G1 + kb, 2048, 8192, 1024, 1>(k)); });
          wg_commit();
          if constexpr (kb > 0) {
            wg_wait<1>();
            keep4(A[(kb + 2) % 3]);
            cons_release<ST_G1 + kb - 1>(rel, lane);
          }
          if constexpr (kb + 1 < 8) ensure_pk<4>(A[(kb + 1) % 3], xs + (kb + 1) * 128, 0u);
          if constexpr (kb + 2 < 8) load_pk<4>(A[(kb + 2) % 3], xs + (kb + 2) * 128);
          if constexpr (kb + 1 < 8) normalise(A[(kb + 1) % 3], kb + 1);
        });
        wg_wait<0>();
        TS(10 + 20 * L);
        fence_acc(acc);
        keep4(A[1]);
        cons_release<ST_G1 + 7>(rel, lane);
        uint4 B[2][4];
#pragma unroll
        for (int k = 0; k < 4; k++) B[0][k] = lds128(sm + k * 2048);
#pragma unroll
        for (int s = 0; s < 8; s++) hs[s] = glu8<32>(&acc[64 * (s >> 2) + 8 * (s & 3)], cl, ch);
        float acc2[96];
        uint4* hd = g_h + (((c * 8 + j) * 2 + g) * 14) * 128 + t128;
        const uint4* hsrc = g_h + (((c * 8 + (j ^ 1)) * 2 + g) * 14) * 128 + t128;
        static_for<0, 8>([&](auto I) {
          constexpr int kb = I.value;
          cons_acquire<ST_G2 + kb>(sbase, L);
          wg_fence();
          static_for<0, 4>([&](auto K) {
            constexpr int k = K.value;
            wgmma_n128<kb == 0 && k == 0, 0>(acc2, B[kb & 1][k], st_desc<ST_G2 + kb, 2048, 8192, 1024, 1>(k));
            wgmma_n64<kb == 0 && k == 0, 64>(acc2, B[kb & 1][k], st_desc<ST_G2 + kb, 1024, 4096, 512, 2>(k) + (16384 >> 4));
          });
          wg_commit();
          if constexpr (kb > 0) {
            wg_wait<1>();
            keep4(B[(kb + 1) & 1]);
            cons_release<ST_G2 + kb - 1>(rel, lane);
          }
          if constexpr (kb + 1 < 8) {
#pragma unroll
            for (int k = 0; k < 4; k++) B[(kb + 1) & 1][k] = lds128(sm + ((kb + 1) * 4 + k) * 2048);
          }
          if constexpr (kb < 4) {
            uint4 t = hs[2 * kb]; t.x = set_tag(t.x, tag); st_ll(hd + (2 * kb) * 128, t);
            t = hs[2 * kb + 1]; t.x = set_tag(t.x, tag); st_ll(hd + (2 * kb + 1) * 128, t);
          }
          if constexpr (kb == 6) {
#pragma unroll
            for (int k = 0; k < 8; k++) cp_async16(sm + k * 2048, hsrc + k * 128);
          }
        });
        wg_wait<0>();
        TS(11 + 20 * L);
        fence_acc(acc2);
        keep4(B[1]);
        cons_release<ST_G2 + 7>(rel, lane);
#pragma unroll
        for (int s = 0; s < 4; s++) hs[8 + s] = glu8<32>(&acc2[8 * s], cl, ch);
#pragma unroll
        for (int s = 0; s < 2; s++) hs[12 + s] = glu8<16>(&acc2[64 + 8 * s], cl, ch);
      }
      {
        PHASE_VARS;
        TS(12 + 20 * L);
        uint4* hd = g_h + (((c * 8 + j) * 2 + g) * 14) * 128 + t128;
        const uint4* hsrc = g_h + (((c * 8 + (j ^ 1)) * 2 + g) * 14) * 128 + t128;
        const uint32_t sm = areg + t128 * 16;
        uint4* pd = g_part + ((((c * 8 + slab) * 2 + cbit) * 4 + ca) * 16) * 32 + lane;
        uint4 hb[7];
        float a0[32], a1[32], a2[32], a3[32];
        auto publish = [&](float (&a)[32], int q, int s0, int s1) {
#pragma unroll
          for (int s = s0; s < s1; s++) {
            uint4 o = pack8(&a[8 * s]);
            o.x = set_tag(o.x, tag);
            st_ll(pd + (4 * q + s) * 32, o);
          }
        };
        static_for<0, 16>([&](auto I) {
          constexpr int i = I.value, q = dn_q(i), par = dn_par(i), kh = dn_kh(i);
          auto mm = [&](auto K) {
            constexpr int k = decltype(K)::value;
            constexpr bool init = (k == 0 && par == 0 && kh == 0);
            constexpr uint64_t db = st_desc<ST_DN + i, 2048, 8192, 1024, 1>(k);
            if constexpr (q == 0) { if constexpr (par) wgmma_n64<init, 0>(a0, hb[k], db); else wgmma_n64<init, 0>(a0, hs[7 * kh + k], db); }
            if constexpr (q == 1) { if constexpr (par) wgmma_n64<init, 0>(a1, hb[k], db); else wgmma_n64<init, 0>(a1, hs[7 * kh + k], db); }
            if constexpr (q == 2) { if constexpr (par) wgmma_n64<init, 0>(a2, hb[k], db); else wgmma_n64<init, 0>(a2, hs[7 * kh + k], db); }
            if constexpr (q == 3) { if constexpr (par) wgmma_n64<init, 0>(a3, hb[k], db); else wgmma_n64<init, 0>(a3, hs[7 * kh + k], db); }
          };
          cons_acquire<ST_DN + i>(sbase, L);
          wg_fence();
          mm(IC<0>{}); mm(IC<1>{}); mm(IC<2>{}); mm(IC<3>{}); mm(IC<4>{}); mm(IC<5>{}); mm(IC<6>{});
          wg_commit();
          if constexpr (i > 0) { wg_wait<1>(); cons_release<ST_DN + i - 1>(rel, lane); }
          if constexpr (i < 3) {
            uint4 t = hs[8 + 2 * i]; t.x = set_tag(t.x, tag); st_ll(hd + (8 + 2 * i) * 128, t);
            t = hs[9 + 2 * i]; t.x = set_tag(t.x, tag); st_ll(hd + (9 + 2 * i) * 128, t);
          }
          if constexpr (i == 4) {
#pragma unroll
            for (int k = 8; k < 14; k++) cp_async16(sm + k * 2048, hsrc + k * 128);
          }
          constexpr int n = i + 1;
          if constexpr (n < 16 && dn_par(n) && n != 4 && n != 7) {
            constexpr int r0 = 7 * dn_kh(n);
            if constexpr (n == 2 || n == 6) cp_wait_all();
#pragma unroll
            for (int k = 0; k < 7; k++) { if constexpr (n != 2) keep(hb[k]); hb[k] = lds128(sm + (r0 + k) * 2048); }
            if constexpr (n == 2 || n == 6) {
              uint32_t bad = 0;
#pragma unroll
              for (int k = 0; k < 7; k++) bad |= hb[k].x ^ tag;
              if (!__all_sync(0xffffffffu, (bad & 1u) == 0u)) {
                for (uint32_t it = 0; it < SPIN_LIMIT; it++) {
                  bad = 0;
#pragma unroll
                  for (int k = 0; k < 7; k++) { hb[k] = ld_ll(hsrc + (r0 + k) * 128); bad |= hb[k].x ^ tag; }
                  if (__all_sync(0xffffffffu, (bad & 1u) == 0u)) break;
                }
#pragma unroll
                for (int k = 0; k < 7; k++) sts128(sm + (r0 + k) * 2048, hb[k]);
              }
              if constexpr (n == 2) { TS(13 + 20 * L); } else { TS(14 + 20 * L); }
            }
          }
          if constexpr (i == 7) { fence_acc(a0); publish(a0, 0, 0, 4); }
          if constexpr (i == 8) { fence_acc(a1); publish(a1, 1, 0, 2); }
          if constexpr (i == 9) publish(a1, 1, 2, 4);
          if constexpr (i == 12) { fence_acc(a2); publish(a2, 2, 0, 2); }
          if constexpr (i == 13) publish(a2, 2, 2, 4);
        });
        wg_wait<0>();
        TS(15 + 20 * L);
        fence_acc(a3);
#pragma unroll
        for (int k = 0; k < 7; k++) { keep(hb[k]); keep(hs[7 + k]); }
        cons_release<NSTAGE - 1>(rel, lane);
        publish(a3, 3, 0, 4);
      }
      {
        PHASE_VARS;
        const uint4* xq = g_xraw + ((c * 8 + j) * 32 + 4 * warp) * 32 + lane;
        const uint4* ps = g_part + ((((c * 8 + j) * 2 + g) * 4) * 16 + 4 * w) * 32 + lane;
        uint4 xr[4], P[4][4];
        float v[32];
        load_pk<4>(xr, xq);
#pragma unroll
        for (int src = 0; src < 4; src++) load_pk<4>(P[src], ps + src * (16 * 32));
#pragma unroll
        for (int src = 0; src < 4; src++) ensure_pk<4>(P[src], ps + src * (16 * 32), tag);
        TS(16 + 20 * L);
        ensure_pk<4>(xr, xq, 0u);
#pragma unroll
        for (int i = 0; i < 4; i++) {
          v[8 * i + 0] = bf_lo(xr[i].x); v[8 * i + 1] = bf_hi(xr[i].x); v[8 * i + 2] = bf_lo(xr[i].y); v[8 * i + 3] = bf_hi(xr[i].y);
          v[8 * i + 4] = bf_lo(xr[i].z); v[8 * i + 5] = bf_hi(xr[i].z); v[8 * i + 6] = bf_lo(xr[i].w); v[8 * i + 7] = bf_hi(xr[i].w);
          float d[8] = {0, 0, 0, 0, 0, 0, 0, 0};
#pragma unroll
          for (int src = 0; src < 4; src++) {
            const uint4 p = P[src][i];
            d[0] += bf_lo(p.x); d[1] += bf_hi(p.x); d[2] += bf_lo(p.y); d[3] += bf_hi(p.y);
            d[4] += bf_lo(p.z); d[5] += bf_hi(p.z); d[6] += bf_lo(p.w); d[7] += bf_hi(p.w);
          }
#pragma unroll
          for (int k = 0; k < 8; k++) v[8 * i + k] += d[k];
        }
        if (L == 0) {
          owner_ln_publish(sbase, v, 1u, 0u);
        } else {
          uint32_t* op = reinterpret_cast<uint32_t*>(out + (size_t)(slab_row0(c, j >> 2, j & 3) + 2 * qr) * 512 + warp * 64 + qc * 2);
#pragma unroll
          for (int i = 0; i < 4; i++) {
            op[i * 8] = pack2(v[8 * i], v[8 * i + 1]);
            op[16 * 256 + i * 8] = pack2(v[8 * i + 2], v[8 * i + 3]);
            op[i * 8 + 4] = pack2(v[8 * i + 4], v[8 * i + 5]);
            op[16 * 256 + i * 8 + 4] = pack2(v[8 * i + 6], v[8 * i + 7]);
          }
        }
      }
      TS(17 + 20 * L);
      if (L == 0) { STOP_AT(3); }
    }
    TG(62);
    asm volatile("barrier.cluster.arrive.release.aligned;\nbarrier.cluster.wait.acquire.aligned; // consumer" ::: "memory");
    TG(63);
  }
}

typedef CUresult (*EncodeFn)(CUtensorMap*, CUtensorMapDataType, cuuint32_t, void*, const cuuint64_t*, const cuuint64_t*,
                             const cuuint32_t*, const cuuint32_t*, CUtensorMapInterleave, CUtensorMapSwizzle,
                             CUtensorMapL2promotion, CUtensorMapFloatOOBfill);

void encode(EncodeFn fn, CUtensorMap* m, int rank, const void* base, const cuuint64_t* dims, const cuuint64_t* strides,
            const cuuint32_t* box, CUtensorMapSwizzle sw) {
  cuuint32_t es[5] = {1, 1, 1, 1, 1};
  fn(m, CU_TENSOR_MAP_DATA_TYPE_BFLOAT16, (cuuint32_t)rank, const_cast<void*>(base), dims, strides, box, es,
     CU_TENSOR_MAP_INTERLEAVE_NONE, sw, CU_TENSOR_MAP_L2_PROMOTION_L2_128B, CU_TENSOR_MAP_FLOAT_OOB_FILL_NONE);
}

}

extern "C" void kernel_launch(void* const* d_in, const int* in_sizes, int n_in, void* d_out, int out_size) {
  (void)in_sizes; (void)n_in; (void)out_size;
  const __nv_bfloat16* x = (const __nv_bfloat16*)d_in[0];
  const char* wqkv = (const char*)d_in[1];
  const char* wo = (const char*)d_in[2];
  const char* wg = (const char*)d_in[4];
  const char* wu = (const char*)d_in[5];
  const char* wd = (const char*)d_in[6];

  static EncodeFn fn = nullptr;
  if (!fn) {
    void* p = nullptr;
    cudaDriverEntryPointQueryResult st;
    cudaGetDriverEntryPoint("cuTensorMapEncodeTiled", &p, cudaEnableDefault, &st);
    fn = (EncodeFn)p;
    cudaFuncSetAttribute(fused_kernel, cudaFuncAttributeMaxDynamicSharedMemorySize, SMEM_BYTES);
  }
  CUtensorMap m_qkv, m_wo, m_gu2, m_gu1, m_guh, m_wd112, m_wd80, m_wd32;
  {
    cuuint64_t dims[3] = {512, 512, 3}, str[2] = {3072, 1024};
    cuuint32_t box[3] = {64, 64, 3};
    encode(fn, &m_qkv, 3, wqkv, dims, str, box, CU_TENSOR_MAP_SWIZZLE_128B);
  }
  {
    cuuint64_t dims[2] = {512, 512}, str[1] = {1024};
    cuuint32_t box[2] = {64, 128};
    encode(fn, &m_wo, 2, wo, dims, str, box, CU_TENSOR_MAP_SWIZZLE_128B);
  }
  {
    const char* lo = wg < wu ? wg : wu;
    cuuint64_t diff = (cuuint64_t)(wg < wu ? wu - wg : wg - wu);
    cuuint64_t dims[4] = {1792, 512, 2, 2}, str[3] = {3584, diff, 128};
    cuuint32_t box2[4] = {64, 64, 2, 2}, box1[4] = {64, 64, 2, 1}, boxh[3] = {32, 64, 2};
    encode(fn, &m_gu2, 4, lo, dims, str, box2, CU_TENSOR_MAP_SWIZZLE_128B);
    encode(fn, &m_gu1, 4, lo, dims, str, box1, CU_TENSOR_MAP_SWIZZLE_128B);
    encode(fn, &m_guh, 3, lo, dims, str, boxh, CU_TENSOR_MAP_SWIZZLE_64B);
  }
  {
    cuuint64_t dims[2] = {512, 1792}, str[1] = {1024};
    cuuint32_t b112[2] = {64, 112}, b80[2] = {64, 80}, b32[2] = {64, 32};
    encode(fn, &m_wd112, 2, wd, dims, str, b112, CU_TENSOR_MAP_SWIZZLE_128B);
    encode(fn, &m_wd80, 2, wd, dims, str, b80, CU_TENSOR_MAP_SWIZZLE_128B);
    encode(fn, &m_wd32, 2, wd, dims, str, b32, CU_TENSOR_MAP_SWIZZLE_128B);
  }
  cudaLaunchConfig_t cfg = {};
  cfg.gridDim = dim3(128);
  cfg.blockDim = dim3(NTHREADS);
  cfg.dynamicSmemBytes = SMEM_BYTES;
  cfg.stream = cudaStreamPerThread;
  cudaLaunchAttribute at[1];
  at[0].id = cudaLaunchAttributeClusterDimension;
  at[0].val.clusterDim.x = 2; at[0].val.clusterDim.y = 1; at[0].val.clusterDim.z = 1;
  cfg.attrs = at; cfg.numAttrs = 1;
  cudaLaunchKernelEx(&cfg, fused_kernel, m_qkv, m_wo, m_gu2, m_gu1, m_guh, m_wd112, m_wd80, m_wd32, x, (__nv_bfloat16*)d_out, wo, wg, wu, wd
  );
}
```

```cpp
#include <cuda_runtime.h>
#include <cuda_bf16.h>
#include <cuda.h>
#include <stdint.h>

namespace {

constexpr int NTHREADS = 384;
constexpr int GRAN = 8192;
constexpr int NGRAN = 12;
constexpr int SM_AREG = NGRAN * GRAN;
constexpr int SM_MISC = SM_AREG + 131072;
constexpr int SM_TSTAT = SM_MISC + 256;
constexpr int SMEM_BYTES = SM_TSTAT + 1024;
constexpr int BAR_FULL = 0, BAR_EMPTY = 96, BAR_HRECV = 192, BAR_HREADY = 224;

__device__ uint4 g_xn[16 * 8 * 32 * 32];
__device__ uint4 g_xraw[16 * 8 * 32 * 32];
__device__ uint4 g_o[16 * 8 * 32 * 32];
__device__ uint4 g_stats[16 * 8 * 8 * 8];
__device__ uint4 g_halo[2 * 32 * 8 * 8 * 32];
__device__ uint4 g_part[16 * 8 * 2 * 4 * 16 * 32];

#define TS(n)
#define TG(n)
#define OPAQUE(x) asm volatile("" : "+r"(x))
#define PHASE_VARS                                                                                   \
  int tid_ = threadIdx.x, bid_ = blockIdx.x;                                                         \
  OPAQUE(tid_); OPAQUE(bid_);                                                                        \
  const int lane = tid_ & 31, warp = tid_ >> 5, g = warp >> 2, w = warp & 3, t128 = tid_ & 127;      \
  const int qr = lane >> 2, qc = lane & 3, slab = warp;                                              \
  const int c = bid_ >> 3, j = bid_ & 7, ca = j >> 1, cbit = j & 1;                                  \
  const uint32_t areg = sbase + SM_AREG + g * 65536;                                                 \
  (void)g; (void)j; (void)w; (void)t128; (void)qr; (void)qc; (void)slab; (void)c; (void)ca; (void)cbit; (void)areg; (void)lane
#define STOP_AT(n)
#define PSTOP_AT(n)

__device__ __forceinline__ uint32_t smem_u32(const void* p) { return (uint32_t)__cvta_generic_to_shared(p); }
__device__ __forceinline__ void mbar_init(uint32_t bar, uint32_t cnt) {
  asm volatile("mbarrier.init.shared::cta.b64 [%0], %1;" ::"r"(bar), "r"(cnt) : "memory");
}
__device__ __forceinline__ void mbar_expect_tx(uint32_t bar, uint32_t bytes) {
  asm volatile("mbarrier.arrive.expect_tx.shared::cta.b64 _, [%0], %1;" ::"r"(bar), "r"(bytes) : "memory");
}
__device__ __forceinline__ void mbar_arrive(uint32_t bar) {
  asm volatile("mbarrier.arrive.shared::cta.b64 _, [%0];" ::"r"(bar) : "memory");
}
__device__ __forceinline__ void mbar_arrive_remote(uint32_t cluster_addr) {
  asm volatile("mbarrier.arrive.relaxed.cluster.shared::cluster.b64 _, [%0];" ::"r"(cluster_addr) : "memory");
}
__device__ __forceinline__ bool mbar_try(uint32_t bar, uint32_t parity) {
  uint32_t ok;
  asm volatile("{\n.reg .pred p;\nmbarrier.try_wait.parity.shared::cta.b64 p, [%1], %2;\nselp.u32 %0, 1, 0, p;\n}"
               : "=r"(ok) : "r"(bar), "r"(parity) : "memory");
  return ok != 0;
}
constexpr uint32_t SPIN_LIMIT = 1u << 16;
constexpr uint32_t SMEM_ORIGIN = 1024;
__device__ __forceinline__ void mbar_wait(uint32_t bar, uint32_t parity) {
  for (uint32_t n = 0; !mbar_try(bar, parity) && n < SPIN_LIMIT; n++) {}
}
__device__ __forceinline__ uint32_t mapa(uint32_t addr, uint32_t rank) {
  uint32_t r;
  asm volatile("mapa.shared::cluster.u32 %0, %1, %2;" : "=r"(r) : "r"(addr), "r"(rank));
  return r;
}

__device__ __forceinline__ void tma_2d(uint32_t dst, const CUtensorMap* m, uint32_t bar, int c0, int c1) {
  asm volatile("cp.async.bulk.tensor.2d.shared::cluster.global.mbarrier::complete_tx::bytes [%0], [%1, {%3, %4}], [%2];"
               ::"r"(dst), "l"(m), "r"(bar), "r"(c0), "r"(c1) : "memory");
}
__device__ __forceinline__ void tma_3d(uint32_t dst, const CUtensorMap* m, uint32_t bar, int c0, int c1, int c2) {
  asm volatile("cp.async.bulk.tensor.3d.shared::cluster.global.mbarrier::complete_tx::bytes [%0], [%1, {%3, %4, %5}], [%2];"
               ::"r"(dst), "l"(m), "r"(bar), "r"(c0), "r"(c1), "r"(c2) : "memory");
}
__device__ __forceinline__ void tma_4d(uint32_t dst, const CUtensorMap* m, uint32_t bar, int c0, int c1, int c2, int c3) {
  asm volatile("cp.async.bulk.tensor.4d.shared::cluster.global.mbarrier::complete_tx::bytes [%0], [%1, {%3, %4, %5, %6}], [%2];"
               ::"r"(dst), "l"(m), "r"(bar), "r"(c0), "r"(c1), "r"(c2), "r"(c3) : "memory");
}
__device__ __forceinline__ void l2_prefetch(const void* p, uint32_t bytes) {
  asm volatile("cp.async.bulk.prefetch.L2.global [%0], %1;" ::"l"(p), "r"(bytes) : "memory");
}

__device__ __forceinline__ uint4 ld_ll(const uint4* p) {
  uint4 v;
  asm volatile("ld.relaxed.gpu.global.v4.u32 {%0,%1,%2,%3}, [%4];" : "=r"(v.x), "=r"(v.y), "=r"(v.z), "=r"(v.w) : "l"(p) : "memory");
  return v;
}
__device__ __forceinline__ void st_ll(uint4* p, uint4 v) {
  asm volatile("st.relaxed.gpu.global.v4.u32 [%0], {%1,%2,%3,%4};" ::"l"(p), "r"(v.x), "r"(v.y), "r"(v.z), "r"(v.w) : "memory");
}
__device__ __forceinline__ uint4 lds128(uint32_t a) {
  uint4 v;
  asm volatile("ld.shared.v4.u32 {%0,%1,%2,%3}, [%4];" : "=r"(v.x), "=r"(v.y), "=r"(v.z), "=r"(v.w) : "r"(a) : "memory");
  return v;
}
__device__ __forceinline__ void sts128(uint32_t a, uint4 v) {
  asm volatile("st.shared.v4.u32 [%0], {%1,%2,%3,%4};" ::"r"(a), "r"(v.x), "r"(v.y), "r"(v.z), "r"(v.w) : "memory");
}
__device__ __forceinline__ void st_async128(uint32_t cluster_addr, uint4 v, uint32_t cluster_bar) {
  asm volatile("st.async.weak.shared::cluster.mbarrier::complete_tx::bytes.v4.b32 [%0], {%1,%2,%3,%4}, [%5];"
               ::"r"(cluster_addr), "r"(v.x), "r"(v.y), "r"(v.z), "r"(v.w), "r"(cluster_bar) : "memory");
}
__device__ __forceinline__ uint32_t pack2(float lo, float hi) {
  uint32_t r;
  asm("cvt.rn.bf16x2.f32 %0, %1, %2;" : "=r"(r) : "f"(hi), "f"(lo));
  return r;
}
__device__ __forceinline__ float bf_lo(uint32_t w) { return __uint_as_float(w << 16); }
__device__ __forceinline__ float bf_hi(uint32_t w) { return __uint_as_float(w & 0xffff0000u); }
__device__ __forceinline__ uint32_t set_tag(uint32_t w, uint32_t tag) { return (w & ~1u) | tag; }
__device__ __forceinline__ uint32_t movm(uint32_t a) {
  uint32_t d;
  asm("movmatrix.sync.aligned.m8n8.trans.b16 %0, %1;" : "=r"(d) : "r"(a));
  return d;
}
__device__ __forceinline__ void mma16816(float (&d)[4], const uint4& a, uint32_t b0, uint32_t b1) {
  asm("mma.sync.aligned.m16n8k16.row.col.f32.bf16.bf16.f32 {%0,%1,%2,%3}, {%4,%5,%6,%7}, {%8,%9}, {%0,%1,%2,%3};"
               : "+f"(d[0]), "+f"(d[1]), "+f"(d[2]), "+f"(d[3])
               : "r"(a.x), "r"(a.y), "r"(a.z), "r"(a.w), "r"(b0), "r"(b1));
}
__device__ __forceinline__ void mma1688(float (&d)[4], uint32_t a0, uint32_t a1, uint32_t b0) {
  asm("mma.sync.aligned.m16n8k8.row.col.f32.bf16.bf16.f32 {%0,%1,%2,%3}, {%4,%5}, {%6}, {%0,%1,%2,%3};"
      : "+f"(d[0]), "+f"(d[1]), "+f"(d[2]), "+f"(d[3])
      : "r"(a0), "r"(a1), "r"(b0));
}
__device__ __forceinline__ void mma16816_z(float (&d)[4], const uint4& a, uint32_t b0, uint32_t b1) {
  asm("mma.sync.aligned.m16n8k16.row.col.f32.bf16.bf16.f32 {%0,%1,%2,%3}, {%4,%5,%6,%7}, {%8,%9}, {%10,%10,%10,%10};"
      : "=f"(d[0]), "=f"(d[1]), "=f"(d[2]), "=f"(d[3])
      : "r"(a.x), "r"(a.y), "r"(a.z), "r"(a.w), "r"(b0), "r"(b1), "f"(0.f));
}
__device__ __forceinline__ float ex2(float x) {
  float y;
  asm("ex2.approx.ftz.f32 %0, %1;" : "=f"(y) : "f"(x));
  return y;
}
__device__ __forceinline__ float rcp(float x) {
  float y;
  asm("rcp.approx.ftz.f32 %0, %1;" : "=f"(y) : "f"(x));
  return y;
}
__device__ __forceinline__ void cp_async16(uint32_t dst, const void* src) {
  asm volatile("cp.async.cg.shared.global [%0], [%1], 16;" ::"r"(dst), "l"(src) : "memory");
}
__device__ __forceinline__ void cp_commit() { asm volatile("cp.async.commit_group;" ::: "memory"); }
template <int N> __device__ __forceinline__ void cp_wait() { asm volatile("cp.async.wait_group %0;" ::"n"(N) : "memory"); }
__device__ __forceinline__ void bar_wg(int id) { asm volatile("bar.sync %0, 128;" ::"r"(id) : "memory"); }
__device__ __forceinline__ void wg_fence() { asm volatile("wgmma.fence.sync.aligned;" ::: "memory"); }
__device__ __forceinline__ void wg_commit() { asm volatile("wgmma.commit_group.sync.aligned;" ::: "memory"); }
template <int N> __device__ __forceinline__ void wg_wait() { asm volatile("wgmma.wait_group.sync.aligned %0;" ::"n"(N) : "memory"); }
__device__ __forceinline__ void keep(const uint4& a) { asm volatile("" ::"r"(a.x), "r"(a.y), "r"(a.z), "r"(a.w) : "memory"); }
template <int T> __device__ __forceinline__ void zero_acc(float (&d)[T]) {
#pragma unroll
  for (int i = 0; i < T; i++) d[i] = 0.f;
}
template <int T> __device__ __forceinline__ void fence_acc(float (&d)[T]) {
#pragma unroll
  for (int i = 0; i < T; i++) asm volatile("" : "+f"(d[i])::"memory");
}

template <int O, int T> __device__ __forceinline__ void wgmma_rs_n64(float (&d)[T], const uint4& a, uint64_t db) {
  asm volatile("{\n.reg .pred p;\nsetp.ne.b32 p, 1, 0;\n"
    "wgmma.mma_async.sync.aligned.m64n64k16.f32.bf16.bf16 "
    "{%0, %1, %2, %3, %4, %5, %6, %7, %8, %9, %10, %11, %12, %13, %14, %15, "
    "%16, %17, %18, %19, %20, %21, %22, %23, %24, %25, %26, %27, %28, %29, %30, %31}, "
    "{%32, %33, %34, %35}, %36, p, 1, 1, 1;\n}\n"
    : "+f"(d[O + 0]), "+f"(d[O + 1]), "+f"(d[O + 2]), "+f"(d[O + 3]), "+f"(d[O + 4]), "+f"(d[O + 5]), "+f"(d[O + 6]), "+f"(d[O + 7]),
      "+f"(d[O + 8]), "+f"(d[O + 9]), "+f"(d[O + 10]), "+f"(d[O + 11]), "+f"(d[O + 12]), "+f"(d[O + 13]), "+f"(d[O + 14]), "+f"(d[O + 15]),
      "+f"(d[O + 16]), "+f"(d[O + 17]), "+f"(d[O + 18]), "+f"(d[O + 19]), "+f"(d[O + 20]), "+f"(d[O + 21]), "+f"(d[O + 22]), "+f"(d[O + 23]),
      "+f"(d[O + 24]), "+f"(d[O + 25]), "+f"(d[O + 26]), "+f"(d[O + 27]), "+f"(d[O + 28]), "+f"(d[O + 29]), "+f"(d[O + 30]), "+f"(d[O + 31])
    : "r"(a.x), "r"(a.y), "r"(a.z), "r"(a.w), "l"(db));
}
template <int O, int T> __device__ __forceinline__ void wgmma_rs_n64_init(float (&d)[T], const uint4& a, uint64_t db) {
  asm volatile("{\n.reg .pred p;\nsetp.ne.b32 p, 0, 0;\n"
    "wgmma.mma_async.sync.aligned.m64n64k16.f32.bf16.bf16 "
    "{%0, %1, %2, %3, %4, %5, %6, %7, %8, %9, %10, %11, %12, %13, %14, %15, "
    "%16, %17, %18, %19, %20, %21, %22, %23, %24, %25, %26, %27, %28, %29, %30, %31}, "
    "{%32, %33, %34, %35}, %36, p, 1, 1, 1;\n}\n"
    : "=f"(d[O + 0]), "=f"(d[O + 1]), "=f"(d[O + 2]), "=f"(d[O + 3]), "=f"(d[O + 4]), "=f"(d[O + 5]), "=f"(d[O + 6]), "=f"(d[O + 7]),
      "=f"(d[O + 8]), "=f"(d[O + 9]), "=f"(d[O + 10]), "=f"(d[O + 11]), "=f"(d[O + 12]), "=f"(d[O + 13]), "=f"(d[O + 14]), "=f"(d[O + 15]),
      "=f"(d[O + 16]), "=f"(d[O + 17]), "=f"(d[O + 18]), "=f"(d[O + 19]), "=f"(d[O + 20]), "=f"(d[O + 21]), "=f"(d[O + 22]), "=f"(d[O + 23]),
      "=f"(d[O + 24]), "=f"(d[O + 25]), "=f"(d[O + 26]), "=f"(d[O + 27]), "=f"(d[O + 28]), "=f"(d[O + 29]), "=f"(d[O + 30]), "=f"(d[O + 31])
    : "r"(a.x), "r"(a.y), "r"(a.z), "r"(a.w), "l"(db));
}
template <bool INIT, int O, int T> __device__ __forceinline__ void wgmma_n64(float (&d)[T], const uint4& a, uint64_t db) {
  if constexpr (INIT) wgmma_rs_n64_init<O>(d, a, db); else wgmma_rs_n64<O>(d, a, db);
}
template <int O, int T> __device__ __forceinline__ void wgmma_rs_n128(float (&d)[T], const uint4& a, uint64_t db) {
  asm volatile("{\n.reg .pred p;\nsetp.ne.b32 p, 1, 0;\n"
    "wgmma.mma_async.sync.aligned.m64n128k16.f32.bf16.bf16 "
    "{%0, %1, %2, %3, %4, %5, %6, %7, %8, %9, %10, %11, %12, %13, %14, %15, "
    "%16, %17, %18, %19, %20, %21, %22, %23, %24, %25, %26, %27, %28, %29, %30, %31, "
    "%32, %33, %34, %35, %36, %37, %38, %39, %40, %41, %42, %43, %44, %45, %46, %47, "
    "%48, %49, %50, %51, %52, %53, %54, %55, %56, %57, %58, %59, %60, %61, %62, %63}, "
    "{%64, %65, %66, %67}, %68, p, 1, 1, 1;\n}\n"
    : "+f"(d[O + 0]), "+f"(d[O + 1]), "+f"(d[O + 2]), "+f"(d[O + 3]), "+f"(d[O + 4]), "+f"(d[O + 5]), "+f"(d[O + 6]), "+f"(d[O + 7]),
      "+f"(d[O + 8]), "+f"(d[O + 9]), "+f"(d[O + 10]), "+f"(d[O + 11]), "+f"(d[O + 12]), "+f"(d[O + 13]), "+f"(d[O + 14]), "+f"(d[O + 15]),
      "+f"(d[O + 16]), "+f"(d[O + 17]), "+f"(d[O + 18]), "+f"(d[O + 19]), "+f"(d[O + 20]), "+f"(d[O + 21]), "+f"(d[O + 22]), "+f"(d[O + 23]),
      "+f"(d[O + 24]), "+f"(d[O + 25]), "+f"(d[O + 26]), "+f"(d[O + 27]), "+f"(d[O + 28]), "+f"(d[O + 29]), "+f"(d[O + 30]), "+f"(d[O + 31]),
      "+f"(d[O + 32]), "+f"(d[O + 33]), "+f"(d[O + 34]), "+f"(d[O + 35]), "+f"(d[O + 36]), "+f"(d[O + 37]), "+f"(d[O + 38]), "+f"(d[O + 39]),
      "+f"(d[O + 40]), "+f"(d[O + 41]), "+f"(d[O + 42]), "+f"(d[O + 43]), "+f"(d[O + 44]), "+f"(d[O + 45]), "+f"(d[O + 46]), "+f"(d[O + 47]),
      "+f"(d[O + 48]), "+f"(d[O + 49]), "+f"(d[O + 50]), "+f"(d[O + 51]), "+f"(d[O + 52]), "+f"(d[O + 53]), "+f"(d[O + 54]), "+f"(d[O + 55]),
      "+f"(d[O + 56]), "+f"(d[O + 57]), "+f"(d[O + 58]), "+f"(d[O + 59]), "+f"(d[O + 60]), "+f"(d[O + 61]), "+f"(d[O + 62]), "+f"(d[O + 63])
    : "r"(a.x), "r"(a.y), "r"(a.z), "r"(a.w), "l"(db));
}
template <int O, int T> __device__ __forceinline__ void wgmma_rs_n128_init(float (&d)[T], const uint4& a, uint64_t db) {
  asm volatile("{\n.reg .pred p;\nsetp.ne.b32 p, 0, 0;\n"
    "wgmma.mma_async.sync.aligned.m64n128k16.f32.bf16.bf16 "
    "{%0, %1, %2, %3, %4, %5, %6, %7, %8, %9, %10, %11, %12, %13, %14, %15, "
    "%16, %17, %18, %19, %20, %21, %22, %23, %24, %25, %26, %27, %28, %29, %30, %31, "
    "%32, %33, %34, %35, %36, %37, %38, %39, %40, %41, %42, %43, %44, %45, %46, %47, "
    "%48, %49, %50, %51, %52, %53, %54, %55, %56, %57, %58, %59, %60, %61, %62, %63}, "
    "{%64, %65, %66, %67}, %68, p, 1, 1, 1;\n}\n"
    : "=f"(d[O + 0]), "=f"(d[O + 1]), "=f"(d[O + 2]), "=f"(d[O + 3]), "=f"(d[O + 4]), "=f"(d[O + 5]), "=f"(d[O + 6]), "=f"(d[O + 7]),
      "=f"(d[O + 8]), "=f"(d[O + 9]), "=f"(d[O + 10]), "=f"(d[O + 11]), "=f"(d[O + 12]), "=f"(d[O + 13]), "=f"(d[O + 14]), "=f"(d[O + 15]),
      "=f"(d[O + 16]), "=f"(d[O + 17]), "=f"(d[O + 18]), "=f"(d[O + 19]), "=f"(d[O + 20]), "=f"(d[O + 21]), "=f"(d[O + 22]), "=f"(d[O + 23]),
      "=f"(d[O + 24]), "=f"(d[O + 25]), "=f"(d[O + 26]), "=f"(d[O + 27]), "=f"(d[O + 28]), "=f"(d[O + 29]), "=f"(d[O + 30]), "=f"(d[O + 31]),
      "=f"(d[O + 32]), "=f"(d[O + 33]), "=f"(d[O + 34]), "=f"(d[O + 35]), "=f"(d[O + 36]), "=f"(d[O + 37]), "=f"(d[O + 38]), "=f"(d[O + 39]),
      "=f"(d[O + 40]), "=f"(d[O + 41]), "=f"(d[O + 42]), "=f"(d[O + 43]), "=f"(d[O + 44]), "=f"(d[O + 45]), "=f"(d[O + 46]), "=f"(d[O + 47]),
      "=f"(d[O + 48]), "=f"(d[O + 49]), "=f"(d[O + 50]), "=f"(d[O + 51]), "=f"(d[O + 52]), "=f"(d[O + 53]), "=f"(d[O + 54]), "=f"(d[O + 55]),
      "=f"(d[O + 56]), "=f"(d[O + 57]), "=f"(d[O + 58]), "=f"(d[O + 59]), "=f"(d[O + 60]), "=f"(d[O + 61]), "=f"(d[O + 62]), "=f"(d[O + 63])
    : "r"(a.x), "r"(a.y), "r"(a.z), "r"(a.w), "l"(db));
}
template <bool INIT, int O, int T> __device__ __forceinline__ void wgmma_n128(float (&d)[T], const uint4& a, uint64_t db) {
  if constexpr (INIT) wgmma_rs_n128_init<O>(d, a, db); else wgmma_rs_n128<O>(d, a, db);
}
template <int O, int T> __device__ __forceinline__ void wgmma_rs_n192(float (&d)[T], const uint4& a, uint64_t db) {
  asm volatile("{\n.reg .pred p;\nsetp.ne.b32 p, 1, 0;\n"
    "wgmma.mma_async.sync.aligned.m64n192k16.f32.bf16.bf16 "
    "{%0, %1, %2, %3, %4, %5, %6, %7, %8, %9, %10, %11, %12, %13, %14, %15, "
    "%16, %17, %18, %19, %20, %21, %22, %23, %24, %25, %26, %27, %28, %29, %30, %31, "
    "%32, %33, %34, %35, %36, %37, %38, %39, %40, %41, %42, %43, %44, %45, %46, %47, "
    "%48, %49, %50, %51, %52, %53, %54, %55, %56, %57, %58, %59, %60, %61, %62, %63, "
    "%64, %65, %66, %67, %68, %69, %70, %71, %72, %73, %74, %75, %76, %77, %78, %79, "
    "%80, %81, %82, %83, %84, %85, %86, %87, %88, %89, %90, %91, %92, %93, %94, %95}, "
    "{%96, %97, %98, %99}, %100, p, 1, 1, 1;\n}\n"
    : "+f"(d[O + 0]), "+f"(d[O + 1]), "+f"(d[O + 2]), "+f"(d[O + 3]), "+f"(d[O + 4]), "+f"(d[O + 5]), "+f"(d[O + 6]), "+f"(d[O + 7]),
      "+f"(d[O + 8]), "+f"(d[O + 9]), "+f"(d[O + 10]), "+f"(d[O + 11]), "+f"(d[O + 12]), "+f"(d[O + 13]), "+f"(d[O + 14]), "+f"(d[O + 15]),
      "+f"(d[O + 16]), "+f"(d[O + 17]), "+f"(d[O + 18]), "+f"(d[O + 19]), "+f"(d[O + 20]), "+f"(d[O + 21]), "+f"(d[O + 22]), "+f"(d[O + 23]),
      "+f"(d[O + 24]), "+f"(d[O + 25]), "+f"(d[O + 26]), "+f"(d[O + 27]), "+f"(d[O + 28]), "+f"(d[O + 29]), "+f"(d[O + 30]), "+f"(d[O + 31]),
      "+f"(d[O + 32]), "+f"(d[O + 33]), "+f"(d[O + 34]), "+f"(d[O + 35]), "+f"(d[O + 36]), "+f"(d[O + 37]), "+f"(d[O + 38]), "+f"(d[O + 39]),
      "+f"(d[O + 40]), "+f"(d[O + 41]), "+f"(d[O + 42]), "+f"(d[O + 43]), "+f"(d[O + 44]), "+f"(d[O + 45]), "+f"(d[O + 46]), "+f"(d[O + 47]),
      "+f"(d[O + 48]), "+f"(d[O + 49]), "+f"(d[O + 50]), "+f"(d[O + 51]), "+f"(d[O + 52]), "+f"(d[O + 53]), "+f"(d[O + 54]), "+f"(d[O + 55]),
      "+f"(d[O + 56]), "+f"(d[O + 57]), "+f"(d[O + 58]), "+f"(d[O + 59]), "+f"(d[O + 60]), "+f"(d[O + 61]), "+f"(d[O + 62]), "+f"(d[O + 63]),
      "+f"(d[O + 64]), "+f"(d[O + 65]), "+f"(d[O + 66]), "+f"(d[O + 67]), "+f"(d[O + 68]), "+f"(d[O + 69]), "+f"(d[O + 70]), "+f"(d[O + 71]),
      "+f"(d[O + 72]), "+f"(d[O + 73]), "+f"(d[O + 74]), "+f"(d[O + 75]), "+f"(d[O + 76]), "+f"(d[O + 77]), "+f"(d[O + 78]), "+f"(d[O + 79]),
      "+f"(d[O + 80]), "+f"(d[O + 81]), "+f"(d[O + 82]), "+f"(d[O + 83]), "+f"(d[O + 84]), "+f"(d[O + 85]), "+f"(d[O + 86]), "+f"(d[O + 87]),
      "+f"(d[O + 88]), "+f"(d[O + 89]), "+f"(d[O + 90]), "+f"(d[O + 91]), "+f"(d[O + 92]), "+f"(d[O + 93]), "+f"(d[O + 94]), "+f"(d[O + 95])
    : "r"(a.x), "r"(a.y), "r"(a.z), "r"(a.w), "l"(db));
}
template <int O, int T> __device__ __forceinline__ void wgmma_rs_n192_init(float (&d)[T], const uint4& a, uint64_t db) {
  asm volatile("{\n.reg .pred p;\nsetp.ne.b32 p, 0, 0;\n"
    "wgmma.mma_async.sync.aligned.m64n192k16.f32.bf16.bf16 "
    "{%0, %1, %2, %3, %4, %5, %6, %7, %8, %9, %10, %11, %12, %13, %14, %15, "
    "%16, %17, %18, %19, %20, %21, %22, %23, %24, %25, %26, %27, %28, %29, %30, %31, "
    "%32, %33, %34, %35, %36, %37, %38, %39, %40, %41, %42, %43, %44, %45, %46, %47, "
    "%48, %49, %50, %51, %52, %53, %54, %55, %56, %57, %58, %59, %60, %61, %62, %63, "
    "%64, %65, %66, %67, %68, %69, %70, %71, %72, %73, %74, %75, %76, %77, %78, %79, "
    "%80, %81, %82, %83, %84, %85, %86, %87, %88, %89, %90, %91, %92, %93, %94, %95}, "
    "{%96, %97, %98, %99}, %100, p, 1, 1, 1;\n}\n"
    : "=f"(d[O + 0]), "=f"(d[O + 1]), "=f"(d[O + 2]), "=f"(d[O + 3]), "=f"(d[O + 4]), "=f"(d[O + 5]), "=f"(d[O + 6]), "=f"(d[O + 7]),
      "=f"(d[O + 8]), "=f"(d[O + 9]), "=f"(d[O + 10]), "=f"(d[O + 11]), "=f"(d[O + 12]), "=f"(d[O + 13]), "=f"(d[O + 14]), "=f"(d[O + 15]),
      "=f"(d[O + 16]), "=f"(d[O + 17]), "=f"(d[O + 18]), "=f"(d[O + 19]), "=f"(d[O + 20]), "=f"(d[O + 21]), "=f"(d[O + 22]), "=f"(d[O + 23]),
      "=f"(d[O + 24]), "=f"(d[O + 25]), "=f"(d[O + 26]), "=f"(d[O + 27]), "=f"(d[O + 28]), "=f"(d[O + 29]), "=f"(d[O + 30]), "=f"(d[O + 31]),
      "=f"(d[O + 32]), "=f"(d[O + 33]), "=f"(d[O + 34]), "=f"(d[O + 35]), "=f"(d[O + 36]), "=f"(d[O + 37]), "=f"(d[O + 38]), "=f"(d[O + 39]),
      "=f"(d[O + 40]), "=f"(d[O + 41]), "=f"(d[O + 42]), "=f"(d[O + 43]), "=f"(d[O + 44]), "=f"(d[O + 45]), "=f"(d[O + 46]), "=f"(d[O + 47]),
      "=f"(d[O + 48]), "=f"(d[O + 49]), "=f"(d[O + 50]), "=f"(d[O + 51]), "=f"(d[O + 52]), "=f"(d[O + 53]), "=f"(d[O + 54]), "=f"(d[O + 55]),
      "=f"(d[O + 56]), "=f"(d[O + 57]), "=f"(d[O + 58]), "=f"(d[O + 59]), "=f"(d[O + 60]), "=f"(d[O + 61]), "=f"(d[O + 62]), "=f"(d[O + 63]),
      "=f"(d[O + 64]), "=f"(d[O + 65]), "=f"(d[O + 66]), "=f"(d[O + 67]), "=f"(d[O + 68]), "=f"(d[O + 69]), "=f"(d[O + 70]), "=f"(d[O + 71]),
      "=f"(d[O + 72]), "=f"(d[O + 73]), "=f"(d[O + 74]), "=f"(d[O + 75]), "=f"(d[O + 76]), "=f"(d[O + 77]), "=f"(d[O + 78]), "=f"(d[O + 79]),
      "=f"(d[O + 80]), "=f"(d[O + 81]), "=f"(d[O + 82]), "=f"(d[O + 83]), "=f"(d[O + 84]), "=f"(d[O + 85]), "=f"(d[O + 86]), "=f"(d[O + 87]),
      "=f"(d[O + 88]), "=f"(d[O + 89]), "=f"(d[O + 90]), "=f"(d[O + 91]), "=f"(d[O + 92]), "=f"(d[O + 93]), "=f"(d[O + 94]), "=f"(d[O + 95])
    : "r"(a.x), "r"(a.y), "r"(a.z), "r"(a.w), "l"(db));
}
template <bool INIT, int O, int T> __device__ __forceinline__ void wgmma_n192(float (&d)[T], const uint4& a, uint64_t db) {
  if constexpr (INIT) wgmma_rs_n192_init<O>(d, a, db); else wgmma_rs_n192<O>(d, a, db);
}
template <int O, int T> __device__ __forceinline__ void wgmma_rs_n256(float (&d)[T], const uint4& a, uint64_t db) {
  asm volatile("{\n.reg .pred p;\nsetp.ne.b32 p, 1, 0;\n"
    "wgmma.mma_async.sync.aligned.m64n256k16.f32.bf16.bf16 "
    "{%0, %1, %2, %3, %4, %5, %6, %7, %8, %9, %10, %11, %12, %13, %14, %15, "
    "%16, %17, %18, %19, %20, %21, %22, %23, %24, %25, %26, %27, %28, %29, %30, %31, "
    "%32, %33, %34, %35, %36, %37, %38, %39, %40, %41, %42, %43, %44, %45, %46, %47, "
    "%48, %49, %50, %51, %52, %53, %54, %55, %56, %57, %58, %59, %60, %61, %62, %63, "
    "%64, %65, %66, %67, %68, %69, %70, %71, %72, %73, %74, %75, %76, %77, %78, %79, "
    "%80, %81, %82, %83, %84, %85, %86, %87, %88, %89, %90, %91, %92, %93, %94, %95, "
    "%96, %97, %98, %99, %100, %101, %102, %103, %104, %105, %106, %107, %108, %109, %110, %111, "
    "%112, %113, %114, %115, %116, %117, %118, %119, %120, %121, %122, %123, %124, %125, %126, %127}, "
    "{%128, %129, %130, %131}, %132, p, 1, 1, 1;\n}\n"
    : "+f"(d[O + 0]), "+f"(d[O + 1]), "+f"(d[O + 2]), "+f"(d[O + 3]), "+f"(d[O + 4]), "+f"(d[O + 5]), "+f"(d[O + 6]), "+f"(d[O + 7]),
      "+f"(d[O + 8]), "+f"(d[O + 9]), "+f"(d[O + 10]), "+f"(d[O + 11]), "+f"(d[O + 12]), "+f"(d[O + 13]), "+f"(d[O + 14]), "+f"(d[O + 15]),
      "+f"(d[O + 16]), "+f"(d[O + 17]), "+f"(d[O + 18]), "+f"(d[O + 19]), "+f"(d[O + 20]), "+f"(d[O + 21]), "+f"(d[O + 22]), "+f"(d[O + 23]),
      "+f"(d[O + 24]), "+f"(d[O + 25]), "+f"(d[O + 26]), "+f"(d[O + 27]), "+f"(d[O + 28]), "+f"(d[O + 29]), "+f"(d[O + 30]), "+f"(d[O + 31]),
      "+f"(d[O + 32]), "+f"(d[O + 33]), "+f"(d[O + 34]), "+f"(d[O + 35]), "+f"(d[O + 36]), "+f"(d[O + 37]), "+f"(d[O + 38]), "+f"(d[O + 39]),
      "+f"(d[O + 40]), "+f"(d[O + 41]), "+f"(d[O + 42]), "+f"(d[O + 43]), "+f"(d[O + 44]), "+f"(d[O + 45]), "+f"(d[O + 46]), "+f"(d[O + 47]),
      "+f"(d[O + 48]), "+f"(d[O + 49]), "+f"(d[O + 50]), "+f"(d[O + 51]), "+f"(d[O + 52]), "+f"(d[O + 53]), "+f"(d[O + 54]), "+f"(d[O + 55]),
      "+f"(d[O + 56]), "+f"(d[O + 57]), "+f"(d[O + 58]), "+f"(d[O + 59]), "+f"(d[O + 60]), "+f"(d[O + 61]), "+f"(d[O + 62]), "+f"(d[O + 63]),
      "+f"(d[O + 64]), "+f"(d[O + 65]), "+f"(d[O + 66]), "+f"(d[O + 67]), "+f"(d[O + 68]), "+f"(d[O + 69]), "+f"(d[O + 70]), "+f"(d[O + 71]),
      "+f"(d[O + 72]), "+f"(d[O + 73]), "+f"(d[O + 74]), "+f"(d[O + 75]), "+f"(d[O + 76]), "+f"(d[O + 77]), "+f"(d[O + 78]), "+f"(d[O + 79]),
      "+f"(d[O + 80]), "+f"(d[O + 81]), "+f"(d[O + 82]), "+f"(d[O + 83]), "+f"(d[O + 84]), "+f"(d[O + 85]), "+f"(d[O + 86]), "+f"(d[O + 87]),
      "+f"(d[O + 88]), "+f"(d[O + 89]), "+f"(d[O + 90]), "+f"(d[O + 91]), "+f"(d[O + 92]), "+f"(d[O + 93]), "+f"(d[O + 94]), "+f"(d[O + 95]),
      "+f"(d[O + 96]), "+f"(d[O + 97]), "+f"(d[O + 98]), "+f"(d[O + 99]), "+f"(d[O + 100]), "+f"(d[O + 101]), "+f"(d[O + 102]), "+f"(d[O + 103]),
      "+f"(d[O + 104]), "+f"(d[O + 105]), "+f"(d[O + 106]), "+f"(d[O + 107]), "+f"(d[O + 108]), "+f"(d[O + 109]), "+f"(d[O + 110]), "+f"(d[O + 111]),
      "+f"(d[O + 112]), "+f"(d[O + 113]), "+f"(d[O + 114]), "+f"(d[O + 115]), "+f"(d[O + 116]), "+f"(d[O + 117]), "+f"(d[O + 118]), "+f"(d[O + 119]),
      "+f"(d[O + 120]), "+f"(d[O + 121]), "+f"(d[O + 122]), "+f"(d[O + 123]), "+f"(d[O + 124]), "+f"(d[O + 125]), "+f"(d[O + 126]), "+f"(d[O + 127])
    : "r"(a.x), "r"(a.y), "r"(a.z), "r"(a.w), "l"(db));
}
template <int O, int T> __device__ __forceinline__ void wgmma_rs_n256_init(float (&d)[T], const uint4& a, uint64_t db) {
  asm volatile("{\n.reg .pred p;\nsetp.ne.b32 p, 0, 0;\n"
    "wgmma.mma_async.sync.aligned.m64n256k16.f32.bf16.bf16 "
    "{%0, %1, %2, %3, %4, %5, %6, %7, %8, %9, %10, %11, %12, %13, %14, %15, "
    "%16, %17, %18, %19, %20, %21, %22, %23, %24, %25, %26, %27, %28, %29, %30, %31, "
    "%32, %33, %34, %35, %36, %37, %38, %39, %40, %41, %42, %43, %44, %45, %46, %47, "
    "%48, %49, %50, %51, %52, %53, %54, %55, %56, %57, %58, %59, %60, %61, %62, %63, "
    "%64, %65, %66, %67, %68, %69, %70, %71, %72, %73, %74, %75, %76, %77, %78, %79, "
    "%80, %81, %82, %83, %84, %85, %86, %87, %88, %89, %90, %91, %92, %93, %94, %95, "
    "%96, %97, %98, %99, %100, %101, %102, %103, %104, %105, %106, %107, %108, %109, %110, %111, "
    "%112, %113, %114, %115, %116, %117, %118, %119, %120, %121, %122, %123, %124, %125, %126, %127}, "
    "{%128, %129, %130, %131}, %132, p, 1, 1, 1;\n}\n"
    : "=f"(d[O + 0]), "=f"(d[O + 1]), "=f"(d[O + 2]), "=f"(d[O + 3]), "=f"(d[O + 4]), "=f"(d[O + 5]), "=f"(d[O + 6]), "=f"(d[O + 7]),
      "=f"(d[O + 8]), "=f"(d[O + 9]), "=f"(d[O + 10]), "=f"(d[O + 11]), "=f"(d[O + 12]), "=f"(d[O + 13]), "=f"(d[O + 14]), "=f"(d[O + 15]),
      "=f"(d[O + 16]), "=f"(d[O + 17]), "=f"(d[O + 18]), "=f"(d[O + 19]), "=f"(d[O + 20]), "=f"(d[O + 21]), "=f"(d[O + 22]), "=f"(d[O + 23]),
      "=f"(d[O + 24]), "=f"(d[O + 25]), "=f"(d[O + 26]), "=f"(d[O + 27]), "=f"(d[O + 28]), "=f"(d[O + 29]), "=f"(d[O + 30]), "=f"(d[O + 31]),
      "=f"(d[O + 32]), "=f"(d[O + 33]), "=f"(d[O + 34]), "=f"(d[O + 35]), "=f"(d[O + 36]), "=f"(d[O + 37]), "=f"(d[O + 38]), "=f"(d[O + 39]),
      "=f"(d[O + 40]), "=f"(d[O + 41]), "=f"(d[O + 42]), "=f"(d[O + 43]), "=f"(d[O + 44]), "=f"(d[O + 45]), "=f"(d[O + 46]), "=f"(d[O + 47]),
      "=f"(d[O + 48]), "=f"(d[O + 49]), "=f"(d[O + 50]), "=f"(d[O + 51]), "=f"(d[O + 52]), "=f"(d[O + 53]), "=f"(d[O + 54]), "=f"(d[O + 55]),
      "=f"(d[O + 56]), "=f"(d[O + 57]), "=f"(d[O + 58]), "=f"(d[O + 59]), "=f"(d[O + 60]), "=f"(d[O + 61]), "=f"(d[O + 62]), "=f"(d[O + 63]),
      "=f"(d[O + 64]), "=f"(d[O + 65]), "=f"(d[O + 66]), "=f"(d[O + 67]), "=f"(d[O + 68]), "=f"(d[O + 69]), "=f"(d[O + 70]), "=f"(d[O + 71]),
      "=f"(d[O + 72]), "=f"(d[O + 73]), "=f"(d[O + 74]), "=f"(d[O + 75]), "=f"(d[O + 76]), "=f"(d[O + 77]), "=f"(d[O + 78]), "=f"(d[O + 79]),
      "=f"(d[O + 80]), "=f"(d[O + 81]), "=f"(d[O + 82]), "=f"(d[O + 83]), "=f"(d[O + 84]), "=f"(d[O + 85]), "=f"(d[O + 86]), "=f"(d[O + 87]),
      "=f"(d[O + 88]), "=f"(d[O + 89]), "=f"(d[O + 90]), "=f"(d[O + 91]), "=f"(d[O + 92]), "=f"(d[O + 93]), "=f"(d[O + 94]), "=f"(d[O + 95]),
      "=f"(d[O + 96]), "=f"(d[O + 97]), "=f"(d[O + 98]), "=f"(d[O + 99]), "=f"(d[O + 100]), "=f"(d[O + 101]), "=f"(d[O + 102]), "=f"(d[O + 103]),
      "=f"(d[O + 104]), "=f"(d[O + 105]), "=f"(d[O + 106]), "=f"(d[O + 107]), "=f"(d[O + 108]), "=f"(d[O + 109]), "=f"(d[O + 110]), "=f"(d[O + 111]),
      "=f"(d[O + 112]), "=f"(d[O + 113]), "=f"(d[O + 114]), "=f"(d[O + 115]), "=f"(d[O + 116]), "=f"(d[O + 117]), "=f"(d[O + 118]), "=f"(d[O + 119]),
      "=f"(d[O + 120]), "=f"(d[O + 121]), "=f"(d[O + 122]), "=f"(d[O + 123]), "=f"(d[O + 124]), "=f"(d[O + 125]), "=f"(d[O + 126]), "=f"(d[O + 127])
    : "r"(a.x), "r"(a.y), "r"(a.z), "r"(a.w), "l"(db));
}
template <bool INIT, int O, int T> __device__ __forceinline__ void wgmma_n256(float (&d)[T], const uint4& a, uint64_t db) {
  if constexpr (INIT) wgmma_rs_n256_init<O>(d, a, db); else wgmma_rs_n256<O>(d, a, db);
}

template <int N> __device__ __forceinline__ void load_pk(uint4* a, const uint4* p) {
#pragma unroll
  for (int i = 0; i < N; i++) a[i] = ld_ll(p + i * 32);
}
__device__ __forceinline__ uint32_t xor_or(uint32_t a, uint32_t b, uint32_t t) {
  uint32_t r;
  asm("lop3.b32 %0, %1, %2, %3, 0x7E;" : "=r"(r) : "r"(a), "r"(b), "r"(t));
  return r;
}
template <int N> __device__ __forceinline__ bool ok_pk(const uint4* a, uint32_t tag) {
  static_assert(N % 2 == 0, "");
  uint32_t x = xor_or(a[0].x, a[1].x, tag);
#pragma unroll
  for (int i = 2; i < N; i += 2) x |= xor_or(a[i].x, a[i + 1].x, tag);
  return __all_sync(0xffffffffu, (x & 1u) == 0u);
}
template <int N> __device__ __forceinline__ void ensure_pk(uint4* a, const uint4* p, uint32_t tag) {
  if (ok_pk<N>(a, tag)) return;
  uint32_t n = 0;
  do { load_pk<N>(a, p); } while (!ok_pk<N>(a, tag) && ++n < SPIN_LIMIT);
}

constexpr int NSTAGE = 44;
constexpr int ST_WO = 8, ST_G1 = 12, ST_G2 = 20, ST_DN = 28;
__host__ __device__ constexpr int st_len(int s) { return s < ST_WO ? 3 : s < ST_G1 ? 2 : s < ST_G2 ? 4 : s < ST_DN ? 3 : 2; }
__host__ __device__ constexpr int st_g0(int s) {
  int pos = 0, g0 = 0;
  for (int i = 0; i <= s; i++) {
    if (pos + st_len(i) > NGRAN) pos = 0;
    g0 = pos;
    pos += st_len(i);
  }
  return g0;
}
__host__ __device__ constexpr int cnt_first(int g, int s) {
  int n = 0;
  for (int i = 0; i < s; i++) n += (st_g0(i) == g);
  return n;
}
__host__ __device__ constexpr int cnt_cover(int g, int s) {
  int n = 0;
  for (int i = 0; i < s; i++) n += (g >= st_g0(i) && g < st_g0(i) + st_len(i));
  return n;
}
__host__ __device__ constexpr uint32_t flip_mask(int s0, int s1) {
  uint32_t m = 0;
  for (int i = s0; i < s1; i++) m ^= ((1u << st_len(i)) - 1u) << st_g0(i);
  return m;
}
__host__ __device__ constexpr int dn_q(int i) { return i < 3 ? 0 : i < 6 ? 1 : i == 6 ? 0 : i == 7 ? 1 : i < 12 ? 2 : 3; }
__host__ __device__ constexpr int dn_par(int i) { return i < 8 ? (i == 2 || i == 4 || i >= 6) : (i & 1); }
__host__ __device__ constexpr int dn_kh(int i) { return i < 8 ? (i == 1 || i >= 5) : ((i & 3) >= 2); }
template <int I> struct IC { static constexpr int value = I; };
template <int B, int E, typename F> __device__ __forceinline__ void static_for(F&& f) {
  if constexpr (B < E) { f(IC<B>{}); static_for<B + 1, E>(f); }
}
template <int S> __device__ __forceinline__ void cons_acquire(uint32_t sbase, uint32_t L) {
  constexpr int g0 = st_g0(S);
  constexpr uint32_t p0 = cnt_first(g0, S) & 1, odd = cnt_first(g0, NSTAGE) & 1;
  mbar_wait(sbase + SM_MISC + BAR_FULL + 8 * g0, p0 ^ (L & odd));
}
template <int S> __device__ __forceinline__ void cons_release(uint32_t sbase, int lane) {
  if (lane < st_len(S)) mbar_arrive(sbase + SM_MISC + BAR_EMPTY + 8 * st_g0(S) + 8 * lane);
}
__device__ __forceinline__ bool elect_one() {
  uint32_t p;
  asm volatile("{\n.reg .pred P;\nelect.sync _|P, 0xffffffff;\nselp.u32 %0, 1, 0, P;\n}" : "=r"(p));
  return p != 0;
}
struct ProdRing { uint32_t pos, par; };
template <int N> __device__ __forceinline__ uint32_t prod_acquire(uint32_t sbase, ProdRing& r) {
  if (r.pos + N > NGRAN) r.pos = 0;
  const uint32_t g0 = r.pos;
#pragma unroll
  for (uint32_t i = 0; i < N; i++) mbar_wait(sbase + SM_MISC + BAR_EMPTY + 8 * (g0 + i), ((r.par >> (g0 + i)) & 1u) ^ 1u);
  r.par ^= ((1u << N) - 1u) << g0;
  r.pos = g0 + N;
  return g0;
}
template <int S> __device__ __forceinline__ void prod_acquire_static(uint32_t sbase, uint32_t L) {
  constexpr int g0 = st_g0(S);
  static_for<0, st_len(S)>([&](auto I) {
    constexpr int g = g0 + I.value;
    constexpr uint32_t p0 = cnt_cover(g, S) & 1, odd = cnt_cover(g, NSTAGE) & 1;
    mbar_wait(sbase + SM_MISC + BAR_EMPTY + 8 * g, p0 ^ (L & odd) ^ 1u);
  });
}
template <int S, int KSTEP_BYTES, int LBO, int SBO, int SWZ> __device__ __forceinline__ constexpr uint64_t st_desc(int k) {
  return (uint64_t)((SMEM_ORIGIN + st_g0(S) * GRAN + k * KSTEP_BYTES) >> 4) | ((uint64_t)(LBO >> 4) << 16) |
         ((uint64_t)(SBO >> 4) << 32) | ((uint64_t)SWZ << 62);
}

__device__ __forceinline__ void combine_stats(const uint4& p0, const uint4& p1, float& mean_lo, float& rstd_lo, float& mean_hi, float& rstd_hi) {
  float m0 = __uint_as_float(p0.x), q0 = __uint_as_float(p0.y), m0h = __uint_as_float(p0.z), q0h = __uint_as_float(p0.w);
  float m1 = __uint_as_float(p1.x), q1 = __uint_as_float(p1.y), m1h = __uint_as_float(p1.z), q1h = __uint_as_float(p1.w);
  float s = m0 + m1, sh = m0h + m1h;
  s += __shfl_xor_sync(0xffffffffu, s, 1); sh += __shfl_xor_sync(0xffffffffu, sh, 1);
  s += __shfl_xor_sync(0xffffffffu, s, 2); sh += __shfl_xor_sync(0xffffffffu, sh, 2);
  mean_lo = s * 0.125f; mean_hi = sh * 0.125f;
  float d0 = m0 - mean_lo, d1 = m1 - mean_lo, d0h = m0h - mean_hi, d1h = m1h - mean_hi;
  float t = q0 + q1 + 64.f * (d0 * d0 + d1 * d1), th = q0h + q1h + 64.f * (d0h * d0h + d1h * d1h);
  t += __shfl_xor_sync(0xffffffffu, t, 1); th += __shfl_xor_sync(0xffffffffu, th, 1);
  t += __shfl_xor_sync(0xffffffffu, t, 2); th += __shfl_xor_sync(0xffffffffu, th, 2);
  rstd_lo = rsqrtf(t * (1.f / 512.f) + 1e-5f);
  rstd_hi = rsqrtf(th * (1.f / 512.f) + 1e-5f);
}
__device__ __forceinline__ uint4 local_stats(const float (&v)[32]) {
  float s = 0.f, sh = 0.f;
#pragma unroll
  for (int i = 0; i < 4; i++) {
    s += (v[8 * i + 0] + v[8 * i + 1]) + (v[8 * i + 4] + v[8 * i + 5]);
    sh += (v[8 * i + 2] + v[8 * i + 3]) + (v[8 * i + 6] + v[8 * i + 7]);
  }
  s += __shfl_xor_sync(0xffffffffu, s, 1); sh += __shfl_xor_sync(0xffffffffu, sh, 1);
  s += __shfl_xor_sync(0xffffffffu, s, 2); sh += __shfl_xor_sync(0xffffffffu, sh, 2);
  float m = s * (1.f / 64.f), mh = sh * (1.f / 64.f);
  float q = 0.f, qh = 0.f;
#pragma unroll
  for (int i = 0; i < 4; i++) {
    float a = v[8 * i + 0] - m, b = v[8 * i + 1] - m, c = v[8 * i + 4] - m, d = v[8 * i + 5] - m;
    q += (a * a + b * b) + (c * c + d * d);
    float e = v[8 * i + 2] - mh, f = v[8 * i + 3] - mh, g = v[8 * i + 6] - mh, h = v[8 * i + 7] - mh;
    qh += (e * e + f * f) + (g * g + h * h);
  }
  q += __shfl_xor_sync(0xffffffffu, q, 1); qh += __shfl_xor_sync(0xffffffffu, qh, 1);
  q += __shfl_xor_sync(0xffffffffu, q, 2); qh += __shfl_xor_sync(0xffffffffu, qh, 2);
  return make_uint4(__float_as_uint(m), __float_as_uint(q), __float_as_uint(mh), __float_as_uint(qh));
}

__device__ __forceinline__ int slab_row0(int c, int g, int w) { return 1024 * g + 64 * c + 32 * (w >> 1) + (w & 1); }

__device__ __forceinline__ void owner_ln_publish(uint32_t sbase, const float (&v)[32], uint32_t tphase, uint32_t tag_xn) {
  PHASE_VARS;
  TS(40 + 4 * tphase);
  uint4 st = local_stats(v);
  if (qc == 0) sts128(sbase + SM_TSTAT + warp * 128 + qr * 16, st);
  uint4* xn = g_xn + ((c * 8 + j) * 32 + 4 * warp) * 32 + lane;
  uint4* xr = g_xraw + ((c * 8 + j) * 32 + 4 * warp) * 32 + lane;
  TS(41 + 4 * tphase);
  asm volatile("bar.sync 3, 256;" ::: "memory");
  TS(42 + 4 * tphase);
  const uint32_t rd = sbase + SM_TSTAT + qc * 256 + qr * 16;
  uint4 p0 = lds128(rd), p1 = lds128(rd + 128);
  float ml, rl, mh, rh;
  combine_stats(p0, p1, ml, rl, mh, rh);
  const float bl = -ml * rl, bh = -mh * rh;
#pragma unroll
  for (int i = 0; i < 4; i++) {
    uint4 o;
    o.x = set_tag(pack2(fmaf(v[8 * i + 0], rl, bl), fmaf(v[8 * i + 1], rl, bl)), tag_xn);
    o.y = pack2(fmaf(v[8 * i + 2], rh, bh), fmaf(v[8 * i + 3], rh, bh));
    o.z = pack2(fmaf(v[8 * i + 4], rl, bl), fmaf(v[8 * i + 5], rl, bl));
    o.w = pack2(fmaf(v[8 * i + 6], rh, bh), fmaf(v[8 * i + 7], rh, bh));
    st_ll(xn + i * 32, o);
  }
#pragma unroll
  for (int i = 0; i < 4; i++) {
    uint4 o;
    o.x = set_tag(pack2(v[8 * i + 0], v[8 * i + 1]), 1u);
    o.y = pack2(v[8 * i + 2], v[8 * i + 3]);
    o.z = pack2(v[8 * i + 4], v[8 * i + 5]);
    o.w = pack2(v[8 * i + 6], v[8 * i + 7]);
    st_ll(xr + i * 32, o);
  }
}

__device__ __forceinline__ uint4 pack8(const float* a) {
  return make_uint4(pack2(a[0], a[1]), pack2(a[2], a[3]), pack2(a[4], a[5]), pack2(a[6], a[7]));
}
template <int U> __device__ __forceinline__ uint4 glu8(const float* g, float cl, float ch) {
  return make_uint4(pack2(g[0] * cl * g[U], g[1] * cl * g[U + 1]), pack2(g[2] * ch * g[U + 2], g[3] * ch * g[U + 3]),
                    pack2(g[4] * cl * g[U + 4], g[5] * cl * g[U + 5]), pack2(g[6] * ch * g[U + 6], g[7] * ch * g[U + 7]));
}
__device__ __forceinline__ uint32_t hfma2(uint32_t a, uint32_t b, uint32_t c) {
  uint32_t d;
  asm("fma.rn.bf16x2 %0, %1, %2, %3;" : "=r"(d) : "r"(a), "r"(b), "r"(c));
  return d;
}
__device__ __forceinline__ void keep4(const uint4 (&a)[4]) { keep(a[0]); keep(a[1]); keep(a[2]); keep(a[3]); }

#define STAGGER 0

__global__ void __launch_bounds__(NTHREADS, 1)
fused_kernel(const __grid_constant__ CUtensorMap m_qkv, const __grid_constant__ CUtensorMap m_wo,
             const __grid_constant__ CUtensorMap m_gu2, const __grid_constant__ CUtensorMap m_gu1,
             const __grid_constant__ CUtensorMap m_guh, const __grid_constant__ CUtensorMap m_wd112,
             const __grid_constant__ CUtensorMap m_wd80, const __grid_constant__ CUtensorMap m_wd32,
             const __nv_bfloat16* __restrict__ x_in,
             __nv_bfloat16* __restrict__ out, const char* __restrict__ w_o, const char* __restrict__ w_g,
             const char* __restrict__ w_u, const char* __restrict__ w_d
) {
  extern __shared__ __align__(1024) unsigned char smem_raw[];
  const uint32_t sbase = smem_u32(smem_raw);
  const uint32_t bars = sbase + SM_MISC;
  if ((sbase & 0xFFFFFFu) != SMEM_ORIGIN) return;
  TG(60);

  uint32_t xw[16];
  if (threadIdx.x < 256) {
    const int cc = blockIdx.x >> 3, jj = blockIdx.x & 7, ln = threadIdx.x & 31;
    const uint32_t* xp = reinterpret_cast<const uint32_t*>(x_in + (size_t)(slab_row0(cc, jj >> 2, jj & 3) + 2 * (ln >> 2)) * 512 + (threadIdx.x >> 5) * 64 + (ln & 3) * 2);
#pragma unroll
    for (int i = 0; i < 4; i++) {
      xw[4 * i] = __ldg(xp + i * 8); xw[4 * i + 1] = __ldg(xp + 16 * 256 + i * 8);
      xw[4 * i + 2] = __ldg(xp + i * 8 + 4); xw[4 * i + 3] = __ldg(xp + 16 * 256 + i * 8 + 4);
    }
  } else if (threadIdx.x == 256) {
    for (int i = 0; i < NGRAN; i++) { mbar_init(bars + BAR_FULL + 8 * i, 1); mbar_init(bars + BAR_EMPTY + 8 * i, 8); }
    for (int i = 0; i < 4; i++) mbar_init(bars + BAR_HRECV + 8 * i, 1);
    for (int i = 0; i < 2; i++) mbar_init(bars + BAR_HREADY + 8 * i, 4);
    asm volatile("fence.mbarrier_init.release.cluster;" ::: "memory");
  }
  __syncthreads();
  asm volatile("barrier.cluster.arrive.release.aligned;" ::: "memory");

  if (threadIdx.x >= 256) {
    asm volatile("setmaxnreg.dec.sync.aligned.u32 40;");
    const int warp = threadIdx.x >> 5, lane = threadIdx.x & 31;
    const int j = blockIdx.x & 7, b = j & 1;
    if (warp == 8) {
      ProdRing r{0u, 0u};
      const int cb0 = 224 * j + 32 * b, hb0 = 224 * j + 192 * (b ^ 1);
      const int jp = j ^ 1, cbp = 224 * jp + 32 * (b ^ 1), hbp = 224 * jp + 192 * b;
#pragma unroll 1
      for (uint32_t L = 0; L < 2; L++) {
        r.pos = 0;
        PSTOP_AT(L == 0 ? 0 : 3);
#pragma unroll 1
        for (int kb = 0; kb < 8; kb++) {
          const uint32_t g0 = prod_acquire<3>(sbase, r);
          if (elect_one()) {
            mbar_expect_tx(bars + BAR_FULL + 8 * g0, 24576);
            tma_3d(sbase + g0 * GRAN, &m_qkv, bars + BAR_FULL + 8 * g0, 64 * j, 64 * kb, 0);
          }
        }
        PSTOP_AT(10 * L + 1);
#pragma unroll 1
        for (int i = 0; i < 4; i++) {
          const uint32_t g0 = prod_acquire<2>(sbase, r);
          if (elect_one()) {
            mbar_expect_tx(bars + BAR_FULL + 8 * g0, 16384);
            tma_2d(sbase + g0 * GRAN, &m_wo, bars + BAR_FULL + 8 * g0, 64 * j, 128 * i);
          }
        }
        PSTOP_AT(10 * L + 2);
#pragma unroll 1
        for (int kb = 0; kb < 8; kb++) {
          const uint32_t g0 = prod_acquire<4>(sbase, r);
          if (elect_one()) {
            mbar_expect_tx(bars + BAR_FULL + 8 * g0, 32768);
            tma_4d(sbase + g0 * GRAN, &m_gu2, bars + BAR_FULL + 8 * g0, cb0, 64 * kb, 0, 0);
          }
        }
#pragma unroll 1
        for (int kb = 0; kb < 8; kb++) {
          const uint32_t g0 = prod_acquire<3>(sbase, r);
          if (elect_one()) {
            mbar_expect_tx(bars + BAR_FULL + 8 * g0, 24576);
            tma_4d(sbase + g0 * GRAN, &m_gu1, bars + BAR_FULL + 8 * g0, cb0 + 128, 64 * kb, 0, 0);
            tma_3d(sbase + g0 * GRAN + 16384, &m_guh, bars + BAR_FULL + 8 * g0, hb0, 64 * kb, 0);
          }
        }
        static_for<0, 16>([&](auto I) {
          constexpr int i = I.value, g0 = st_g0(ST_DN + i);
          prod_acquire_static<ST_DN + i>(sbase, L);
          if (elect_one()) {
            const uint32_t dst = sbase + g0 * GRAN, fb = bars + BAR_FULL + 8 * g0;
            const int n0 = 256 * b + 64 * dn_q(i);
            mbar_expect_tx(fb, 14336);
            if constexpr (dn_kh(i) == 0) {
              tma_2d(dst, &m_wd112, fb, n0, dn_par(i) ? cbp : cb0);
            } else {
              tma_2d(dst, &m_wd80, fb, n0, (dn_par(i) ? cbp : cb0) + 112);
              tma_2d(dst + 10240, &m_wd32, fb, n0, dn_par(i) ? hbp : hb0);
            }
          }
        });
        r.par ^= flip_mask(ST_DN, NSTAGE);
      }
    } else if (warp == 9) {
      const int cta = blockIdx.x;
      if (lane == 0) l2_prefetch(w_o + cta * 4096, 4096);
      if (lane == 1) l2_prefetch(w_g + cta * 14336, 14336);
      if (lane == 2) l2_prefetch(w_u + cta * 14336, 14336);
      if (lane == 3) l2_prefetch(w_d + cta * 14336, 14336);
    }
    __syncwarp();
    asm volatile("barrier.cluster.wait.acquire.aligned; // producer" ::: "memory");
    asm volatile("barrier.cluster.arrive.release.aligned;\nbarrier.cluster.wait.acquire.aligned; // producer" ::: "memory");
  } else {
    asm volatile("setmaxnreg.inc.sync.aligned.u32 232;");
    TS(0);
    TG(61);

    {
      float v[32];
#pragma unroll
      for (int i = 0; i < 16; i++) { v[2 * i] = bf_lo(xw[i]); v[2 * i + 1] = bf_hi(xw[i]); }
      owner_ln_publish(sbase, v, 0u, 1u);
      asm volatile("barrier.cluster.wait.acquire.aligned; // consumer" ::: "memory");
    }
    STOP_AT(0);
    TS(1);

#pragma unroll 1
    for (uint32_t L = 0; L < 2; L++) {
      const uint32_t tag = L ^ 1;
      {
        PHASE_VARS;
        uint4 qf[4], kf[4], vf[4], pp[4];
        const int blk = 16 * g + c;
        const uint4* halo_src = g_halo + ((((L * 32 + (blk > 0 ? blk - 1 : 0)) * 8 + j) * 2 + (w & 1)) * 4) * 32 + lane;
        {
          float acc[96];
          uint4 A[3][4];
          const uint4* xs = g_xn + ((c * 8 + slab) * 32) * 32 + lane;
          bar_wg(1 + g);
          load_pk<4>(A[0], xs);
          ensure_pk<4>(A[0], xs, tag);
          TS(2 + 20 * L);
          load_pk<4>(A[1], xs + 128);
          static_for<0, 8>([&](auto I) {
            constexpr int kb = I.value;
            cons_acquire<kb>(sbase, L);
            wg_fence();
            static_for<0, 4>([&](auto K) { constexpr int k = K.value; wgmma_n192<kb == 0 && k == 0, 0>(acc, A[kb % 3][k], st_desc<kb, 2048, 8192, 1024, 1>(k)); });
            wg_commit();
            if constexpr (kb > 0) {
              wg_wait<1>();
              keep4(A[(kb + 2) % 3]);
              cons_release<kb - 1>(sbase, lane);
            }
            if constexpr (kb + 1 < 8) ensure_pk<4>(A[(kb + 1) % 3], xs + (kb + 1) * 128, tag);
            if constexpr (kb + 2 < 8) load_pk<4>(A[(kb + 2) % 3], xs + (kb + 2) * 128);
          });
          wg_wait<0>();
          TS(3 + 20 * L);
          fence_acc(acc);
          keep4(A[1]);
          cons_release<7>(sbase, lane);
#pragma unroll
          for (int h = 0; h < 4; h++) {
            kf[h] = pack8(&acc[32 + 8 * h]);
            const uint4 t = pack8(&acc[64 + 8 * h]);
            vf[h] = make_uint4(movm(t.x), movm(t.y), movm(t.z), movm(t.w));
            pp[h] = make_uint4(kf[h].y, kf[h].w, vf[h].y, vf[h].w);
          }
          if (w >= 2 && blk < 31) {
            uint4* hd = g_halo + ((((L * 32 + blk) * 8 + j) * 2 + (w & 1)) * 4) * 32 + lane;
#pragma unroll
            for (int h = 0; h < 4; h++) { uint4 t = pp[h]; t.x |= 1u; st_ll(hd + h * 32, t); }
          }
#pragma unroll
          for (int h = 0; h < 4; h++) sts128(areg + (28 + h) * 2048 + t128 * 16, pp[h]);
          if (w < 2 && blk > 0) load_pk<4>(pp, halo_src);
#pragma unroll
          for (int h = 0; h < 4; h++) qf[h] = pack8(&acc[8 * h]);
        }
        bar_wg(1 + g);
        const bool first = (w < 2) && (blk == 0);
        if (w >= 2) {
#pragma unroll
          for (int h = 0; h < 4; h++) pp[h] = lds128(areg + (28 + h) * 2048 + (t128 - 64) * 16);
        }
        bar_wg(1 + g);
        if (w < 2 && blk > 0) {
          ensure_pk<4>(pp, halo_src, 1u);
          uint4* hz = const_cast<uint4*>(halo_src);
#pragma unroll
          for (int h = 0; h < 4; h++) st_ll(hz + h * 32, make_uint4(0, 0, 0, 0));
        }
        TS(4 + 20 * L);
        const bool n0 = 2 * qc <= qr, n1 = 2 * qc + 1 <= qr;
        const uint32_t msk = (n0 ? 0xffffu : 0u) | (n1 ? 0xffff0000u : 0u);
        const float sc = 0.25f * 1.4426950408889634f;
        const float NEG = -1e30f;
        uint4* od = g_o + ((c * 8 + slab) * 32 + 4 * j) * 32 + lane;
        float l0[4], l1[4], h0[4], h1[4], ml[4], mh[4];
#pragma unroll
        for (int h = 0; h < 4; h++) {
          float sp[4], s0[4], s1[4];
          mma16816_z(sp, qf[h], pp[h].x, pp[h].y);
          mma16816_z(s0, qf[h], kf[h].x, kf[h].z);
          mma16816_z(s1, qf[h], kf[h].y, kf[h].w);
          if (first) { sp[0] = NEG; sp[1] = NEG; }
          l0[h] = n0 ? s0[0] : sp[0]; l1[h] = n1 ? s0[1] : sp[1];
          h0[h] = n0 ? s1[2] : s0[2]; h1[h] = n1 ? s1[3] : s0[3];
          ml[h] = fmaxf(l0[h], l1[h]); mh[h] = fmaxf(h0[h], h1[h]);
        }
#pragma unroll
        for (int h = 0; h < 4; h++) { ml[h] = fmaxf(ml[h], __shfl_xor_sync(0xffffffffu, ml[h], 1)); mh[h] = fmaxf(mh[h], __shfl_xor_sync(0xffffffffu, mh[h], 1)); }
#pragma unroll
        for (int h = 0; h < 4; h++) { ml[h] = fmaxf(ml[h], __shfl_xor_sync(0xffffffffu, ml[h], 2)); mh[h] = fmaxf(mh[h], __shfl_xor_sync(0xffffffffu, mh[h], 2)); }
        float sl[4], sh[4];
#pragma unroll
        for (int h = 0; h < 4; h++) {
          const float bl = -ml[h] * sc, bh = -mh[h] * sc;
          l0[h] = ex2(fmaf(l0[h], sc, bl)); l1[h] = ex2(fmaf(l1[h], sc, bl));
          h0[h] = ex2(fmaf(h0[h], sc, bh)); h1[h] = ex2(fmaf(h1[h], sc, bh));
          sl[h] = l0[h] + l1[h]; sh[h] = h0[h] + h1[h];
        }
#pragma unroll
        for (int h = 0; h < 4; h++) { sl[h] += __shfl_xor_sync(0xffffffffu, sl[h], 1); sh[h] += __shfl_xor_sync(0xffffffffu, sh[h], 1); }
#pragma unroll
        for (int h = 0; h < 4; h++) { sl[h] += __shfl_xor_sync(0xffffffffu, sl[h], 2); sh[h] += __shfl_xor_sync(0xffffffffu, sh[h], 2); }
#pragma unroll
        for (int h = 0; h < 4; h++) {
          const float il = rcp(sl[h]), ih = rcp(sh[h]);
          const uint32_t pl = pack2(l0[h] * il, l1[h] * il), ph = pack2(h0[h] * ih, h1[h] * ih);
          const uint4 P = make_uint4(pl & msk, ph & ~msk, 0u, ph & msk);
          float o0[4], o1[4];
          mma16816_z(o0, P, vf[h].x, vf[h].y);
          mma16816_z(o1, P, vf[h].z, vf[h].w);
          mma1688(o0, pl & ~msk, 0u, pp[h].z);
          mma1688(o1, pl & ~msk, 0u, pp[h].w);
          st_ll(od + h * 32, make_uint4(set_tag(pack2(o0[0], o0[1]), tag), pack2(o0[2], o0[3]), pack2(o1[0], o1[1]), pack2(o1[2], o1[3])));
        }
      }
      TS(5 + 20 * L);
      if (L == 0) { STOP_AT(1); } else { STOP_AT(11); }
      {
        PHASE_VARS;
        float acc[32];
        uint4 A[32], xr[4];
        const uint4* os = g_o + ((c * 8 + slab) * 32) * 32 + lane;
        uint4* xp = g_xraw + ((c * 8 + slab) * 32 + 4 * j) * 32 + lane;
        load_pk<4>(xr, xp);
        load_pk<4>(A, os);
        ensure_pk<4>(A, os, tag);
        TS(6 + 20 * L);
        load_pk<28>(A + 4, os + 128);
        static_for<0, 8>([&](auto I) {
          constexpr int kb = I.value;
          if constexpr ((kb & 1) == 0) cons_acquire<ST_WO + kb / 2>(sbase, L);
          if constexpr (kb > 0) ensure_pk<4>(A + 4 * kb, os + kb * 128, tag);
          wg_fence();
          static_for<0, 4>([&](auto K) {
            constexpr int k = K.value;
            wgmma_n64<kb == 0 && k == 0, 0>(acc, A[4 * kb + k], st_desc<ST_WO + kb / 2, 2048, 8192, 1024, 1>(4 * (kb & 1) + k));
          });
          wg_commit();
          if constexpr ((kb & 1) == 0 && kb > 0) { wg_wait<1>(); cons_release<ST_WO + kb / 2 - 1>(sbase, lane); }
        });
        wg_wait<0>();
        TS(7 + 20 * L);
        fence_acc(acc);
#pragma unroll
        for (int k = 0; k < 32; k++) keep(A[k]);
        cons_release<ST_WO + 3>(sbase, lane);
        ensure_pk<4>(xr, xp, 1u);
#pragma unroll
        for (int i = 0; i < 4; i++) {
          acc[8 * i + 0] += bf_lo(xr[i].x); acc[8 * i + 1] += bf_hi(xr[i].x); acc[8 * i + 2] += bf_lo(xr[i].y); acc[8 * i + 3] += bf_hi(xr[i].y);
          acc[8 * i + 4] += bf_lo(xr[i].z); acc[8 * i + 5] += bf_hi(xr[i].z); acc[8 * i + 6] += bf_lo(xr[i].w); acc[8 * i + 7] += bf_hi(xr[i].w);
          uint4 o = pack8(&acc[8 * i]);
          o.x = set_tag(o.x, 0u);
          st_ll(xp + i * 32, o);
        }
        uint4 st = local_stats(acc);
        st.x = set_tag(st.x, tag);
        if (qc == 0) st_ll(g_stats + ((c * 8 + slab) * 8 + j) * 8 + qr, st);
      }
      TS(8 + 20 * L);
      if (L == 0) { STOP_AT(2); } else { STOP_AT(12); }
      uint4 hs[14];
      {
        PHASE_VARS;
        float acc[128];
        uint4 A[3][4];
        const uint4* xs = g_xraw + ((c * 8 + slab) * 32) * 32 + lane;
        const uint4* sp = g_stats + ((c * 8 + slab) * 8 + 2 * qc) * 8 + qr;
        const uint32_t sm = areg + t128 * 16;
        uint32_t rl2, rh2, bl2, bh2;
        float cl, ch;
        {
          uint4 p[2];
          load_pk<4>(A[0], xs);
          p[0] = ld_ll(sp); p[1] = ld_ll(sp + 8);
          for (uint32_t n = 0; !ok_pk<2>(p, tag) && n < SPIN_LIMIT; n++) { load_pk<4>(A[0], xs); p[0] = ld_ll(sp); p[1] = ld_ll(sp + 8); }
          TS(9 + 20 * L);
          load_pk<4>(A[1], xs + 128);
          float ml, rl, mh, rh;
          combine_stats(p[0], p[1], ml, rl, mh, rh);
          rl2 = pack2(rl, rl); rh2 = pack2(rh, rh);
          const float rlb = bf_lo(rl2), rhb = bf_lo(rh2);
          bl2 = pack2(-ml * rlb, -ml * rlb); bh2 = pack2(-mh * rhb, -mh * rhb);
          cl = rl / rlb; cl *= cl; ch = rh / rhb; ch *= ch;
        }
        auto normalise = [&](uint4 (&xb)[4], int kb) {
#pragma unroll
          for (int k = 0; k < 4; k++) {
            xb[k].x = hfma2(xb[k].x, rl2, bl2); xb[k].y = hfma2(xb[k].y, rh2, bh2);
            xb[k].z = hfma2(xb[k].z, rl2, bl2); xb[k].w = hfma2(xb[k].w, rh2, bh2);
            sts128(sm + (kb * 4 + k) * 2048, xb[k]);
          }
        };
        ensure_pk<4>(A[0], xs, 0u);
        normalise(A[0], 0);
        static_for<0, 8>([&](auto I) {
          constexpr int kb = I.value;
          cons_acquire<ST_G1 + kb>(sbase, L);
          wg_fence();
          static_for<0, 4>([&](auto K) { constexpr int k = K.value; wgmma_n256<kb == 0 && k == 0, 0>(acc, A[kb % 3][k], st_desc<ST_G1 + kb, 2048, 8192, 1024, 1>(k)); });
          wg_commit();
          if constexpr (kb > 0) {
            wg_wait<1>();
            keep4(A[(kb + 2) % 3]);
            cons_release<ST_G1 + kb - 1>(sbase, lane);
          }
          if constexpr (kb + 1 < 8) ensure_pk<4>(A[(kb + 1) % 3], xs + (kb + 1) * 128, 0u);
          if constexpr (kb + 2 < 8) load_pk<4>(A[(kb + 2) % 3], xs + (kb + 2) * 128);
          if constexpr (kb + 1 < 8) normalise(A[(kb + 1) % 3], kb + 1);
        });
        wg_wait<0>();
        TS(10 + 20 * L);
        fence_acc(acc);
        keep4(A[1]);
        cons_release<ST_G1 + 7>(sbase, lane);
        uint4 B[2][4];
#pragma unroll
        for (int k = 0; k < 4; k++) B[0][k] = lds128(sm + k * 2048);
#pragma unroll
        for (int s = 0; s < 8; s++) hs[s] = glu8<32>(&acc[64 * (s >> 2) + 8 * (s & 3)], cl, ch);
        float acc2[96];
        const uint32_t hdst = mapa(sm, cbit ^ 1);
        const uint32_t hbar1 = mapa(bars + BAR_HRECV + 16 * g, cbit ^ 1);
        if (t128 == 0) { mbar_expect_tx(bars + BAR_HRECV + 16 * g, 8 * 2048); mbar_expect_tx(bars + BAR_HRECV + 16 * g + 8, 6 * 2048); }
        static_for<0, 8>([&](auto I) {
          constexpr int kb = I.value;
          cons_acquire<ST_G2 + kb>(sbase, L);
          wg_fence();
          static_for<0, 4>([&](auto K) {
            constexpr int k = K.value;
            wgmma_n128<kb == 0 && k == 0, 0>(acc2, B[kb & 1][k], st_desc<ST_G2 + kb, 2048, 8192, 1024, 1>(k));
            wgmma_n64<kb == 0 && k == 0, 64>(acc2, B[kb & 1][k], st_desc<ST_G2 + kb, 1024, 4096, 512, 2>(k) + (16384 >> 4));
          });
          wg_commit();
          if constexpr (kb > 0) {
            wg_wait<1>();
            keep4(B[(kb + 1) & 1]);
            cons_release<ST_G2 + kb - 1>(sbase, lane);
          }
          if constexpr (kb + 1 < 8) {
#pragma unroll
            for (int k = 0; k < 4; k++) B[(kb + 1) & 1][k] = lds128(sm + ((kb + 1) * 4 + k) * 2048);
          }
          if constexpr (kb == 3) {
            __syncwarp();
            if (lane == 0) mbar_arrive_remote(mapa(bars + BAR_HREADY + 8 * g, cbit ^ 1));
          }
          if constexpr (kb >= 4) {
            if constexpr (kb == 4) mbar_wait(bars + BAR_HREADY + 8 * g, L);
            st_async128(hdst + (2 * kb - 8) * 2048, hs[2 * kb - 8], hbar1);
            st_async128(hdst + (2 * kb - 7) * 2048, hs[2 * kb - 7], hbar1);
          }
        });
        wg_wait<0>();
        TS(11 + 20 * L);
        fence_acc(acc2);
        keep4(B[1]);
        cons_release<ST_G2 + 7>(sbase, lane);
#pragma unroll
        for (int s = 0; s < 4; s++) hs[8 + s] = glu8<32>(&acc2[8 * s], cl, ch);
#pragma unroll
        for (int s = 0; s < 2; s++) hs[12 + s] = glu8<16>(&acc2[64 + 8 * s], cl, ch);
      }
      {
        PHASE_VARS;
        TS(12 + 20 * L);
        const uint32_t hdst = mapa(areg + t128 * 16, cbit ^ 1);
        const uint32_t hbar2 = mapa(bars + BAR_HRECV + 16 * g + 8, cbit ^ 1);
        uint4* pd = g_part + ((((c * 8 + slab) * 2 + cbit) * 4 + ca) * 16) * 32 + lane;
        uint4 hb[7];
        float a0[32], a1[32], a2[32], a3[32];
        auto publish = [&](float (&a)[32], int q, int s0, int s1) {
#pragma unroll
          for (int s = s0; s < s1; s++) {
            uint4 o = pack8(&a[8 * s]);
            o.x = set_tag(o.x, tag);
            st_ll(pd + (4 * q + s) * 32, o);
          }
        };
        static_for<0, 16>([&](auto I) {
          constexpr int i = I.value, q = dn_q(i), par = dn_par(i), kh = dn_kh(i);
          auto mm = [&](auto K) {
            constexpr int k = decltype(K)::value;
            constexpr bool init = (k == 0 && par == 0 && kh == 0);
            constexpr uint64_t db = st_desc<ST_DN + i, 2048, 8192, 1024, 1>(k);
            if constexpr (q == 0) { if constexpr (par) wgmma_n64<init, 0>(a0, hb[k], db); else wgmma_n64<init, 0>(a0, hs[7 * kh + k], db); }
            if constexpr (q == 1) { if constexpr (par) wgmma_n64<init, 0>(a1, hb[k], db); else wgmma_n64<init, 0>(a1, hs[7 * kh + k], db); }
            if constexpr (q == 2) { if constexpr (par) wgmma_n64<init, 0>(a2, hb[k], db); else wgmma_n64<init, 0>(a2, hs[7 * kh + k], db); }
            if constexpr (q == 3) { if constexpr (par) wgmma_n64<init, 0>(a3, hb[k], db); else wgmma_n64<init, 0>(a3, hs[7 * kh + k], db); }
          };
          cons_acquire<ST_DN + i>(sbase, L);
          wg_fence();
          mm(IC<0>{}); mm(IC<1>{}); mm(IC<2>{}); mm(IC<3>{}); mm(IC<4>{}); mm(IC<5>{}); mm(IC<6>{});
          wg_commit();
          if constexpr (i > 0) { wg_wait<1>(); cons_release<ST_DN + i - 1>(sbase, lane); }
          if constexpr (i < 3) {
            st_async128(hdst + (8 + 2 * i) * 2048, hs[8 + 2 * i], hbar2);
            st_async128(hdst + (9 + 2 * i) * 2048, hs[9 + 2 * i], hbar2);
          }
          constexpr int n = i + 1;
          if constexpr (n < 16 && dn_par(n) && n != 4 && n != 7) {
            if constexpr (n == 2) { mbar_wait(bars + BAR_HRECV + 16 * g, L); TS(13 + 20 * L); }
            if constexpr (n == 6) { mbar_wait(bars + BAR_HRECV + 16 * g + 8, L); TS(14 + 20 * L); }
#pragma unroll
            for (int k = 0; k < 7; k++) { if constexpr (n != 2) keep(hb[k]); hb[k] = lds128(areg + t128 * 16 + (7 * dn_kh(n) + k) * 2048); }
          }
          if constexpr (i == 7) { fence_acc(a0); publish(a0, 0, 0, 4); }
          if constexpr (i == 8) { fence_acc(a1); publish(a1, 1, 0, 2); }
          if constexpr (i == 9) publish(a1, 1, 2, 4);
          if constexpr (i == 12) { fence_acc(a2); publish(a2, 2, 0, 2); }
          if constexpr (i == 13) publish(a2, 2, 2, 4);
        });
        wg_wait<0>();
        TS(15 + 20 * L);
        fence_acc(a3);
#pragma unroll
        for (int k = 0; k < 7; k++) { keep(hb[k]); keep(hs[7 + k]); }
        cons_release<NSTAGE - 1>(sbase, lane);
        publish(a3, 3, 0, 4);
      }
      {
        PHASE_VARS;
        const uint4* xq = g_xraw + ((c * 8 + j) * 32 + 4 * warp) * 32 + lane;
        const uint4* ps = g_part + ((((c * 8 + j) * 2 + g) * 4) * 16 + 4 * w) * 32 + lane;
        uint4 xr[4], P[4][4];
        float v[32];
        load_pk<4>(xr, xq);
#pragma unroll
        for (int src = 0; src < 4; src++) load_pk<4>(P[src], ps + src * (16 * 32));
#pragma unroll
        for (int src = 0; src < 4; src++) ensure_pk<4>(P[src], ps + src * (16 * 32), tag);
        TS(16 + 20 * L);
        ensure_pk<4>(xr, xq, 0u);
#pragma unroll
        for (int i = 0; i < 4; i++) {
          v[8 * i + 0] = bf_lo(xr[i].x); v[8 * i + 1] = bf_hi(xr[i].x); v[8 * i + 2] = bf_lo(xr[i].y); v[8 * i + 3] = bf_hi(xr[i].y);
          v[8 * i + 4] = bf_lo(xr[i].z); v[8 * i + 5] = bf_hi(xr[i].z); v[8 * i + 6] = bf_lo(xr[i].w); v[8 * i + 7] = bf_hi(xr[i].w);
          float d[8] = {0, 0, 0, 0, 0, 0, 0, 0};
#pragma unroll
          for (int src = 0; src < 4; src++) {
            const uint4 p = P[src][i];
            d[0] += bf_lo(p.x); d[1] += bf_hi(p.x); d[2] += bf_lo(p.y); d[3] += bf_hi(p.y);
            d[4] += bf_lo(p.z); d[5] += bf_hi(p.z); d[6] += bf_lo(p.w); d[7] += bf_hi(p.w);
          }
#pragma unroll
          for (int k = 0; k < 8; k++) v[8 * i + k] += d[k];
        }
        if (L == 0) {
          owner_ln_publish(sbase, v, 1u, 0u);
        } else {
          uint32_t* op = reinterpret_cast<uint32_t*>(out + (size_t)(slab_row0(c, j >> 2, j & 3) + 2 * qr) * 512 + warp * 64 + qc * 2);
#pragma unroll
          for (int i = 0; i < 4; i++) {
            op[i * 8] = pack2(v[8 * i], v[8 * i + 1]);
            op[16 * 256 + i * 8] = pack2(v[8 * i + 2], v[8 * i + 3]);
            op[i * 8 + 4] = pack2(v[8 * i + 4], v[8 * i + 5]);
            op[16 * 256 + i * 8 + 4] = pack2(v[8 * i + 6], v[8 * i + 7]);
          }
        }
      }
      TS(17 + 20 * L);
      if (L == 0) { STOP_AT(3); }
    }
    TG(62);
    asm volatile("barrier.cluster.arrive.release.aligned;\nbarrier.cluster.wait.acquire.aligned; // consumer" ::: "memory");
    TG(63);
  }
}

typedef CUresult (*EncodeFn)(CUtensorMap*, CUtensorMapDataType, cuuint32_t, void*, const cuuint64_t*, const cuuint64_t*,
                             const cuuint32_t*, const cuuint32_t*, CUtensorMapInterleave, CUtensorMapSwizzle,
                             CUtensorMapL2promotion, CUtensorMapFloatOOBfill);

void encode(EncodeFn fn, CUtensorMap* m, int rank, const void* base, const cuuint64_t* dims, const cuuint64_t* strides,
            const cuuint32_t* box, CUtensorMapSwizzle sw) {
  cuuint32_t es[5] = {1, 1, 1, 1, 1};
  fn(m, CU_TENSOR_MAP_DATA_TYPE_BFLOAT16, (cuuint32_t)rank, const_cast<void*>(base), dims, strides, box, es,
     CU_TENSOR_MAP_INTERLEAVE_NONE, sw, CU_TENSOR_MAP_L2_PROMOTION_L2_128B, CU_TENSOR_MAP_FLOAT_OOB_FILL_NONE);
}

}

extern "C" void kernel_launch(void* const* d_in, const int* in_sizes, int n_in, void* d_out, int out_size) {
  (void)in_sizes; (void)n_in; (void)out_size;
  const __nv_bfloat16* x = (const __nv_bfloat16*)d_in[0];
  const char* wqkv = (const char*)d_in[1];
  const char* wo = (const char*)d_in[2];
  const char* wg = (const char*)d_in[4];
  const char* wu = (const char*)d_in[5];
  const char* wd = (const char*)d_in[6];

  static EncodeFn fn = nullptr;
  if (!fn) {
    void* p = nullptr;
    cudaDriverEntryPointQueryResult st;
    cudaGetDriverEntryPoint("cuTensorMapEncodeTiled", &p, cudaEnableDefault, &st);
    fn = (EncodeFn)p;
    cudaFuncSetAttribute(fused_kernel, cudaFuncAttributeMaxDynamicSharedMemorySize, SMEM_BYTES);
  }
  CUtensorMap m_qkv, m_wo, m_gu2, m_gu1, m_guh, m_wd112, m_wd80, m_wd32;
  {
    cuuint64_t dims[3] = {512, 512, 3}, str[2] = {3072, 1024};
    cuuint32_t box[3] = {64, 64, 3};
    encode(fn, &m_qkv, 3, wqkv, dims, str, box, CU_TENSOR_MAP_SWIZZLE_128B);
  }
  {
    cuuint64_t dims[2] = {512, 512}, str[1] = {1024};
    cuuint32_t box[2] = {64, 128};
    encode(fn, &m_wo, 2, wo, dims, str, box, CU_TENSOR_MAP_SWIZZLE_128B);
  }
  {
    const char* lo = wg < wu ? wg : wu;
    cuuint64_t diff = (cuuint64_t)(wg < wu ? wu - wg : wg - wu);
    cuuint64_t dims[4] = {1792, 512, 2, 2}, str[3] = {3584, diff, 128};
    cuuint32_t box2[4] = {64, 64, 2, 2}, box1[4] = {64, 64, 2, 1}, boxh[3] = {32, 64, 2};
    encode(fn, &m_gu2, 4, lo, dims, str, box2, CU_TENSOR_MAP_SWIZZLE_128B);
    encode(fn, &m_gu1, 4, lo, dims, str, box1, CU_TENSOR_MAP_SWIZZLE_128B);
    encode(fn, &m_guh, 3, lo, dims, str, boxh, CU_TENSOR_MAP_SWIZZLE_64B);
  }
  {
    cuuint64_t dims[2] = {512, 1792}, str[1] = {1024};
    cuuint32_t b112[2] = {64, 112}, b80[2] = {64, 80}, b32[2] = {64, 32};
    encode(fn, &m_wd112, 2, wd, dims, str, b112, CU_TENSOR_MAP_SWIZZLE_128B);
    encode(fn, &m_wd80, 2, wd, dims, str, b80, CU_TENSOR_MAP_SWIZZLE_128B);
    encode(fn, &m_wd32, 2, wd, dims, str, b32, CU_TENSOR_MAP_SWIZZLE_128B);
  }
  cudaLaunchConfig_t cfg = {};
  cfg.gridDim = dim3(128);
  cfg.blockDim = dim3(NTHREADS);
  cfg.dynamicSmemBytes = SMEM_BYTES;
  cfg.stream = cudaStreamPerThread;
  cudaLaunchAttribute at[1];
  at[0].id = cudaLaunchAttributeClusterDimension;
  at[0].val.clusterDim.x = 2; at[0].val.clusterDim.y = 1; at[0].val.clusterDim.z = 1;
  cfg.attrs = at; cfg.numAttrs = 1;
  cudaLaunchKernelEx(&cfg, fused_kernel, m_qkv, m_wo, m_gu2, m_gu1, m_guh, m_wd112, m_wd80, m_wd32, x, (__nv_bfloat16*)d_out, wo, wg, wu, wd
  );
}
```

```cpp
#include <cuda_runtime.h>
#include <cuda_bf16.h>
#include <cuda.h>
#include <stdint.h>

namespace {

constexpr int NTHREADS = 384;
constexpr int GRAN = 8192;
constexpr int NGRAN = 12;
constexpr int SM_AREG = NGRAN * GRAN;
constexpr int SM_MISC = SM_AREG + 131072;
constexpr int SM_TSTAT = SM_MISC + 256;
constexpr int SMEM_BYTES = SM_TSTAT + 1024;
constexpr int BAR_FULL = 0, BAR_EMPTY = 96, BAR_HRECV = 192, BAR_HREADY = 224;

__device__ uint4 g_xn[16 * 8 * 32 * 32];
__device__ uint4 g_xraw[16 * 8 * 32 * 32];
__device__ uint4 g_o[16 * 8 * 32 * 32];
__device__ uint4 g_stats[16 * 8 * 8 * 8];
__device__ uint4 g_halo[2 * 32 * 8 * 8 * 32];
__device__ uint4 g_part[16 * 8 * 2 * 4 * 16 * 32];

#define TS(n)
#define TG(n)
#define OPAQUE(x) asm volatile("" : "+r"(x))
#define PHASE_VARS                                                                                   \
  int tid_ = threadIdx.x, bid_ = blockIdx.x;                                                         \
  OPAQUE(tid_); OPAQUE(bid_);                                                                        \
  const int lane = tid_ & 31, warp = tid_ >> 5, g = warp >> 2, w = warp & 3, t128 = tid_ & 127;      \
  const int qr = lane >> 2, qc = lane & 3, slab = warp;                                              \
  const int c = bid_ >> 3, j = bid_ & 7, ca = j >> 1, cbit = j & 1;                                  \
  const uint32_t areg = sbase + SM_AREG + g * 65536;                                                 \
  (void)g; (void)j; (void)w; (void)t128; (void)qr; (void)qc; (void)slab; (void)c; (void)ca; (void)cbit; (void)areg; (void)lane
#define STOP_AT(n)
#define PSTOP_AT(n)

__device__ __forceinline__ uint32_t smem_u32(const void* p) { return (uint32_t)__cvta_generic_to_shared(p); }
__device__ __forceinline__ void mbar_init(uint32_t bar, uint32_t cnt) {
  asm volatile("mbarrier.init.shared::cta.b64 [%0], %1;" ::"r"(bar), "r"(cnt) : "memory");
}
__device__ __forceinline__ void mbar_expect_tx(uint32_t bar, uint32_t bytes) {
  asm volatile("mbarrier.arrive.expect_tx.shared::cta.b64 _, [%0], %1;" ::"r"(bar), "r"(bytes) : "memory");
}
__device__ __forceinline__ void mbar_arrive(uint32_t bar) {
  asm volatile("mbarrier.arrive.shared::cta.b64 _, [%0];" ::"r"(bar) : "memory");
}
__device__ __forceinline__ void mbar_arrive_remote(uint32_t cluster_addr) {
  asm volatile("mbarrier.arrive.relaxed.cluster.shared::cluster.b64 _, [%0];" ::"r"(cluster_addr) : "memory");
}
__device__ __forceinline__ bool mbar_try(uint32_t bar, uint32_t parity) {
  uint32_t ok;
  asm volatile("{\n.reg .pred p;\nmbarrier.try_wait.parity.shared::cta.b64 p, [%1], %2;\nselp.u32 %0, 1, 0, p;\n}"
               : "=r"(ok) : "r"(bar), "r"(parity) : "memory");
  return ok != 0;
}
constexpr uint32_t SPIN_LIMIT = 1u << 16;
constexpr uint32_t SMEM_ORIGIN = 1024;
__device__ __forceinline__ void mbar_wait(uint32_t bar, uint32_t parity) {
  for (uint32_t n = 0; !mbar_try(bar, parity) && n < SPIN_LIMIT; n++) {}
}
__device__ __forceinline__ uint32_t mapa(uint32_t addr, uint32_t rank) {
  uint32_t r;
  asm volatile("mapa.shared::cluster.u32 %0, %1, %2;" : "=r"(r) : "r"(addr), "r"(rank));
  return r;
}

__device__ __forceinline__ void tma_2d(uint32_t dst, const CUtensorMap* m, uint32_t bar, int c0, int c1) {
  asm volatile("cp.async.bulk.tensor.2d.shared::cluster.global.mbarrier::complete_tx::bytes [%0], [%1, {%3, %4}], [%2];"
               ::"r"(dst), "l"(m), "r"(bar), "r"(c0), "r"(c1) : "memory");
}
__device__ __forceinline__ void tma_3d(uint32_t dst, const CUtensorMap* m, uint32_t bar, int c0, int c1, int c2) {
  asm volatile("cp.async.bulk.tensor.3d.shared::cluster.global.mbarrier::complete_tx::bytes [%0], [%1, {%3, %4, %5}], [%2];"
               ::"r"(dst), "l"(m), "r"(bar), "r"(c0), "r"(c1), "r"(c2) : "memory");
}
__device__ __forceinline__ void tma_4d(uint32_t dst, const CUtensorMap* m, uint32_t bar, int c0, int c1, int c2, int c3) {
  asm volatile("cp.async.bulk.tensor.4d.shared::cluster.global.mbarrier::complete_tx::bytes [%0], [%1, {%3, %4, %5, %6}], [%2];"
               ::"r"(dst), "l"(m), "r"(bar), "r"(c0), "r"(c1), "r"(c2), "r"(c3) : "memory");
}
__device__ __forceinline__ void l2_prefetch(const void* p, uint32_t bytes) {
  asm volatile("cp.async.bulk.prefetch.L2.global [%0], %1;" ::"l"(p), "r"(bytes) : "memory");
}

__device__ __forceinline__ uint4 ld_ll(const uint4* p) {
  uint4 v;
  asm volatile("ld.relaxed.gpu.global.v4.u32 {%0,%1,%2,%3}, [%4];" : "=r"(v.x), "=r"(v.y), "=r"(v.z), "=r"(v.w) : "l"(p) : "memory");
  return v;
}
__device__ __forceinline__ void st_ll(uint4* p, uint4 v) {
  asm volatile("st.relaxed.gpu.global.v4.u32 [%0], {%1,%2,%3,%4};" ::"l"(p), "r"(v.x), "r"(v.y), "r"(v.z), "r"(v.w) : "memory");
}
__device__ __forceinline__ uint4 lds128(uint32_t a) {
  uint4 v;
  asm volatile("ld.shared.v4.u32 {%0,%1,%2,%3}, [%4];" : "=r"(v.x), "=r"(v.y), "=r"(v.z), "=r"(v.w) : "r"(a) : "memory");
  return v;
}
__device__ __forceinline__ void sts128(uint32_t a, uint4 v) {
  asm volatile("st.shared.v4.u32 [%0], {%1,%2,%3,%4};" ::"r"(a), "r"(v.x), "r"(v.y), "r"(v.z), "r"(v.w) : "memory");
}
__device__ __forceinline__ void st_async128(uint32_t cluster_addr, uint4 v, uint32_t cluster_bar) {
  asm volatile("st.async.weak.shared::cluster.mbarrier::complete_tx::bytes.v4.b32 [%0], {%1,%2,%3,%4}, [%5];"
               ::"r"(cluster_addr), "r"(v.x), "r"(v.y), "r"(v.z), "r"(v.w), "r"(cluster_bar) : "memory");
}
__device__ __forceinline__ uint32_t pack2(float lo, float hi) {
  uint32_t r;
  asm("cvt.rn.bf16x2.f32 %0, %1, %2;" : "=r"(r) : "f"(hi), "f"(lo));
  return r;
}
__device__ __forceinline__ float bf_lo(uint32_t w) { return __uint_as_float(w << 16); }
__device__ __forceinline__ float bf_hi(uint32_t w) { return __uint_as_float(w & 0xffff0000u); }
__device__ __forceinline__ uint32_t set_tag(uint32_t w, uint32_t tag) { return (w & ~1u) | tag; }
__device__ __forceinline__ uint32_t movm(uint32_t a) {
  uint32_t d;
  asm("movmatrix.sync.aligned.m8n8.trans.b16 %0, %1;" : "=r"(d) : "r"(a));
  return d;
}
__device__ __forceinline__ void mma16816(float (&d)[4], const uint4& a, uint32_t b0, uint32_t b1) {
  asm("mma.sync.aligned.m16n8k16.row.col.f32.bf16.bf16.f32 {%0,%1,%2,%3}, {%4,%5,%6,%7}, {%8,%9}, {%0,%1,%2,%3};"
               : "+f"(d[0]), "+f"(d[1]), "+f"(d[2]), "+f"(d[3])
               : "r"(a.x), "r"(a.y), "r"(a.z), "r"(a.w), "r"(b0), "r"(b1));
}
__device__ __forceinline__ void mma1688(float (&d)[4], uint32_t a0, uint32_t a1, uint32_t b0) {
  asm("mma.sync.aligned.m16n8k8.row.col.f32.bf16.bf16.f32 {%0,%1,%2,%3}, {%4,%5}, {%6}, {%0,%1,%2,%3};"
      : "+f"(d[0]), "+f"(d[1]), "+f"(d[2]), "+f"(d[3])
      : "r"(a0), "r"(a1), "r"(b0));
}
__device__ __forceinline__ void mma16816_z(float (&d)[4], const uint4& a, uint32_t b0, uint32_t b1) {
  asm("mma.sync.aligned.m16n8k16.row.col.f32.bf16.bf16.f32 {%0,%1,%2,%3}, {%4,%5,%6,%7}, {%8,%9}, {%10,%10,%10,%10};"
      : "=f"(d[0]), "=f"(d[1]), "=f"(d[2]), "=f"(d[3])
      : "r"(a.x), "r"(a.y), "r"(a.z), "r"(a.w), "r"(b0), "r"(b1), "f"(0.f));
}
__device__ __forceinline__ float ex2(float x) {
  float y;
  asm("ex2.approx.ftz.f32 %0, %1;" : "=f"(y) : "f"(x));
  return y;
}
__device__ __forceinline__ float rcp(float x) {
  float y;
  asm("rcp.approx.ftz.f32 %0, %1;" : "=f"(y) : "f"(x));
  return y;
}
__device__ __forceinline__ void cp_async16(uint32_t dst, const void* src) {
  asm volatile("cp.async.cg.shared.global [%0], [%1], 16;" ::"r"(dst), "l"(src) : "memory");
}
__device__ __forceinline__ void cp_commit() { asm volatile("cp.async.commit_group;" ::: "memory"); }
template <int N> __device__ __forceinline__ void cp_wait() { asm volatile("cp.async.wait_group %0;" ::"n"(N) : "memory"); }
__device__ __forceinline__ void bar_wg(int id) { asm volatile("bar.sync %0, 128;" ::"r"(id) : "memory"); }
__device__ __forceinline__ void wg_fence() { asm volatile("wgmma.fence.sync.aligned;" ::: "memory"); }
__device__ __forceinline__ void wg_commit() { asm volatile("wgmma.commit_group.sync.aligned;" ::: "memory"); }
template <int N> __device__ __forceinline__ void wg_wait() { asm volatile("wgmma.wait_group.sync.aligned %0;" ::"n"(N) : "memory"); }
__device__ __forceinline__ void keep(const uint4& a) { asm volatile("" ::"r"(a.x), "r"(a.y), "r"(a.z), "r"(a.w) : "memory"); }
template <int T> __device__ __forceinline__ void zero_acc(float (&d)[T]) {
#pragma unroll
  for (int i = 0; i < T; i++) d[i] = 0.f;
}
template <int T> __device__ __forceinline__ void fence_acc(float (&d)[T]) {
#pragma unroll
  for (int i = 0; i < T; i++) asm volatile("" : "+f"(d[i])::"memory");
}

template <int O, int T> __device__ __forceinline__ void wgmma_rs_n64(float (&d)[T], const uint4& a, uint64_t db) {
  asm volatile("{\n.reg .pred p;\nsetp.ne.b32 p, 1, 0;\n"
    "wgmma.mma_async.sync.aligned.m64n64k16.f32.bf16.bf16 "
    "{%0, %1, %2, %3, %4, %5, %6, %7, %8, %9, %10, %11, %12, %13, %14, %15, "
    "%16, %17, %18, %19, %20, %21, %22, %23, %24, %25, %26, %27, %28, %29, %30, %31}, "
    "{%32, %33, %34, %35}, %36, p, 1, 1, 1;\n}\n"
    : "+f"(d[O + 0]), "+f"(d[O + 1]), "+f"(d[O + 2]), "+f"(d[O + 3]), "+f"(d[O + 4]), "+f"(d[O + 5]), "+f"(d[O + 6]), "+f"(d[O + 7]),
      "+f"(d[O + 8]), "+f"(d[O + 9]), "+f"(d[O + 10]), "+f"(d[O + 11]), "+f"(d[O + 12]), "+f"(d[O + 13]), "+f"(d[O + 14]), "+f"(d[O + 15]),
      "+f"(d[O + 16]), "+f"(d[O + 17]), "+f"(d[O + 18]), "+f"(d[O + 19]), "+f"(d[O + 20]), "+f"(d[O + 21]), "+f"(d[O + 22]), "+f"(d[O + 23]),
      "+f"(d[O + 24]), "+f"(d[O + 25]), "+f"(d[O + 26]), "+f"(d[O + 27]), "+f"(d[O + 28]), "+f"(d[O + 29]), "+f"(d[O + 30]), "+f"(d[O + 31])
    : "r"(a.x), "r"(a.y), "r"(a.z), "r"(a.w), "l"(db));
}
template <int O, int T> __device__ __forceinline__ void wgmma_rs_n64_init(float (&d)[T], const uint4& a, uint64_t db) {
  asm volatile("{\n.reg .pred p;\nsetp.ne.b32 p, 0, 0;\n"
    "wgmma.mma_async.sync.aligned.m64n64k16.f32.bf16.bf16 "
    "{%0, %1, %2, %3, %4, %5, %6, %7, %8, %9, %10, %11, %12, %13, %14, %15, "
    "%16, %17, %18, %19, %20, %21, %22, %23, %24, %25, %26, %27, %28, %29, %30, %31}, "
    "{%32, %33, %34, %35}, %36, p, 1, 1, 1;\n}\n"
    : "=f"(d[O + 0]), "=f"(d[O + 1]), "=f"(d[O + 2]), "=f"(d[O + 3]), "=f"(d[O + 4]), "=f"(d[O + 5]), "=f"(d[O + 6]), "=f"(d[O + 7]),
      "=f"(d[O + 8]), "=f"(d[O + 9]), "=f"(d[O + 10]), "=f"(d[O + 11]), "=f"(d[O + 12]), "=f"(d[O + 13]), "=f"(d[O + 14]), "=f"(d[O + 15]),
      "=f"(d[O + 16]), "=f"(d[O + 17]), "=f"(d[O + 18]), "=f"(d[O + 19]), "=f"(d[O + 20]), "=f"(d[O + 21]), "=f"(d[O + 22]), "=f"(d[O + 23]),
      "=f"(d[O + 24]), "=f"(d[O + 25]), "=f"(d[O + 26]), "=f"(d[O + 27]), "=f"(d[O + 28]), "=f"(d[O + 29]), "=f"(d[O + 30]), "=f"(d[O + 31])
    : "r"(a.x), "r"(a.y), "r"(a.z), "r"(a.w), "l"(db));
}
template <bool INIT, int O, int T> __device__ __forceinline__ void wgmma_n64(float (&d)[T], const uint4& a, uint64_t db) {
  if constexpr (INIT) wgmma_rs_n64_init<O>(d, a, db); else wgmma_rs_n64<O>(d, a, db);
}
template <int O, int T> __device__ __forceinline__ void wgmma_rs_n128(float (&d)[T], const uint4& a, uint64_t db) {
  asm volatile("{\n.reg .pred p;\nsetp.ne.b32 p, 1, 0;\n"
    "wgmma.mma_async.sync.aligned.m64n128k16.f32.bf16.bf16 "
    "{%0, %1, %2, %3, %4, %5, %6, %7, %8, %9, %10, %11, %12, %13, %14, %15, "
    "%16, %17, %18, %19, %20, %21, %22, %23, %24, %25, %26, %27, %28, %29, %30, %31, "
    "%32, %33, %34, %35, %36, %37, %38, %39, %40, %41, %42, %43, %44, %45, %46, %47, "
    "%48, %49, %50, %51, %52, %53, %54, %55, %56, %57, %58, %59, %60, %61, %62, %63}, "
    "{%64, %65, %66, %67}, %68, p, 1, 1, 1;\n}\n"
    : "+f"(d[O + 0]), "+f"(d[O + 1]), "+f"(d[O + 2]), "+f"(d[O + 3]), "+f"(d[O + 4]), "+f"(d[O + 5]), "+f"(d[O + 6]), "+f"(d[O + 7]),
      "+f"(d[O + 8]), "+f"(d[O + 9]), "+f"(d[O + 10]), "+f"(d[O + 11]), "+f"(d[O + 12]), "+f"(d[O + 13]), "+f"(d[O + 14]), "+f"(d[O + 15]),
      "+f"(d[O + 16]), "+f"(d[O + 17]), "+f"(d[O + 18]), "+f"(d[O + 19]), "+f"(d[O + 20]), "+f"(d[O + 21]), "+f"(d[O + 22]), "+f"(d[O + 23]),
      "+f"(d[O + 24]), "+f"(d[O + 25]), "+f"(d[O + 26]), "+f"(d[O + 27]), "+f"(d[O + 28]), "+f"(d[O + 29]), "+f"(d[O + 30]), "+f"(d[O + 31]),
      "+f"(d[O + 32]), "+f"(d[O + 33]), "+f"(d[O + 34]), "+f"(d[O + 35]), "+f"(d[O + 36]), "+f"(d[O + 37]), "+f"(d[O + 38]), "+f"(d[O + 39]),
      "+f"(d[O + 40]), "+f"(d[O + 41]), "+f"(d[O + 42]), "+f"(d[O + 43]), "+f"(d[O + 44]), "+f"(d[O + 45]), "+f"(d[O + 46]), "+f"(d[O + 47]),
      "+f"(d[O + 48]), "+f"(d[O + 49]), "+f"(d[O + 50]), "+f"(d[O + 51]), "+f"(d[O + 52]), "+f"(d[O + 53]), "+f"(d[O + 54]), "+f"(d[O + 55]),
      "+f"(d[O + 56]), "+f"(d[O + 57]), "+f"(d[O + 58]), "+f"(d[O + 59]), "+f"(d[O + 60]), "+f"(d[O + 61]), "+f"(d[O + 62]), "+f"(d[O + 63])
    : "r"(a.x), "r"(a.y), "r"(a.z), "r"(a.w), "l"(db));
}
template <int O, int T> __device__ __forceinline__ void wgmma_rs_n128_init(float (&d)[T], const uint4& a, uint64_t db) {
  asm volatile("{\n.reg .pred p;\nsetp.ne.b32 p, 0, 0;\n"
    "wgmma.mma_async.sync.aligned.m64n128k16.f32.bf16.bf16 "
    "{%0, %1, %2, %3, %4, %5, %6, %7, %8, %9, %10, %11, %12, %13, %14, %15, "
    "%16, %17, %18, %19, %20, %21, %22, %23, %24, %25, %26, %27, %28, %29, %30, %31, "
    "%32, %33, %34, %35, %36, %37, %38, %39, %40, %41, %42, %43, %44, %45, %46, %47, "
    "%48, %49, %50, %51, %52, %53, %54, %55, %56, %57, %58, %59, %60, %61, %62, %63}, "
    "{%64, %65, %66, %67}, %68, p, 1, 1, 1;\n}\n"
    : "=f"(d[O + 0]), "=f"(d[O + 1]), "=f"(d[O + 2]), "=f"(d[O + 3]), "=f"(d[O + 4]), "=f"(d[O + 5]), "=f"(d[O + 6]), "=f"(d[O + 7]),
      "=f"(d[O + 8]), "=f"(d[O + 9]), "=f"(d[O + 10]), "=f"(d[O + 11]), "=f"(d[O + 12]), "=f"(d[O + 13]), "=f"(d[O + 14]), "=f"(d[O + 15]),
      "=f"(d[O + 16]), "=f"(d[O + 17]), "=f"(d[O + 18]), "=f"(d[O + 19]), "=f"(d[O + 20]), "=f"(d[O + 21]), "=f"(d[O + 22]), "=f"(d[O + 23]),
      "=f"(d[O + 24]), "=f"(d[O + 25]), "=f"(d[O + 26]), "=f"(d[O + 27]), "=f"(d[O + 28]), "=f"(d[O + 29]), "=f"(d[O + 30]), "=f"(d[O + 31]),
      "=f"(d[O + 32]), "=f"(d[O + 33]), "=f"(d[O + 34]), "=f"(d[O + 35]), "=f"(d[O + 36]), "=f"(d[O + 37]), "=f"(d[O + 38]), "=f"(d[O + 39]),
      "=f"(d[O + 40]), "=f"(d[O + 41]), "=f"(d[O + 42]), "=f"(d[O + 43]), "=f"(d[O + 44]), "=f"(d[O + 45]), "=f"(d[O + 46]), "=f"(d[O + 47]),
      "=f"(d[O + 48]), "=f"(d[O + 49]), "=f"(d[O + 50]), "=f"(d[O + 51]), "=f"(d[O + 52]), "=f"(d[O + 53]), "=f"(d[O + 54]), "=f"(d[O + 55]),
      "=f"(d[O + 56]), "=f"(d[O + 57]), "=f"(d[O + 58]), "=f"(d[O + 59]), "=f"(d[O + 60]), "=f"(d[O + 61]), "=f"(d[O + 62]), "=f"(d[O + 63])
    : "r"(a.x), "r"(a.y), "r"(a.z), "r"(a.w), "l"(db));
}
template <bool INIT, int O, int T> __device__ __forceinline__ void wgmma_n128(float (&d)[T], const uint4& a, uint64_t db) {
  if constexpr (INIT) wgmma_rs_n128_init<O>(d, a, db); else wgmma_rs_n128<O>(d, a, db);
}
template <int O, int T> __device__ __forceinline__ void wgmma_rs_n192(float (&d)[T], const uint4& a, uint64_t db) {
  asm volatile("{\n.reg .pred p;\nsetp.ne.b32 p, 1, 0;\n"
    "wgmma.mma_async.sync.aligned.m64n192k16.f32.bf16.bf16 "
    "{%0, %1, %2, %3, %4, %5, %6, %7, %8, %9, %10, %11, %12, %13, %14, %15, "
    "%16, %17, %18, %19, %20, %21, %22, %23, %24, %25, %26, %27, %28, %29, %30, %31, "
    "%32, %33, %34, %35, %36, %37, %38, %39, %40, %41, %42, %43, %44, %45, %46, %47, "
    "%48, %49, %50, %51, %52, %53, %54, %55, %56, %57, %58, %59, %60, %61, %62, %63, "
    "%64, %65, %66, %67, %68, %69, %70, %71, %72, %73, %74, %75, %76, %77, %78, %79, "
    "%80, %81, %82, %83, %84, %85, %86, %87, %88, %89, %90, %91, %92, %93, %94, %95}, "
    "{%96, %97, %98, %99}, %100, p, 1, 1, 1;\n}\n"
    : "+f"(d[O + 0]), "+f"(d[O + 1]), "+f"(d[O + 2]), "+f"(d[O + 3]), "+f"(d[O + 4]), "+f"(d[O + 5]), "+f"(d[O + 6]), "+f"(d[O + 7]),
      "+f"(d[O + 8]), "+f"(d[O + 9]), "+f"(d[O + 10]), "+f"(d[O + 11]), "+f"(d[O + 12]), "+f"(d[O + 13]), "+f"(d[O + 14]), "+f"(d[O + 15]),
      "+f"(d[O + 16]), "+f"(d[O + 17]), "+f"(d[O + 18]), "+f"(d[O + 19]), "+f"(d[O + 20]), "+f"(d[O + 21]), "+f"(d[O + 22]), "+f"(d[O + 23]),
      "+f"(d[O + 24]), "+f"(d[O + 25]), "+f"(d[O + 26]), "+f"(d[O + 27]), "+f"(d[O + 28]), "+f"(d[O + 29]), "+f"(d[O + 30]), "+f"(d[O + 31]),
      "+f"(d[O + 32]), "+f"(d[O + 33]), "+f"(d[O + 34]), "+f"(d[O + 35]), "+f"(d[O + 36]), "+f"(d[O + 37]), "+f"(d[O + 38]), "+f"(d[O + 39]),
      "+f"(d[O + 40]), "+f"(d[O + 41]), "+f"(d[O + 42]), "+f"(d[O + 43]), "+f"(d[O + 44]), "+f"(d[O + 45]), "+f"(d[O + 46]), "+f"(d[O + 47]),
      "+f"(d[O + 48]), "+f"(d[O + 49]), "+f"(d[O + 50]), "+f"(d[O + 51]), "+f"(d[O + 52]), "+f"(d[O + 53]), "+f"(d[O + 54]), "+f"(d[O + 55]),
      "+f"(d[O + 56]), "+f"(d[O + 57]), "+f"(d[O + 58]), "+f"(d[O + 59]), "+f"(d[O + 60]), "+f"(d[O + 61]), "+f"(d[O + 62]), "+f"(d[O + 63]),
      "+f"(d[O + 64]), "+f"(d[O + 65]), "+f"(d[O + 66]), "+f"(d[O + 67]), "+f"(d[O + 68]), "+f"(d[O + 69]), "+f"(d[O + 70]), "+f"(d[O + 71]),
      "+f"(d[O + 72]), "+f"(d[O + 73]), "+f"(d[O + 74]), "+f"(d[O + 75]), "+f"(d[O + 76]), "+f"(d[O + 77]), "+f"(d[O + 78]), "+f"(d[O + 79]),
      "+f"(d[O + 80]), "+f"(d[O + 81]), "+f"(d[O + 82]), "+f"(d[O + 83]), "+f"(d[O + 84]), "+f"(d[O + 85]), "+f"(d[O + 86]), "+f"(d[O + 87]),
      "+f"(d[O + 88]), "+f"(d[O + 89]), "+f"(d[O + 90]), "+f"(d[O + 91]), "+f"(d[O + 92]), "+f"(d[O + 93]), "+f"(d[O + 94]), "+f"(d[O + 95])
    : "r"(a.x), "r"(a.y), "r"(a.z), "r"(a.w), "l"(db));
}
template <int O, int T> __device__ __forceinline__ void wgmma_rs_n192_init(float (&d)[T], const uint4& a, uint64_t db) {
  asm volatile("{\n.reg .pred p;\nsetp.ne.b32 p, 0, 0;\n"
    "wgmma.mma_async.sync.aligned.m64n192k16.f32.bf16.bf16 "
    "{%0, %1, %2, %3, %4, %5, %6, %7, %8, %9, %10, %11, %12, %13, %14, %15, "
    "%16, %17, %18, %19, %20, %21, %22, %23, %24, %25, %26, %27, %28, %29, %30, %31, "
    "%32, %33, %34, %35, %36, %37, %38, %39, %40, %41, %42, %43, %44, %45, %46, %47, "
    "%48, %49, %50, %51, %52, %53, %54, %55, %56, %57, %58, %59, %60, %61, %62, %63, "
    "%64, %65, %66, %67, %68, %69, %70, %71, %72, %73, %74, %75, %76, %77, %78, %79, "
    "%80, %81, %82, %83, %84, %85, %86, %87, %88, %89, %90, %91, %92, %93, %94, %95}, "
    "{%96, %97, %98, %99}, %100, p, 1, 1, 1;\n}\n"
    : "=f"(d[O + 0]), "=f"(d[O + 1]), "=f"(d[O + 2]), "=f"(d[O + 3]), "=f"(d[O + 4]), "=f"(d[O + 5]), "=f"(d[O + 6]), "=f"(d[O + 7]),
      "=f"(d[O + 8]), "=f"(d[O + 9]), "=f"(d[O + 10]), "=f"(d[O + 11]), "=f"(d[O + 12]), "=f"(d[O + 13]), "=f"(d[O + 14]), "=f"(d[O + 15]),
      "=f"(d[O + 16]), "=f"(d[O + 17]), "=f"(d[O + 18]), "=f"(d[O + 19]), "=f"(d[O + 20]), "=f"(d[O + 21]), "=f"(d[O + 22]), "=f"(d[O + 23]),
      "=f"(d[O + 24]), "=f"(d[O + 25]), "=f"(d[O + 26]), "=f"(d[O + 27]), "=f"(d[O + 28]), "=f"(d[O + 29]), "=f"(d[O + 30]), "=f"(d[O + 31]),
      "=f"(d[O + 32]), "=f"(d[O + 33]), "=f"(d[O + 34]), "=f"(d[O + 35]), "=f"(d[O + 36]), "=f"(d[O + 37]), "=f"(d[O + 38]), "=f"(d[O + 39]),
      "=f"(d[O + 40]), "=f"(d[O + 41]), "=f"(d[O + 42]), "=f"(d[O + 43]), "=f"(d[O + 44]), "=f"(d[O + 45]), "=f"(d[O + 46]), "=f"(d[O + 47]),
      "=f"(d[O + 48]), "=f"(d[O + 49]), "=f"(d[O + 50]), "=f"(d[O + 51]), "=f"(d[O + 52]), "=f"(d[O + 53]), "=f"(d[O + 54]), "=f"(d[O + 55]),
      "=f"(d[O + 56]), "=f"(d[O + 57]), "=f"(d[O + 58]), "=f"(d[O + 59]), "=f"(d[O + 60]), "=f"(d[O + 61]), "=f"(d[O + 62]), "=f"(d[O + 63]),
      "=f"(d[O + 64]), "=f"(d[O + 65]), "=f"(d[O + 66]), "=f"(d[O + 67]), "=f"(d[O + 68]), "=f"(d[O + 69]), "=f"(d[O + 70]), "=f"(d[O + 71]),
      "=f"(d[O + 72]), "=f"(d[O + 73]), "=f"(d[O + 74]), "=f"(d[O + 75]), "=f"(d[O + 76]), "=f"(d[O + 77]), "=f"(d[O + 78]), "=f"(d[O + 79]),
      "=f"(d[O + 80]), "=f"(d[O + 81]), "=f"(d[O + 82]), "=f"(d[O + 83]), "=f"(d[O + 84]), "=f"(d[O + 85]), "=f"(d[O + 86]), "=f"(d[O + 87]),
      "=f"(d[O + 88]), "=f"(d[O + 89]), "=f"(d[O + 90]), "=f"(d[O + 91]), "=f"(d[O + 92]), "=f"(d[O + 93]), "=f"(d[O + 94]), "=f"(d[O + 95])
    : "r"(a.x), "r"(a.y), "r"(a.z), "r"(a.w), "l"(db));
}
template <bool INIT, int O, int T> __device__ __forceinline__ void wgmma_n192(float (&d)[T], const uint4& a, uint64_t db) {
  if constexpr (INIT) wgmma_rs_n192_init<O>(d, a, db); else wgmma_rs_n192<O>(d, a, db);
}
template <int O, int T> __device__ __forceinline__ void wgmma_rs_n256(float (&d)[T], const uint4& a, uint64_t db) {
  asm volatile("{\n.reg .pred p;\nsetp.ne.b32 p, 1, 0;\n"
    "wgmma.mma_async.sync.aligned.m64n256k16.f32.bf16.bf16 "
    "{%0, %1, %2, %3, %4, %5, %6, %7, %8, %9, %10, %11, %12, %13, %14, %15, "
    "%16, %17, %18, %19, %20, %21, %22, %23, %24, %25, %26, %27, %28, %29, %30, %31, "
    "%32, %33, %34, %35, %36, %37, %38, %39, %40, %41, %42, %43, %44, %45, %46, %47, "
    "%48, %49, %50, %51, %52, %53, %54, %55, %56, %57, %58, %59, %60, %61, %62, %63, "
    "%64, %65, %66, %67, %68, %69, %70, %71, %72, %73, %74, %75, %76, %77, %78, %79, "
    "%80, %81, %82, %83, %84, %85, %86, %87, %88, %89, %90, %91, %92, %93, %94, %95, "
    "%96, %97, %98, %99, %100, %101, %102, %103, %104, %105, %106, %107, %108, %109, %110, %111, "
    "%112, %113, %114, %115, %116, %117, %118, %119, %120, %121, %122, %123, %124, %125, %126, %127}, "
    "{%128, %129, %130, %131}, %132, p, 1, 1, 1;\n}\n"
    : "+f"(d[O + 0]), "+f"(d[O + 1]), "+f"(d[O + 2]), "+f"(d[O + 3]), "+f"(d[O + 4]), "+f"(d[O + 5]), "+f"(d[O + 6]), "+f"(d[O + 7]),
      "+f"(d[O + 8]), "+f"(d[O + 9]), "+f"(d[O + 10]), "+f"(d[O + 11]), "+f"(d[O + 12]), "+f"(d[O + 13]), "+f"(d[O + 14]), "+f"(d[O + 15]),
      "+f"(d[O + 16]), "+f"(d[O + 17]), "+f"(d[O + 18]), "+f"(d[O + 19]), "+f"(d[O + 20]), "+f"(d[O + 21]), "+f"(d[O + 22]), "+f"(d[O + 23]),
      "+f"(d[O + 24]), "+f"(d[O + 25]), "+f"(d[O + 26]), "+f"(d[O + 27]), "+f"(d[O + 28]), "+f"(d[O + 29]), "+f"(d[O + 30]), "+f"(d[O + 31]),
      "+f"(d[O + 32]), "+f"(d[O + 33]), "+f"(d[O + 34]), "+f"(d[O + 35]), "+f"(d[O + 36]), "+f"(d[O + 37]), "+f"(d[O + 38]), "+f"(d[O + 39]),
      "+f"(d[O + 40]), "+f"(d[O + 41]), "+f"(d[O + 42]), "+f"(d[O + 43]), "+f"(d[O + 44]), "+f"(d[O + 45]), "+f"(d[O + 46]), "+f"(d[O + 47]),
      "+f"(d[O + 48]), "+f"(d[O + 49]), "+f"(d[O + 50]), "+f"(d[O + 51]), "+f"(d[O + 52]), "+f"(d[O + 53]), "+f"(d[O + 54]), "+f"(d[O + 55]),
      "+f"(d[O + 56]), "+f"(d[O + 57]), "+f"(d[O + 58]), "+f"(d[O + 59]), "+f"(d[O + 60]), "+f"(d[O + 61]), "+f"(d[O + 62]), "+f"(d[O + 63]),
      "+f"(d[O + 64]), "+f"(d[O + 65]), "+f"(d[O + 66]), "+f"(d[O + 67]), "+f"(d[O + 68]), "+f"(d[O + 69]), "+f"(d[O + 70]), "+f"(d[O + 71]),
      "+f"(d[O + 72]), "+f"(d[O + 73]), "+f"(d[O + 74]), "+f"(d[O + 75]), "+f"(d[O + 76]), "+f"(d[O + 77]), "+f"(d[O + 78]), "+f"(d[O + 79]),
      "+f"(d[O + 80]), "+f"(d[O + 81]), "+f"(d[O + 82]), "+f"(d[O + 83]), "+f"(d[O + 84]), "+f"(d[O + 85]), "+f"(d[O + 86]), "+f"(d[O + 87]),
      "+f"(d[O + 88]), "+f"(d[O + 89]), "+f"(d[O + 90]), "+f"(d[O + 91]), "+f"(d[O + 92]), "+f"(d[O + 93]), "+f"(d[O + 94]), "+f"(d[O + 95]),
      "+f"(d[O + 96]), "+f"(d[O + 97]), "+f"(d[O + 98]), "+f"(d[O + 99]), "+f"(d[O + 100]), "+f"(d[O + 101]), "+f"(d[O + 102]), "+f"(d[O + 103]),
      "+f"(d[O + 104]), "+f"(d[O + 105]), "+f"(d[O + 106]), "+f"(d[O + 107]), "+f"(d[O + 108]), "+f"(d[O + 109]), "+f"(d[O + 110]), "+f"(d[O + 111]),
      "+f"(d[O + 112]), "+f"(d[O + 113]), "+f"(d[O + 114]), "+f"(d[O + 115]), "+f"(d[O + 116]), "+f"(d[O + 117]), "+f"(d[O + 118]), "+f"(d[O + 119]),
      "+f"(d[O + 120]), "+f"(d[O + 121]), "+f"(d[O + 122]), "+f"(d[O + 123]), "+f"(d[O + 124]), "+f"(d[O + 125]), "+f"(d[O + 126]), "+f"(d[O + 127])
    : "r"(a.x), "r"(a.y), "r"(a.z), "r"(a.w), "l"(db));
}
template <int O, int T> __device__ __forceinline__ void wgmma_rs_n256_init(float (&d)[T], const uint4& a, uint64_t db) {
  asm volatile("{\n.reg .pred p;\nsetp.ne.b32 p, 0, 0;\n"
    "wgmma.mma_async.sync.aligned.m64n256k16.f32.bf16.bf16 "
    "{%0, %1, %2, %3, %4, %5, %6, %7, %8, %9, %10, %11, %12, %13, %14, %15, "
    "%16, %17, %18, %19, %20, %21, %22, %23, %24, %25, %26, %27, %28, %29, %30, %31, "
    "%32, %33, %34, %35, %36, %37, %38, %39, %40, %41, %42, %43, %44, %45, %46, %47, "
    "%48, %49, %50, %51, %52, %53, %54, %55, %56, %57, %58, %59, %60, %61, %62, %63, "
    "%64, %65, %66, %67, %68, %69, %70, %71, %72, %73, %74, %75, %76, %77, %78, %79, "
    "%80, %81, %82, %83, %84, %85, %86, %87, %88, %89, %90, %91, %92, %93, %94, %95, "
    "%96, %97, %98, %99, %100, %101, %102, %103, %104, %105, %106, %107, %108, %109, %110, %111, "
    "%112, %113, %114, %115, %116, %117, %118, %119, %120, %121, %122, %123, %124, %125, %126, %127}, "
    "{%128, %129, %130, %131}, %132, p, 1, 1, 1;\n}\n"
    : "=f"(d[O + 0]), "=f"(d[O + 1]), "=f"(d[O + 2]), "=f"(d[O + 3]), "=f"(d[O + 4]), "=f"(d[O + 5]), "=f"(d[O + 6]), "=f"(d[O + 7]),
      "=f"(d[O + 8]), "=f"(d[O + 9]), "=f"(d[O + 10]), "=f"(d[O + 11]), "=f"(d[O + 12]), "=f"(d[O + 13]), "=f"(d[O + 14]), "=f"(d[O + 15]),
      "=f"(d[O + 16]), "=f"(d[O + 17]), "=f"(d[O + 18]), "=f"(d[O + 19]), "=f"(d[O + 20]), "=f"(d[O + 21]), "=f"(d[O + 22]), "=f"(d[O + 23]),
      "=f"(d[O + 24]), "=f"(d[O + 25]), "=f"(d[O + 26]), "=f"(d[O + 27]), "=f"(d[O + 28]), "=f"(d[O + 29]), "=f"(d[O + 30]), "=f"(d[O + 31]),
      "=f"(d[O + 32]), "=f"(d[O + 33]), "=f"(d[O + 34]), "=f"(d[O + 35]), "=f"(d[O + 36]), "=f"(d[O + 37]), "=f"(d[O + 38]), "=f"(d[O + 39]),
      "=f"(d[O + 40]), "=f"(d[O + 41]), "=f"(d[O + 42]), "=f"(d[O + 43]), "=f"(d[O + 44]), "=f"(d[O + 45]), "=f"(d[O + 46]), "=f"(d[O + 47]),
      "=f"(d[O + 48]), "=f"(d[O + 49]), "=f"(d[O + 50]), "=f"(d[O + 51]), "=f"(d[O + 52]), "=f"(d[O + 53]), "=f"(d[O + 54]), "=f"(d[O + 55]),
      "=f"(d[O + 56]), "=f"(d[O + 57]), "=f"(d[O + 58]), "=f"(d[O + 59]), "=f"(d[O + 60]), "=f"(d[O + 61]), "=f"(d[O + 62]), "=f"(d[O + 63]),
      "=f"(d[O + 64]), "=f"(d[O + 65]), "=f"(d[O + 66]), "=f"(d[O + 67]), "=f"(d[O + 68]), "=f"(d[O + 69]), "=f"(d[O + 70]), "=f"(d[O + 71]),
      "=f"(d[O + 72]), "=f"(d[O + 73]), "=f"(d[O + 74]), "=f"(d[O + 75]), "=f"(d[O + 76]), "=f"(d[O + 77]), "=f"(d[O + 78]), "=f"(d[O + 79]),
      "=f"(d[O + 80]), "=f"(d[O + 81]), "=f"(d[O + 82]), "=f"(d[O + 83]), "=f"(d[O + 84]), "=f"(d[O + 85]), "=f"(d[O + 86]), "=f"(d[O + 87]),
      "=f"(d[O + 88]), "=f"(d[O + 89]), "=f"(d[O + 90]), "=f"(d[O + 91]), "=f"(d[O + 92]), "=f"(d[O + 93]), "=f"(d[O + 94]), "=f"(d[O + 95]),
      "=f"(d[O + 96]), "=f"(d[O + 97]), "=f"(d[O + 98]), "=f"(d[O + 99]), "=f"(d[O + 100]), "=f"(d[O + 101]), "=f"(d[O + 102]), "=f"(d[O + 103]),
      "=f"(d[O + 104]), "=f"(d[O + 105]), "=f"(d[O + 106]), "=f"(d[O + 107]), "=f"(d[O + 108]), "=f"(d[O + 109]), "=f"(d[O + 110]), "=f"(d[O + 111]),
      "=f"(d[O + 112]), "=f"(d[O + 113]), "=f"(d[O + 114]), "=f"(d[O + 115]), "=f"(d[O + 116]), "=f"(d[O + 117]), "=f"(d[O + 118]), "=f"(d[O + 119]),
      "=f"(d[O + 120]), "=f"(d[O + 121]), "=f"(d[O + 122]), "=f"(d[O + 123]), "=f"(d[O + 124]), "=f"(d[O + 125]), "=f"(d[O + 126]), "=f"(d[O + 127])
    : "r"(a.x), "r"(a.y), "r"(a.z), "r"(a.w), "l"(db));
}
template <bool INIT, int O, int T> __device__ __forceinline__ void wgmma_n256(float (&d)[T], const uint4& a, uint64_t db) {
  if constexpr (INIT) wgmma_rs_n256_init<O>(d, a, db); else wgmma_rs_n256<O>(d, a, db);
}

template <int N> __device__ __forceinline__ void load_pk(uint4* a, const uint4* p) {
#pragma unroll
  for (int i = 0; i < N; i++) a[i] = ld_ll(p + i * 32);
}
__device__ __forceinline__ uint32_t xor_or(uint32_t a, uint32_t b, uint32_t t) {
  uint32_t r;
  asm("lop3.b32 %0, %1, %2, %3, 0x7E;" : "=r"(r) : "r"(a), "r"(b), "r"(t));
  return r;
}
template <int N> __device__ __forceinline__ bool ok_pk(const uint4* a, uint32_t tag) {
  static_assert(N % 2 == 0, "");
  uint32_t x = xor_or(a[0].x, a[1].x, tag);
#pragma unroll
  for (int i = 2; i < N; i += 2) x |= xor_or(a[i].x, a[i + 1].x, tag);
  return __all_sync(0xffffffffu, (x & 1u) == 0u);
}
template <int N> __device__ __forceinline__ void ensure_pk(uint4* a, const uint4* p, uint32_t tag) {
  if (ok_pk<N>(a, tag)) return;
  uint32_t n = 0;
  do { load_pk<N>(a, p); } while (!ok_pk<N>(a, tag) && ++n < SPIN_LIMIT);
}

constexpr int NSTAGE = 44;
constexpr int ST_WO = 8, ST_G1 = 12, ST_G2 = 20, ST_DN = 28;
__host__ __device__ constexpr int st_len(int s) { return s < ST_WO ? 3 : s < ST_G1 ? 2 : s < ST_G2 ? 4 : s < ST_DN ? 3 : 2; }
__host__ __device__ constexpr int st_g0(int s) {
  int pos = 0, g0 = 0;
  for (int i = 0; i <= s; i++) {
    if (pos + st_len(i) > NGRAN) pos = 0;
    g0 = pos;
    pos += st_len(i);
  }
  return g0;
}
__host__ __device__ constexpr int cnt_first(int g, int s) {
  int n = 0;
  for (int i = 0; i < s; i++) n += (st_g0(i) == g);
  return n;
}
__host__ __device__ constexpr int cnt_cover(int g, int s) {
  int n = 0;
  for (int i = 0; i < s; i++) n += (g >= st_g0(i) && g < st_g0(i) + st_len(i));
  return n;
}
__host__ __device__ constexpr uint32_t flip_mask(int s0, int s1) {
  uint32_t m = 0;
  for (int i = s0; i < s1; i++) m ^= ((1u << st_len(i)) - 1u) << st_g0(i);
  return m;
}
__host__ __device__ constexpr int dn_q(int i) { return i < 3 ? 0 : i < 6 ? 1 : i == 6 ? 0 : i == 7 ? 1 : i < 12 ? 2 : 3; }
__host__ __device__ constexpr int dn_par(int i) { return i < 8 ? (i == 2 || i == 4 || i >= 6) : (i & 1); }
__host__ __device__ constexpr int dn_kh(int i) { return i < 8 ? (i == 1 || i >= 5) : ((i & 3) >= 2); }
template <int I> struct IC { static constexpr int value = I; };
template <int B, int E, typename F> __device__ __forceinline__ void static_for(F&& f) {
  if constexpr (B < E) { f(IC<B>{}); static_for<B + 1, E>(f); }
}
template <int S> __device__ __forceinline__ void cons_acquire(uint32_t sbase, uint32_t L) {
  constexpr int g0 = st_g0(S);
  constexpr uint32_t p0 = cnt_first(g0, S) & 1, odd = cnt_first(g0, NSTAGE) & 1;
  mbar_wait(sbase + SM_MISC + BAR_FULL + 8 * g0, p0 ^ (L & odd));
}
template <int S> __device__ __forceinline__ void cons_release(uint32_t sbase, int lane) {
  if (lane < st_len(S)) mbar_arrive(sbase + SM_MISC + BAR_EMPTY + 8 * st_g0(S) + 8 * lane);
}
__device__ __forceinline__ bool elect_one() {
  uint32_t p;
  asm volatile("{\n.reg .pred P;\nelect.sync _|P, 0xffffffff;\nselp.u32 %0, 1, 0, P;\n}" : "=r"(p));
  return p != 0;
}
struct ProdRing { uint32_t pos, par; };
template <int N> __device__ __forceinline__ uint32_t prod_acquire(uint32_t sbase, ProdRing& r) {
  if (r.pos + N > NGRAN) r.pos = 0;
  const uint32_t g0 = r.pos;
#pragma unroll
  for (uint32_t i = 0; i < N; i++) mbar_wait(sbase + SM_MISC + BAR_EMPTY + 8 * (g0 + i), ((r.par >> (g0 + i)) & 1u) ^ 1u);
  r.par ^= ((1u << N) - 1u) << g0;
  r.pos = g0 + N;
  return g0;
}
template <int S> __device__ __forceinline__ void prod_acquire_static(uint32_t sbase, uint32_t L) {
  constexpr int g0 = st_g0(S);
  static_for<0, st_len(S)>([&](auto I) {
    constexpr int g = g0 + I.value;
    constexpr uint32_t p0 = cnt_cover(g, S) & 1, odd = cnt_cover(g, NSTAGE) & 1;
    mbar_wait(sbase + SM_MISC + BAR_EMPTY + 8 * g, p0 ^ (L & odd) ^ 1u);
  });
}
template <int S, int KSTEP_BYTES, int LBO, int SBO, int SWZ> __device__ __forceinline__ constexpr uint64_t st_desc(int k) {
  return (uint64_t)((SMEM_ORIGIN + st_g0(S) * GRAN + k * KSTEP_BYTES) >> 4) | ((uint64_t)(LBO >> 4) << 16) |
         ((uint64_t)(SBO >> 4) << 32) | ((uint64_t)SWZ << 62);
}

__device__ __forceinline__ void combine_stats(const uint4& p0, const uint4& p1, float& mean_lo, float& rstd_lo, float& mean_hi, float& rstd_hi) {
  float m0 = __uint_as_float(p0.x), q0 = __uint_as_float(p0.y), m0h = __uint_as_float(p0.z), q0h = __uint_as_float(p0.w);
  float m1 = __uint_as_float(p1.x), q1 = __uint_as_float(p1.y), m1h = __uint_as_float(p1.z), q1h = __uint_as_float(p1.w);
  float s = m0 + m1, sh = m0h + m1h;
  s += __shfl_xor_sync(0xffffffffu, s, 1); sh += __shfl_xor_sync(0xffffffffu, sh, 1);
  s += __shfl_xor_sync(0xffffffffu, s, 2); sh += __shfl_xor_sync(0xffffffffu, sh, 2);
  mean_lo = s * 0.125f; mean_hi = sh * 0.125f;
  float d0 = m0 - mean_lo, d1 = m1 - mean_lo, d0h = m0h - mean_hi, d1h = m1h - mean_hi;
  float t = q0 + q1 + 64.f * (d0 * d0 + d1 * d1), th = q0h + q1h + 64.f * (d0h * d0h + d1h * d1h);
  t += __shfl_xor_sync(0xffffffffu, t, 1); th += __shfl_xor_sync(0xffffffffu, th, 1);
  t += __shfl_xor_sync(0xffffffffu, t, 2); th += __shfl_xor_sync(0xffffffffu, th, 2);
  rstd_lo = rsqrtf(t * (1.f / 512.f) + 1e-5f);
  rstd_hi = rsqrtf(th * (1.f / 512.f) + 1e-5f);
}
__device__ __forceinline__ uint4 local_stats(const float (&v)[32]) {
  float s = 0.f, sh = 0.f;
#pragma unroll
  for (int i = 0; i < 4; i++) {
    s += (v[8 * i + 0] + v[8 * i + 1]) + (v[8 * i + 4] + v[8 * i + 5]);
    sh += (v[8 * i + 2] + v[8 * i + 3]) + (v[8 * i + 6] + v[8 * i + 7]);
  }
  s += __shfl_xor_sync(0xffffffffu, s, 1); sh += __shfl_xor_sync(0xffffffffu, sh, 1);
  s += __shfl_xor_sync(0xffffffffu, s, 2); sh += __shfl_xor_sync(0xffffffffu, sh, 2);
  float m = s * (1.f / 64.f), mh = sh * (1.f / 64.f);
  float q = 0.f, qh = 0.f;
#pragma unroll
  for (int i = 0; i < 4; i++) {
    float a = v[8 * i + 0] - m, b = v[8 * i + 1] - m, c = v[8 * i + 4] - m, d = v[8 * i + 5] - m;
    q += (a * a + b * b) + (c * c + d * d);
    float e = v[8 * i + 2] - mh, f = v[8 * i + 3] - mh, g = v[8 * i + 6] - mh, h = v[8 * i + 7] - mh;
    qh += (e * e + f * f) + (g * g + h * h);
  }
  q += __shfl_xor_sync(0xffffffffu, q, 1); qh += __shfl_xor_sync(0xffffffffu, qh, 1);
  q += __shfl_xor_sync(0xffffffffu, q, 2); qh += __shfl_xor_sync(0xffffffffu, qh, 2);
  return make_uint4(__float_as_uint(m), __float_as_uint(q), __float_as_uint(mh), __float_as_uint(qh));
}

__device__ __forceinline__ int slab_row0(int c, int g, int w) { return 1024 * g + 64 * c + 32 * (w >> 1) + (w & 1); }

__device__ __forceinline__ void owner_ln_publish(uint32_t sbase, const float (&v)[32], uint32_t tphase, uint32_t tag_xn, uint4 (&xraw)[4]) {
  PHASE_VARS;
  TS(40 + 4 * tphase);
  uint4 st = local_stats(v);
  if (qc == 0) sts128(sbase + SM_TSTAT + warp * 128 + qr * 16, st);
  uint4* xn = g_xn + ((c * 8 + j) * 32 + 4 * warp) * 32 + lane;
  TS(41 + 4 * tphase);
  asm volatile("bar.sync 3, 256;" ::: "memory");
  TS(42 + 4 * tphase);
  const uint32_t rd = sbase + SM_TSTAT + qc * 256 + qr * 16;
  uint4 p0 = lds128(rd), p1 = lds128(rd + 128);
  float ml, rl, mh, rh;
  combine_stats(p0, p1, ml, rl, mh, rh);
  const float bl = -ml * rl, bh = -mh * rh;
#pragma unroll
  for (int i = 0; i < 4; i++) {
    uint4 o;
    o.x = set_tag(pack2(fmaf(v[8 * i + 0], rl, bl), fmaf(v[8 * i + 1], rl, bl)), tag_xn);
    o.y = pack2(fmaf(v[8 * i + 2], rh, bh), fmaf(v[8 * i + 3], rh, bh));
    o.z = pack2(fmaf(v[8 * i + 4], rl, bl), fmaf(v[8 * i + 5], rl, bl));
    o.w = pack2(fmaf(v[8 * i + 6], rh, bh), fmaf(v[8 * i + 7], rh, bh));
    st_ll(xn + i * 32, o);
  }
#pragma unroll
  for (int i = 0; i < 4; i++) {
    xraw[i].x = set_tag(pack2(v[8 * i + 0], v[8 * i + 1]), 1u);
    xraw[i].y = pack2(v[8 * i + 2], v[8 * i + 3]);
    xraw[i].z = pack2(v[8 * i + 4], v[8 * i + 5]);
    xraw[i].w = pack2(v[8 * i + 6], v[8 * i + 7]);
  }
}

__device__ __forceinline__ uint4 pack8(const float* a) {
  return make_uint4(pack2(a[0], a[1]), pack2(a[2], a[3]), pack2(a[4], a[5]), pack2(a[6], a[7]));
}
template <int U> __device__ __forceinline__ uint4 glu8(const float* g, float cl, float ch) {
  return make_uint4(pack2(g[0] * cl * g[U], g[1] * cl * g[U + 1]), pack2(g[2] * ch * g[U + 2], g[3] * ch * g[U + 3]),
                    pack2(g[4] * cl * g[U + 4], g[5] * cl * g[U + 5]), pack2(g[6] * ch * g[U + 6], g[7] * ch * g[U + 7]));
}
__device__ __forceinline__ uint32_t hfma2(uint32_t a, uint32_t b, uint32_t c) {
  uint32_t d;
  asm("fma.rn.bf16x2 %0, %1, %2, %3;" : "=r"(d) : "r"(a), "r"(b), "r"(c));
  return d;
}
__device__ __forceinline__ void keep4(const uint4 (&a)[4]) { keep(a[0]); keep(a[1]); keep(a[2]); keep(a[3]); }

#define STAGGER 0

__global__ void __launch_bounds__(NTHREADS, 1)
fused_kernel(const __grid_constant__ CUtensorMap m_qkv, const __grid_constant__ CUtensorMap m_wo,
             const __grid_constant__ CUtensorMap m_gu2, const __grid_constant__ CUtensorMap m_gu1,
             const __grid_constant__ CUtensorMap m_guh, const __grid_constant__ CUtensorMap m_wd112,
             const __grid_constant__ CUtensorMap m_wd80, const __grid_constant__ CUtensorMap m_wd32,
             const __nv_bfloat16* __restrict__ x_in,
             __nv_bfloat16* __restrict__ out, const char* __restrict__ w_o, const char* __restrict__ w_g,
             const char* __restrict__ w_u, const char* __restrict__ w_d
) {
  extern __shared__ __align__(1024) unsigned char smem_raw[];
  const uint32_t sbase = smem_u32(smem_raw);
  const uint32_t bars = sbase + SM_MISC;
  if ((sbase & 0xFFFFFFu) != SMEM_ORIGIN) return;
  TG(60);

  uint32_t xw[16];
  if (threadIdx.x < 256) {
    const int cc = blockIdx.x >> 3, jj = blockIdx.x & 7, ln = threadIdx.x & 31;
    const uint32_t* xp = reinterpret_cast<const uint32_t*>(x_in + (size_t)(slab_row0(cc, jj >> 2, jj & 3) + 2 * (ln >> 2)) * 512 + (threadIdx.x >> 5) * 64 + (ln & 3) * 2);
#pragma unroll
    for (int i = 0; i < 4; i++) {
      xw[4 * i] = __ldg(xp + i * 8); xw[4 * i + 1] = __ldg(xp + 16 * 256 + i * 8);
      xw[4 * i + 2] = __ldg(xp + i * 8 + 4); xw[4 * i + 3] = __ldg(xp + 16 * 256 + i * 8 + 4);
    }
  } else if (threadIdx.x == 256) {
    for (int i = 0; i < NGRAN; i++) { mbar_init(bars + BAR_FULL + 8 * i, 1); mbar_init(bars + BAR_EMPTY + 8 * i, 8); }
    for (int i = 0; i < 4; i++) mbar_init(bars + BAR_HRECV + 8 * i, 1);
    for (int i = 0; i < 2; i++) mbar_init(bars + BAR_HREADY + 8 * i, 4);
    asm volatile("fence.mbarrier_init.release.cluster;" ::: "memory");
  }
  __syncthreads();
  asm volatile("barrier.cluster.arrive.release.aligned;" ::: "memory");

  if (threadIdx.x >= 256) {
    asm volatile("setmaxnreg.dec.sync.aligned.u32 40;");
    const int warp = threadIdx.x >> 5, lane = threadIdx.x & 31;
    const int j = blockIdx.x & 7, b = j & 1;
    if (warp == 8) {
      ProdRing r{0u, 0u};
      const int cb0 = 224 * j + 32 * b, hb0 = 224 * j + 192 * (b ^ 1);
      const int jp = j ^ 1, cbp = 224 * jp + 32 * (b ^ 1), hbp = 224 * jp + 192 * b;
#pragma unroll 1
      for (uint32_t L = 0; L < 2; L++) {
        r.pos = 0;
        PSTOP_AT(L == 0 ? 0 : 3);
#pragma unroll 1
        for (int kb = 0; kb < 8; kb++) {
          const uint32_t g0 = prod_acquire<3>(sbase, r);
          if (elect_one()) {
            mbar_expect_tx(bars + BAR_FULL + 8 * g0, 24576);
            tma_3d(sbase + g0 * GRAN, &m_qkv, bars + BAR_FULL + 8 * g0, 64 * j, 64 * kb, 0);
          }
        }
        PSTOP_AT(10 * L + 1);
#pragma unroll 1
        for (int i = 0; i < 4; i++) {
          const uint32_t g0 = prod_acquire<2>(sbase, r);
          if (elect_one()) {
            mbar_expect_tx(bars + BAR_FULL + 8 * g0, 16384);
            tma_2d(sbase + g0 * GRAN, &m_wo, bars + BAR_FULL + 8 * g0, 64 * j, 128 * i);
          }
        }
        PSTOP_AT(10 * L + 2);
#pragma unroll 1
        for (int kb = 0; kb < 8; kb++) {
          const uint32_t g0 = prod_acquire<4>(sbase, r);
          if (elect_one()) {
            mbar_expect_tx(bars + BAR_FULL + 8 * g0, 32768);
            tma_4d(sbase + g0 * GRAN, &m_gu2, bars + BAR_FULL + 8 * g0, cb0, 64 * kb, 0, 0);
          }
        }
#pragma unroll 1
        for (int kb = 0; kb < 8; kb++) {
          const uint32_t g0 = prod_acquire<3>(sbase, r);
          if (elect_one()) {
            mbar_expect_tx(bars + BAR_FULL + 8 * g0, 24576);
            tma_4d(sbase + g0 * GRAN, &m_gu1, bars + BAR_FULL + 8 * g0, cb0 + 128, 64 * kb, 0, 0);
            tma_3d(sbase + g0 * GRAN + 16384, &m_guh, bars + BAR_FULL + 8 * g0, hb0, 64 * kb, 0);
          }
        }
        static_for<0, 16>([&](auto I) {
          constexpr int i = I.value, g0 = st_g0(ST_DN + i);
          prod_acquire_static<ST_DN + i>(sbase, L);
          if (elect_one()) {
            const uint32_t dst = sbase + g0 * GRAN, fb = bars + BAR_FULL + 8 * g0;
            const int n0 = 256 * b + 64 * dn_q(i);
            mbar_expect_tx(fb, 14336);
            if constexpr (dn_kh(i) == 0) {
              tma_2d(dst, &m_wd112, fb, n0, dn_par(i) ? cbp : cb0);
            } else {
              tma_2d(dst, &m_wd80, fb, n0, (dn_par(i) ? cbp : cb0) + 112);
              tma_2d(dst + 10240, &m_wd32, fb, n0, dn_par(i) ? hbp : hb0);
            }
          }
        });
        r.par ^= flip_mask(ST_DN, NSTAGE);
      }
    } else if (warp == 9) {
      const int cta = blockIdx.x;
      if (lane == 0) l2_prefetch(w_o + cta * 4096, 4096);
      if (lane == 1) l2_prefetch(w_g + cta * 14336, 14336);
      if (lane == 2) l2_prefetch(w_u + cta * 14336, 14336);
      if (lane == 3) l2_prefetch(w_d + cta * 14336, 14336);
    }
    __syncwarp();
    asm volatile("barrier.cluster.wait.acquire.aligned; // producer" ::: "memory");
    asm volatile("barrier.cluster.arrive.release.aligned;\nbarrier.cluster.wait.acquire.aligned; // producer" ::: "memory");
  } else {
    asm volatile("setmaxnreg.inc.sync.aligned.u32 232;");
    TS(0);
    TG(61);

    uint4 xraw[4];
    {
      float v[32];
#pragma unroll
      for (int i = 0; i < 16; i++) { v[2 * i] = bf_lo(xw[i]); v[2 * i + 1] = bf_hi(xw[i]); }
      owner_ln_publish(sbase, v, 0u, 1u, xraw);
      asm volatile("barrier.cluster.wait.acquire.aligned; // consumer" ::: "memory");
    }
    STOP_AT(0);
    TS(1);

#pragma unroll 1
    for (uint32_t L = 0; L < 2; L++) {
      const uint32_t tag = L ^ 1;
      {
        PHASE_VARS;
        uint4 qf[4], kf[4], vf[4], pp[4];
        const int blk = 16 * g + c;
        const uint4* halo_src = g_halo + ((((L * 32 + (blk > 0 ? blk - 1 : 0)) * 8 + j) * 2 + (w & 1)) * 4) * 32 + lane;
        {
          float acc[96];
          uint4 A[3][4];
          const uint4* xs = g_xn + ((c * 8 + slab) * 32) * 32 + lane;
          bar_wg(1 + g);
          load_pk<4>(A[0], xs);
          ensure_pk<4>(A[0], xs, tag);
          TS(2 + 20 * L);
          load_pk<4>(A[1], xs + 128);
          static_for<0, 8>([&](auto I) {
            constexpr int kb = I.value;
            cons_acquire<kb>(sbase, L);
            wg_fence();
            static_for<0, 4>([&](auto K) { constexpr int k = K.value; wgmma_n192<kb == 0 && k == 0, 0>(acc, A[kb % 3][k], st_desc<kb, 2048, 8192, 1024, 1>(k)); });
            wg_commit();
            if constexpr (kb > 0) {
              wg_wait<1>();
              keep4(A[(kb + 2) % 3]);
              cons_release<kb - 1>(sbase, lane);
            }
            if constexpr (kb + 1 < 8) ensure_pk<4>(A[(kb + 1) % 3], xs + (kb + 1) * 128, tag);
            if constexpr (kb + 2 < 8) load_pk<4>(A[(kb + 2) % 3], xs + (kb + 2) * 128);
            if constexpr (kb == 2) {
              uint4* xr = g_xraw + ((c * 8 + j) * 32 + 4 * warp) * 32 + lane;
#pragma unroll
              for (int i = 0; i < 4; i++) st_ll(xr + i * 32, xraw[i]);
            }
          });
          wg_wait<0>();
          TS(3 + 20 * L);
          fence_acc(acc);
          keep4(A[1]);
          cons_release<7>(sbase, lane);
#pragma unroll
          for (int h = 0; h < 4; h++) {
            kf[h] = pack8(&acc[32 + 8 * h]);
            const uint4 t = pack8(&acc[64 + 8 * h]);
            vf[h] = make_uint4(movm(t.x), movm(t.y), movm(t.z), movm(t.w));
            pp[h] = make_uint4(kf[h].y, kf[h].w, vf[h].y, vf[h].w);
          }
          if (w >= 2 && blk < 31) {
            uint4* hd = g_halo + ((((L * 32 + blk) * 8 + j) * 2 + (w & 1)) * 4) * 32 + lane;
#pragma unroll
            for (int h = 0; h < 4; h++) { uint4 t = pp[h]; t.x |= 1u; st_ll(hd + h * 32, t); }
          }
#pragma unroll
          for (int h = 0; h < 4; h++) sts128(areg + (28 + h) * 2048 + t128 * 16, pp[h]);
          if (w < 2 && blk > 0) load_pk<4>(pp, halo_src);
#pragma unroll
          for (int h = 0; h < 4; h++) qf[h] = pack8(&acc[8 * h]);
        }
        bar_wg(1 + g);
        const bool first = (w < 2) && (blk == 0);
        if (w >= 2) {
#pragma unroll
          for (int h = 0; h < 4; h++) pp[h] = lds128(areg + (28 + h) * 2048 + (t128 - 64) * 16);
        }
        bar_wg(1 + g);
        if (w < 2 && blk > 0) {
          ensure_pk<4>(pp, halo_src, 1u);
          uint4* hz = const_cast<uint4*>(halo_src);
#pragma unroll
          for (int h = 0; h < 4; h++) st_ll(hz + h * 32, make_uint4(0, 0, 0, 0));
        }
        TS(4 + 20 * L);
        const bool n0 = 2 * qc <= qr, n1 = 2 * qc + 1 <= qr;
        const uint32_t msk = (n0 ? 0xffffu : 0u) | (n1 ? 0xffff0000u : 0u);
        const float sc = 0.25f * 1.4426950408889634f;
        const float NEG = -1e30f;
        uint4* od = g_o + ((c * 8 + slab) * 32 + 4 * j) * 32 + lane;
        float l0[4], l1[4], h0[4], h1[4], ml[4], mh[4];
#pragma unroll
        for (int h = 0; h < 4; h++) {
          float sp[4], s0[4], s1[4];
          mma16816_z(sp, qf[h], pp[h].x, pp[h].y);
          mma16816_z(s0, qf[h], kf[h].x, kf[h].z);
          mma16816_z(s1, qf[h], kf[h].y, kf[h].w);
          if (first) { sp[0] = NEG; sp[1] = NEG; }
          l0[h] = n0 ? s0[0] : sp[0]; l1[h] = n1 ? s0[1] : sp[1];
          h0[h] = n0 ? s1[2] : s0[2]; h1[h] = n1 ? s1[3] : s0[3];
          ml[h] = fmaxf(l0[h], l1[h]); mh[h] = fmaxf(h0[h], h1[h]);
        }
#pragma unroll
        for (int h = 0; h < 4; h++) { ml[h] = fmaxf(ml[h], __shfl_xor_sync(0xffffffffu, ml[h], 1)); mh[h] = fmaxf(mh[h], __shfl_xor_sync(0xffffffffu, mh[h], 1)); }
#pragma unroll
        for (int h = 0; h < 4; h++) { ml[h] = fmaxf(ml[h], __shfl_xor_sync(0xffffffffu, ml[h], 2)); mh[h] = fmaxf(mh[h], __shfl_xor_sync(0xffffffffu, mh[h], 2)); }
        float sl[4], sh[4];
#pragma unroll
        for (int h = 0; h < 4; h++) {
          const float bl = -ml[h] * sc, bh = -mh[h] * sc;
          l0[h] = ex2(fmaf(l0[h], sc, bl)); l1[h] = ex2(fmaf(l1[h], sc, bl));
          h0[h] = ex2(fmaf(h0[h], sc, bh)); h1[h] = ex2(fmaf(h1[h], sc, bh));
          sl[h] = l0[h] + l1[h]; sh[h] = h0[h] + h1[h];
        }
#pragma unroll
        for (int h = 0; h < 4; h++) { sl[h] += __shfl_xor_sync(0xffffffffu, sl[h], 1); sh[h] += __shfl_xor_sync(0xffffffffu, sh[h], 1); }
#pragma unroll
        for (int h = 0; h < 4; h++) { sl[h] += __shfl_xor_sync(0xffffffffu, sl[h], 2); sh[h] += __shfl_xor_sync(0xffffffffu, sh[h], 2); }
#pragma unroll
        for (int h = 0; h < 4; h++) {
          const float il = rcp(sl[h]), ih = rcp(sh[h]);
          const uint32_t pl = pack2(l0[h] * il, l1[h] * il), ph = pack2(h0[h] * ih, h1[h] * ih);
          const uint4 P = make_uint4(pl & msk, ph & ~msk, 0u, ph & msk);
          float o0[4], o1[4];
          mma16816_z(o0, P, vf[h].x, vf[h].y);
          mma16816_z(o1, P, vf[h].z, vf[h].w);
          mma1688(o0, pl & ~msk, 0u, pp[h].z);
          mma1688(o1, pl & ~msk, 0u, pp[h].w);
          st_ll(od + h * 32, make_uint4(set_tag(pack2(o0[0], o0[1]), tag), pack2(o0[2], o0[3]), pack2(o1[0], o1[1]), pack2(o1[2], o1[3])));
        }
      }
      TS(5 + 20 * L);
      if (L == 0) { STOP_AT(1); } else { STOP_AT(11); }
      {
        PHASE_VARS;
        float acc[32];
        uint4 A[32], xr[4];
        const uint4* os = g_o + ((c * 8 + slab) * 32) * 32 + lane;
        uint4* xp = g_xraw + ((c * 8 + slab) * 32 + 4 * j) * 32 + lane;
        load_pk<4>(xr, xp);
        load_pk<4>(A, os);
        ensure_pk<4>(A, os, tag);
        TS(6 + 20 * L);
        load_pk<28>(A + 4, os + 128);
        static_for<0, 8>([&](auto I) {
          constexpr int kb = I.value;
          if constexpr ((kb & 1) == 0) cons_acquire<ST_WO + kb / 2>(sbase, L);
          if constexpr (kb > 0) ensure_pk<4>(A + 4 * kb, os + kb * 128, tag);
          wg_fence();
          static_for<0, 4>([&](auto K) {
            constexpr int k = K.value;
            wgmma_n64<kb == 0 && k == 0, 0>(acc, A[4 * kb + k], st_desc<ST_WO + kb / 2, 2048, 8192, 1024, 1>(4 * (kb & 1) + k));
          });
          wg_commit();
          if constexpr ((kb & 1) == 0 && kb > 0) { wg_wait<1>(); cons_release<ST_WO + kb / 2 - 1>(sbase, lane); }
        });
        wg_wait<0>();
        TS(7 + 20 * L);
        fence_acc(acc);
#pragma unroll
        for (int k = 0; k < 32; k++) keep(A[k]);
        cons_release<ST_WO + 3>(sbase, lane);
        ensure_pk<4>(xr, xp, 1u);
#pragma unroll
        for (int i = 0; i < 4; i++) {
          acc[8 * i + 0] += bf_lo(xr[i].x); acc[8 * i + 1] += bf_hi(xr[i].x); acc[8 * i + 2] += bf_lo(xr[i].y); acc[8 * i + 3] += bf_hi(xr[i].y);
          acc[8 * i + 4] += bf_lo(xr[i].z); acc[8 * i + 5] += bf_hi(xr[i].z); acc[8 * i + 6] += bf_lo(xr[i].w); acc[8 * i + 7] += bf_hi(xr[i].w);
          uint4 o = pack8(&acc[8 * i]);
          o.x = set_tag(o.x, 0u);
          st_ll(xp + i * 32, o);
        }
        uint4 st = local_stats(acc);
        st.x = set_tag(st.x, tag);
        if (qc == 0) st_ll(g_stats + ((c * 8 + slab) * 8 + j) * 8 + qr, st);
      }
      TS(8 + 20 * L);
      if (L == 0) { STOP_AT(2); } else { STOP_AT(12); }
      uint4 hs[14];
      {
        PHASE_VARS;
        float acc[128];
        uint4 A[3][4];
        const uint4* xs = g_xraw + ((c * 8 + slab) * 32) * 32 + lane;
        const uint4* sp = g_stats + ((c * 8 + slab) * 8 + 2 * qc) * 8 + qr;
        const uint32_t sm = areg + t128 * 16;
        uint32_t rl2, rh2, bl2, bh2;
        float cl, ch;
        {
          uint4 p[2];
          load_pk<4>(A[0], xs);
          p[0] = ld_ll(sp); p[1] = ld_ll(sp + 8);
          for (uint32_t n = 0; !ok_pk<2>(p, tag) && n < SPIN_LIMIT; n++) { load_pk<4>(A[0], xs); p[0] = ld_ll(sp); p[1] = ld_ll(sp + 8); }
          TS(9 + 20 * L);
          load_pk<4>(A[1], xs + 128);
          float ml, rl, mh, rh;
          combine_stats(p[0], p[1], ml, rl, mh, rh);
          rl2 = pack2(rl, rl); rh2 = pack2(rh, rh);
          const float rlb = bf_lo(rl2), rhb = bf_lo(rh2);
          bl2 = pack2(-ml * rlb, -ml * rlb); bh2 = pack2(-mh * rhb, -mh * rhb);
          cl = rl / rlb; cl *= cl; ch = rh / rhb; ch *= ch;
        }
        auto normalise = [&](uint4 (&xb)[4], int kb) {
#pragma unroll
          for (int k = 0; k < 4; k++) {
            xb[k].x = hfma2(xb[k].x, rl2, bl2); xb[k].y = hfma2(xb[k].y, rh2, bh2);
            xb[k].z = hfma2(xb[k].z, rl2, bl2); xb[k].w = hfma2(xb[k].w, rh2, bh2);
            sts128(sm + (kb * 4 + k) * 2048, xb[k]);
          }
        };
        ensure_pk<4>(A[0], xs, 0u);
        normalise(A[0], 0);
        static_for<0, 8>([&](auto I) {
          constexpr int kb = I.value;
          cons_acquire<ST_G1 + kb>(sbase, L);
          wg_fence();
          static_for<0, 4>([&](auto K) { constexpr int k = K.value; wgmma_n256<kb == 0 && k == 0, 0>(acc, A[kb % 3][k], st_desc<ST_G1 + kb, 2048, 8192, 1024, 1>(k)); });
          wg_commit();
          if constexpr (kb > 0) {
            wg_wait<1>();
            keep4(A[(kb + 2) % 3]);
            cons_release<ST_G1 + kb - 1>(sbase, lane);
          }
          if constexpr (kb + 1 < 8) ensure_pk<4>(A[(kb + 1) % 3], xs + (kb + 1) * 128, 0u);
          if constexpr (kb + 2 < 8) load_pk<4>(A[(kb + 2) % 3], xs + (kb + 2) * 128);
          if constexpr (kb + 1 < 8) normalise(A[(kb + 1) % 3], kb + 1);
        });
        wg_wait<0>();
        TS(10 + 20 * L);
        fence_acc(acc);
        keep4(A[1]);
        cons_release<ST_G1 + 7>(sbase, lane);
        uint4 B[2][4];
#pragma unroll
        for (int k = 0; k < 4; k++) B[0][k] = lds128(sm + k * 2048);
#pragma unroll
        for (int s = 0; s < 8; s++) hs[s] = glu8<32>(&acc[64 * (s >> 2) + 8 * (s & 3)], cl, ch);
        float acc2[96];
        const uint32_t hdst = mapa(sm, cbit ^ 1);
        const uint32_t hbar1 = mapa(bars + BAR_HRECV + 16 * g, cbit ^ 1);
        if (t128 == 0) { mbar_expect_tx(bars + BAR_HRECV + 16 * g, 8 * 2048); mbar_expect_tx(bars + BAR_HRECV + 16 * g + 8, 6 * 2048); }
        static_for<0, 8>([&](auto I) {
          constexpr int kb = I.value;
          cons_acquire<ST_G2 + kb>(sbase, L);
          wg_fence();
          static_for<0, 4>([&](auto K) {
            constexpr int k = K.value;
            wgmma_n128<kb == 0 && k == 0, 0>(acc2, B[kb & 1][k], st_desc<ST_G2 + kb, 2048, 8192, 1024, 1>(k));
            wgmma_n64<kb == 0 && k == 0, 64>(acc2, B[kb & 1][k], st_desc<ST_G2 + kb, 1024, 4096, 512, 2>(k) + (16384 >> 4));
          });
          wg_commit();
          if constexpr (kb > 0) {
            wg_wait<1>();
            keep4(B[(kb + 1) & 1]);
            cons_release<ST_G2 + kb - 1>(sbase, lane);
          }
          if constexpr (kb + 1 < 8) {
#pragma unroll
            for (int k = 0; k < 4; k++) B[(kb + 1) & 1][k] = lds128(sm + ((kb + 1) * 4 + k) * 2048);
          }
          if constexpr (kb == 3) {
            __syncwarp();
            if (lane == 0) mbar_arrive_remote(mapa(bars + BAR_HREADY + 8 * g, cbit ^ 1));
          }
          if constexpr (kb >= 4) {
            if constexpr (kb == 4) mbar_wait(bars + BAR_HREADY + 8 * g, L);
            st_async128(hdst + (2 * kb - 8) * 2048, hs[2 * kb - 8], hbar1);
            st_async128(hdst + (2 * kb - 7) * 2048, hs[2 * kb - 7], hbar1);
          }
        });
        wg_wait<0>();
        TS(11 + 20 * L);
        fence_acc(acc2);
        keep4(B[1]);
        cons_release<ST_G2 + 7>(sbase, lane);
#pragma unroll
        for (int s = 0; s < 4; s++) hs[8 + s] = glu8<32>(&acc2[8 * s], cl, ch);
#pragma unroll
        for (int s = 0; s < 2; s++) hs[12 + s] = glu8<16>(&acc2[64 + 8 * s], cl, ch);
      }
      {
        PHASE_VARS;
        TS(12 + 20 * L);
        const uint32_t hdst = mapa(areg + t128 * 16, cbit ^ 1);
        const uint32_t hbar2 = mapa(bars + BAR_HRECV + 16 * g + 8, cbit ^ 1);
        uint4* pd = g_part + ((((c * 8 + slab) * 2 + cbit) * 4 + ca) * 16) * 32 + lane;
        uint4 hb[7];
        float a0[32], a1[32], a2[32], a3[32];
        auto publish = [&](float (&a)[32], int q, int s0, int s1) {
#pragma unroll
          for (int s = s0; s < s1; s++) {
            uint4 o = pack8(&a[8 * s]);
            o.x = set_tag(o.x, tag);
            st_ll(pd + (4 * q + s) * 32, o);
          }
        };
        static_for<0, 16>([&](auto I) {
          constexpr int i = I.value, q = dn_q(i), par = dn_par(i), kh = dn_kh(i);
          auto mm = [&](auto K) {
            constexpr int k = decltype(K)::value;
            constexpr bool init = (k == 0 && par == 0 && kh == 0);
            constexpr uint64_t db = st_desc<ST_DN + i, 2048, 8192, 1024, 1>(k);
            if constexpr (q == 0) { if constexpr (par) wgmma_n64<init, 0>(a0, hb[k], db); else wgmma_n64<init, 0>(a0, hs[7 * kh + k], db); }
            if constexpr (q == 1) { if constexpr (par) wgmma_n64<init, 0>(a1, hb[k], db); else wgmma_n64<init, 0>(a1, hs[7 * kh + k], db); }
            if constexpr (q == 2) { if constexpr (par) wgmma_n64<init, 0>(a2, hb[k], db); else wgmma_n64<init, 0>(a2, hs[7 * kh + k], db); }
            if constexpr (q == 3) { if constexpr (par) wgmma_n64<init, 0>(a3, hb[k], db); else wgmma_n64<init, 0>(a3, hs[7 * kh + k], db); }
          };
          cons_acquire<ST_DN + i>(sbase, L);
          wg_fence();
          mm(IC<0>{}); mm(IC<1>{}); mm(IC<2>{}); mm(IC<3>{}); mm(IC<4>{}); mm(IC<5>{}); mm(IC<6>{});
          wg_commit();
          if constexpr (i > 0) { wg_wait<1>(); cons_release<ST_DN + i - 1>(sbase, lane); }
          if constexpr (i < 3) {
            st_async128(hdst + (8 + 2 * i) * 2048, hs[8 + 2 * i], hbar2);
            st_async128(hdst + (9 + 2 * i) * 2048, hs[9 + 2 * i], hbar2);
          }
          constexpr int n = i + 1;
          if constexpr (n < 16 && dn_par(n) && n != 4 && n != 7) {
            if constexpr (n == 2) { mbar_wait(bars + BAR_HRECV + 16 * g, L); TS(13 + 20 * L); }
            if constexpr (n == 6) { mbar_wait(bars + BAR_HRECV + 16 * g + 8, L); TS(14 + 20 * L); }
#pragma unroll
            for (int k = 0; k < 7; k++) { if constexpr (n != 2) keep(hb[k]); hb[k] = lds128(areg + t128 * 16 + (7 * dn_kh(n) + k) * 2048); }
          }
          if constexpr (i == 7) { fence_acc(a0); publish(a0, 0, 0, 4); }
          if constexpr (i == 8) { fence_acc(a1); publish(a1, 1, 0, 2); }
          if constexpr (i == 9) publish(a1, 1, 2, 4);
          if constexpr (i == 12) { fence_acc(a2); publish(a2, 2, 0, 2); }
          if constexpr (i == 13) publish(a2, 2, 2, 4);
        });
        wg_wait<0>();
        TS(15 + 20 * L);
        fence_acc(a3);
#pragma unroll
        for (int k = 0; k < 7; k++) { keep(hb[k]); keep(hs[7 + k]); }
        cons_release<NSTAGE - 1>(sbase, lane);
        publish(a3, 3, 0, 4);
      }
      {
        PHASE_VARS;
        const uint4* xq = g_xraw + ((c * 8 + j) * 32 + 4 * warp) * 32 + lane;
        const uint4* ps = g_part + ((((c * 8 + j) * 2 + g) * 4) * 16 + 4 * w) * 32 + lane;
        uint4 xr[4], P[4][4];
        float v[32];
        load_pk<4>(xr, xq);
#pragma unroll
        for (int src = 0; src < 4; src++) load_pk<4>(P[src], ps + src * (16 * 32));
#pragma unroll
        for (int src = 0; src < 4; src++) ensure_pk<4>(P[src], ps + src * (16 * 32), tag);
        TS(16 + 20 * L);
        ensure_pk<4>(xr, xq, 0u);
#pragma unroll
        for (int i = 0; i < 4; i++) {
          v[8 * i + 0] = bf_lo(xr[i].x); v[8 * i + 1] = bf_hi(xr[i].x); v[8 * i + 2] = bf_lo(xr[i].y); v[8 * i + 3] = bf_hi(xr[i].y);
          v[8 * i + 4] = bf_lo(xr[i].z); v[8 * i + 5] = bf_hi(xr[i].z); v[8 * i + 6] = bf_lo(xr[i].w); v[8 * i + 7] = bf_hi(xr[i].w);
          float d[8] = {0, 0, 0, 0, 0, 0, 0, 0};
#pragma unroll
          for (int src = 0; src < 4; src++) {
            const uint4 p = P[src][i];
            d[0] += bf_lo(p.x); d[1] += bf_hi(p.x); d[2] += bf_lo(p.y); d[3] += bf_hi(p.y);
            d[4] += bf_lo(p.z); d[5] += bf_hi(p.z); d[6] += bf_lo(p.w); d[7] += bf_hi(p.w);
          }
#pragma unroll
          for (int k = 0; k < 8; k++) v[8 * i + k] += d[k];
        }
        if (L == 0) {
          owner_ln_publish(sbase, v, 1u, 0u, xraw);
        } else {
#pragma unroll
          for (int i = 0; i < 4; i++) xraw[i] = make_uint4(0, 0, 0, 0);
          uint32_t* op = reinterpret_cast<uint32_t*>(out + (size_t)(slab_row0(c, j >> 2, j & 3) + 2 * qr) * 512 + warp * 64 + qc * 2);
#pragma unroll
          for (int i = 0; i < 4; i++) {
            op[i * 8] = pack2(v[8 * i], v[8 * i + 1]);
            op[16 * 256 + i * 8] = pack2(v[8 * i + 2], v[8 * i + 3]);
            op[i * 8 + 4] = pack2(v[8 * i + 4], v[8 * i + 5]);
            op[16 * 256 + i * 8 + 4] = pack2(v[8 * i + 6], v[8 * i + 7]);
          }
        }
      }
      TS(17 + 20 * L);
      if (L == 0) { STOP_AT(3); }
    }
    TG(62);
    asm volatile("barrier.cluster.arrive.release.aligned;\nbarrier.cluster.wait.acquire.aligned; // consumer" ::: "memory");
    TG(63);
  }
}

typedef CUresult (*EncodeFn)(CUtensorMap*, CUtensorMapDataType, cuuint32_t, void*, const cuuint64_t*, const cuuint64_t*,
                             const cuuint32_t*, const cuuint32_t*, CUtensorMapInterleave, CUtensorMapSwizzle,
                             CUtensorMapL2promotion, CUtensorMapFloatOOBfill);

void encode(EncodeFn fn, CUtensorMap* m, int rank, const void* base, const cuuint64_t* dims, const cuuint64_t* strides,
            const cuuint32_t* box, CUtensorMapSwizzle sw) {
  cuuint32_t es[5] = {1, 1, 1, 1, 1};
  fn(m, CU_TENSOR_MAP_DATA_TYPE_BFLOAT16, (cuuint32_t)rank, const_cast<void*>(base), dims, strides, box, es,
     CU_TENSOR_MAP_INTERLEAVE_NONE, sw, CU_TENSOR_MAP_L2_PROMOTION_L2_128B, CU_TENSOR_MAP_FLOAT_OOB_FILL_NONE);
}

}

extern "C" void kernel_launch(void* const* d_in, const int* in_sizes, int n_in, void* d_out, int out_size) {
  (void)in_sizes; (void)n_in; (void)out_size;
  const __nv_bfloat16* x = (const __nv_bfloat16*)d_in[0];
  const char* wqkv = (const char*)d_in[1];
  const char* wo = (const char*)d_in[2];
  const char* wg = (const char*)d_in[4];
  const char* wu = (const char*)d_in[5];
  const char* wd = (const char*)d_in[6];

  static EncodeFn fn = nullptr;
  if (!fn) {
    void* p = nullptr;
    cudaDriverEntryPointQueryResult st;
    cudaGetDriverEntryPoint("cuTensorMapEncodeTiled", &p, cudaEnableDefault, &st);
    fn = (EncodeFn)p;
    cudaFuncSetAttribute(fused_kernel, cudaFuncAttributeMaxDynamicSharedMemorySize, SMEM_BYTES);
  }
  CUtensorMap m_qkv, m_wo, m_gu2, m_gu1, m_guh, m_wd112, m_wd80, m_wd32;
  {
    cuuint64_t dims[3] = {512, 512, 3}, str[2] = {3072, 1024};
    cuuint32_t box[3] = {64, 64, 3};
    encode(fn, &m_qkv, 3, wqkv, dims, str, box, CU_TENSOR_MAP_SWIZZLE_128B);
  }
  {
    cuuint64_t dims[2] = {512, 512}, str[1] = {1024};
    cuuint32_t box[2] = {64, 128};
    encode(fn, &m_wo, 2, wo, dims, str, box, CU_TENSOR_MAP_SWIZZLE_128B);
  }
  {
    const char* lo = wg < wu ? wg : wu;
    cuuint64_t diff = (cuuint64_t)(wg < wu ? wu - wg : wg - wu);
    cuuint64_t dims[4] = {1792, 512, 2, 2}, str[3] = {3584, diff, 128};
    cuuint32_t box2[4] = {64, 64, 2, 2}, box1[4] = {64, 64, 2, 1}, boxh[3] = {32, 64, 2};
    encode(fn, &m_gu2, 4, lo, dims, str, box2, CU_TENSOR_MAP_SWIZZLE_128B);
    encode(fn, &m_gu1, 4, lo, dims, str, box1, CU_TENSOR_MAP_SWIZZLE_128B);
    encode(fn, &m_guh, 3, lo, dims, str, boxh, CU_TENSOR_MAP_SWIZZLE_64B);
  }
  {
    cuuint64_t dims[2] = {512, 1792}, str[1] = {1024};
    cuuint32_t b112[2] = {64, 112}, b80[2] = {64, 80}, b32[2] = {64, 32};
    encode(fn, &m_wd112, 2, wd, dims, str, b112, CU_TENSOR_MAP_SWIZZLE_128B);
    encode(fn, &m_wd80, 2, wd, dims, str, b80, CU_TENSOR_MAP_SWIZZLE_128B);
    encode(fn, &m_wd32, 2, wd, dims, str, b32, CU_TENSOR_MAP_SWIZZLE_128B);
  }
  cudaLaunchConfig_t cfg = {};
  cfg.gridDim = dim3(128);
  cfg.blockDim = dim3(NTHREADS);
  cfg.dynamicSmemBytes = SMEM_BYTES;
  cfg.stream = cudaStreamPerThread;
  cudaLaunchAttribute at[1];
  at[0].id = cudaLaunchAttributeClusterDimension;
  at[0].val.clusterDim.x = 2; at[0].val.clusterDim.y = 1; at[0].val.clusterDim.z = 1;
  cfg.attrs = at; cfg.numAttrs = 1;
  cudaLaunchKernelEx(&cfg, fused_kernel, m_qkv, m_wo, m_gu2, m_gu1, m_guh, m_wd112, m_wd80, m_wd32, x, (__nv_bfloat16*)d_out, wo, wg, wu, wd
  );
}
```

```cpp
#include <cuda_runtime.h>
#include <cuda_bf16.h>
#include <cuda.h>
#include <stdint.h>

namespace {

constexpr int NTHREADS = 384;
constexpr int GRAN = 8192;
constexpr int NGRAN = 12;
constexpr int SM_AREG = NGRAN * GRAN;
constexpr int SM_MISC = SM_AREG + 131072;
constexpr int SM_TSTAT = SM_MISC + 256;
constexpr int SMEM_BYTES = SM_TSTAT + 1024;
constexpr int BAR_FULL = 0, BAR_EMPTY = 96, BAR_HRECV = 192, BAR_HREADY = 224;

__device__ uint4 g_xn[16 * 8 * 32 * 32];
__device__ uint4 g_xraw[16 * 8 * 32 * 32];
__device__ uint4 g_o[16 * 8 * 32 * 32];
__device__ uint4 g_stats[16 * 8 * 8 * 8];
__device__ uint4 g_halo[2 * 32 * 8 * 8 * 32];
__device__ uint4 g_part[16 * 8 * 2 * 4 * 16 * 32];

#define TS(n)
#define TG(n)
#define OPAQUE(x) asm volatile("" : "+r"(x))
#define PHASE_VARS                                                                                   \
  int tid_ = threadIdx.x, bid_ = blockIdx.x;                                                         \
  OPAQUE(tid_); OPAQUE(bid_);                                                                        \
  const int lane = tid_ & 31, warp = tid_ >> 5, g = warp >> 2, w = warp & 3, t128 = tid_ & 127;      \
  const int qr = lane >> 2, qc = lane & 3, slab = warp;                                              \
  const int c = bid_ >> 3, j = bid_ & 7, ca = j >> 1, cbit = j & 1;                                  \
  const uint32_t areg = sbase + SM_AREG + g * 65536;                                                 \
  (void)g; (void)j; (void)w; (void)t128; (void)qr; (void)qc; (void)slab; (void)c; (void)ca; (void)cbit; (void)areg; (void)lane
#define STOP_AT(n)
#define PSTOP_AT(n)

__device__ __forceinline__ uint32_t smem_u32(const void* p) { return (uint32_t)__cvta_generic_to_shared(p); }
__device__ __forceinline__ void mbar_init(uint32_t bar, uint32_t cnt) {
  asm volatile("mbarrier.init.shared::cta.b64 [%0], %1;" ::"r"(bar), "r"(cnt) : "memory");
}
__device__ __forceinline__ void mbar_expect_tx(uint32_t bar, uint32_t bytes) {
  asm volatile("mbarrier.arrive.expect_tx.shared::cta.b64 _, [%0], %1;" ::"r"(bar), "r"(bytes) : "memory");
}
__device__ __forceinline__ void mbar_arrive(uint32_t bar) {
  asm volatile("mbarrier.arrive.shared::cta.b64 _, [%0];" ::"r"(bar) : "memory");
}
__device__ __forceinline__ void mbar_arrive_remote(uint32_t cluster_addr) {
  asm volatile("mbarrier.arrive.relaxed.cluster.shared::cluster.b64 _, [%0];" ::"r"(cluster_addr) : "memory");
}
__device__ __forceinline__ bool mbar_try(uint32_t bar, uint32_t parity) {
  uint32_t ok;
  asm volatile("{\n.reg .pred p;\nmbarrier.try_wait.parity.shared::cta.b64 p, [%1], %2;\nselp.u32 %0, 1, 0, p;\n}"
               : "=r"(ok) : "r"(bar), "r"(parity) : "memory");
  return ok != 0;
}
constexpr uint32_t SPIN_LIMIT = 1u << 16;
constexpr uint32_t SMEM_ORIGIN = 1024;
__device__ __forceinline__ void mbar_wait(uint32_t bar, uint32_t parity) {
  for (uint32_t n = 0; !mbar_try(bar, parity) && n < SPIN_LIMIT; n++) {}
}
__device__ __forceinline__ uint32_t mapa(uint32_t addr, uint32_t rank) {
  uint32_t r;
  asm volatile("mapa.shared::cluster.u32 %0, %1, %2;" : "=r"(r) : "r"(addr), "r"(rank));
  return r;
}

__device__ __forceinline__ void tma_2d(uint32_t dst, const CUtensorMap* m, uint32_t bar, int c0, int c1) {
  asm volatile("cp.async.bulk.tensor.2d.shared::cluster.global.mbarrier::complete_tx::bytes [%0], [%1, {%3, %4}], [%2];"
               ::"r"(dst), "l"(m), "r"(bar), "r"(c0), "r"(c1) : "memory");
}
__device__ __forceinline__ void tma_3d(uint32_t dst, const CUtensorMap* m, uint32_t bar, int c0, int c1, int c2) {
  asm volatile("cp.async.bulk.tensor.3d.shared::cluster.global.mbarrier::complete_tx::bytes [%0], [%1, {%3, %4, %5}], [%2];"
               ::"r"(dst), "l"(m), "r"(bar), "r"(c0), "r"(c1), "r"(c2) : "memory");
}
__device__ __forceinline__ void tma_4d(uint32_t dst, const CUtensorMap* m, uint32_t bar, int c0, int c1, int c2, int c3) {
  asm volatile("cp.async.bulk.tensor.4d.shared::cluster.global.mbarrier::complete_tx::bytes [%0], [%1, {%3, %4, %5, %6}], [%2];"
               ::"r"(dst), "l"(m), "r"(bar), "r"(c0), "r"(c1), "r"(c2), "r"(c3) : "memory");
}
__device__ __forceinline__ void l2_prefetch(const void* p, uint32_t bytes) {
  asm volatile("cp.async.bulk.prefetch.L2.global [%0], %1;" ::"l"(p), "r"(bytes) : "memory");
}

__device__ __forceinline__ uint4 ld_ll(const uint4* p) {
  uint4 v;
  asm volatile("ld.relaxed.gpu.global.v4.u32 {%0,%1,%2,%3}, [%4];" : "=r"(v.x), "=r"(v.y), "=r"(v.z), "=r"(v.w) : "l"(p) : "memory");
  return v;
}
__device__ __forceinline__ void st_ll(uint4* p, uint4 v) {
  asm volatile("st.relaxed.gpu.global.v4.u32 [%0], {%1,%2,%3,%4};" ::"l"(p), "r"(v.x), "r"(v.y), "r"(v.z), "r"(v.w) : "memory");
}
__device__ __forceinline__ uint4 lds128(uint32_t a) {
  uint4 v;
  asm volatile("ld.shared.v4.u32 {%0,%1,%2,%3}, [%4];" : "=r"(v.x), "=r"(v.y), "=r"(v.z), "=r"(v.w) : "r"(a) : "memory");
  return v;
}
__device__ __forceinline__ void sts128(uint32_t a, uint4 v) {
  asm volatile("st.shared.v4.u32 [%0], {%1,%2,%3,%4};" ::"r"(a), "r"(v.x), "r"(v.y), "r"(v.z), "r"(v.w) : "memory");
}
__device__ __forceinline__ void st_async128(uint32_t cluster_addr, uint4 v, uint32_t cluster_bar) {
  asm volatile("st.async.weak.shared::cluster.mbarrier::complete_tx::bytes.v4.b32 [%0], {%1,%2,%3,%4}, [%5];"
               ::"r"(cluster_addr), "r"(v.x), "r"(v.y), "r"(v.z), "r"(v.w), "r"(cluster_bar) : "memory");
}
__device__ __forceinline__ uint32_t pack2(float lo, float hi) {
  uint32_t r;
  asm("cvt.rn.bf16x2.f32 %0, %1, %2;" : "=r"(r) : "f"(hi), "f"(lo));
  return r;
}
__device__ __forceinline__ float bf_lo(uint32_t w) { return __uint_as_float(w << 16); }
__device__ __forceinline__ float bf_hi(uint32_t w) { return __uint_as_float(w & 0xffff0000u); }
__device__ __forceinline__ uint32_t set_tag(uint32_t w, uint32_t tag) { return (w & ~1u) | tag; }
__device__ __forceinline__ uint32_t movm(uint32_t a) {
  uint32_t d;
  asm("movmatrix.sync.aligned.m8n8.trans.b16 %0, %1;" : "=r"(d) : "r"(a));
  return d;
}
__device__ __forceinline__ void mma16816(float (&d)[4], const uint4& a, uint32_t b0, uint32_t b1) {
  asm("mma.sync.aligned.m16n8k16.row.col.f32.bf16.bf16.f32 {%0,%1,%2,%3}, {%4,%5,%6,%7}, {%8,%9}, {%0,%1,%2,%3};"
               : "+f"(d[0]), "+f"(d[1]), "+f"(d[2]), "+f"(d[3])
               : "r"(a.x), "r"(a.y), "r"(a.z), "r"(a.w), "r"(b0), "r"(b1));
}
__device__ __forceinline__ void mma1688(float (&d)[4], uint32_t a0, uint32_t a1, uint32_t b0) {
  asm("mma.sync.aligned.m16n8k8.row.col.f32.bf16.bf16.f32 {%0,%1,%2,%3}, {%4,%5}, {%6}, {%0,%1,%2,%3};"
      : "+f"(d[0]), "+f"(d[1]), "+f"(d[2]), "+f"(d[3])
      : "r"(a0), "r"(a1), "r"(b0));
}
__device__ __forceinline__ void mma16816_z(float (&d)[4], const uint4& a, uint32_t b0, uint32_t b1) {
  asm("mma.sync.aligned.m16n8k16.row.col.f32.bf16.bf16.f32 {%0,%1,%2,%3}, {%4,%5,%6,%7}, {%8,%9}, {%10,%10,%10,%10};"
      : "=f"(d[0]), "=f"(d[1]), "=f"(d[2]), "=f"(d[3])
      : "r"(a.x), "r"(a.y), "r"(a.z), "r"(a.w), "r"(b0), "r"(b1), "f"(0.f));
}
__device__ __forceinline__ float ex2(float x) {
  float y;
  asm("ex2.approx.ftz.f32 %0, %1;" : "=f"(y) : "f"(x));
  return y;
}
__device__ __forceinline__ float rcp(float x) {
  float y;
  asm("rcp.approx.ftz.f32 %0, %1;" : "=f"(y) : "f"(x));
  return y;
}
__device__ __forceinline__ void cp_async16(uint32_t dst, const void* src) {
  asm volatile("cp.async.cg.shared.global [%0], [%1], 16;" ::"r"(dst), "l"(src) : "memory");
}
__device__ __forceinline__ void cp_wait_all() { asm volatile("cp.async.wait_all;" ::: "memory"); }
__device__ __forceinline__ void cp_commit() { asm volatile("cp.async.commit_group;" ::: "memory"); }
template <int N> __device__ __forceinline__ void cp_wait() { asm volatile("cp.async.wait_group %0;" ::"n"(N) : "memory"); }
__device__ __forceinline__ void bar_wg(int id) { asm volatile("bar.sync %0, 128;" ::"r"(id) : "memory"); }
__device__ __forceinline__ void wg_fence() { asm volatile("wgmma.fence.sync.aligned;" ::: "memory"); }
__device__ __forceinline__ void wg_commit() { asm volatile("wgmma.commit_group.sync.aligned;" ::: "memory"); }
template <int N> __device__ __forceinline__ void wg_wait() { asm volatile("wgmma.wait_group.sync.aligned %0;" ::"n"(N) : "memory"); }
__device__ __forceinline__ void keep(const uint4& a) { asm volatile("" ::"r"(a.x), "r"(a.y), "r"(a.z), "r"(a.w) : "memory"); }
template <int T> __device__ __forceinline__ void zero_acc(float (&d)[T]) {
#pragma unroll
  for (int i = 0; i < T; i++) d[i] = 0.f;
}
template <int T> __device__ __forceinline__ void fence_acc(float (&d)[T]) {
#pragma unroll
  for (int i = 0; i < T; i++) asm volatile("" : "+f"(d[i])::"memory");
}

template <int O, int T> __device__ __forceinline__ void wgmma_rs_n64(float (&d)[T], const uint4& a, uint64_t db) {
  asm volatile("{\n.reg .pred p;\nsetp.ne.b32 p, 1, 0;\n"
    "wgmma.mma_async.sync.aligned.m64n64k16.f32.bf16.bf16 "
    "{%0, %1, %2, %3, %4, %5, %6, %7, %8, %9, %10, %11, %12, %13, %14, %15, "
    "%16, %17, %18, %19, %20, %21, %22, %23, %24, %25, %26, %27, %28, %29, %30, %31}, "
    "{%32, %33, %34, %35}, %36, p, 1, 1, 1;\n}\n"
    : "+f"(d[O + 0]), "+f"(d[O + 1]), "+f"(d[O + 2]), "+f"(d[O + 3]), "+f"(d[O + 4]), "+f"(d[O + 5]), "+f"(d[O + 6]), "+f"(d[O + 7]),
      "+f"(d[O + 8]), "+f"(d[O + 9]), "+f"(d[O + 10]), "+f"(d[O + 11]), "+f"(d[O + 12]), "+f"(d[O + 13]), "+f"(d[O + 14]), "+f"(d[O + 15]),
      "+f"(d[O + 16]), "+f"(d[O + 17]), "+f"(d[O + 18]), "+f"(d[O + 19]), "+f"(d[O + 20]), "+f"(d[O + 21]), "+f"(d[O + 22]), "+f"(d[O + 23]),
      "+f"(d[O + 24]), "+f"(d[O + 25]), "+f"(d[O + 26]), "+f"(d[O + 27]), "+f"(d[O + 28]), "+f"(d[O + 29]), "+f"(d[O + 30]), "+f"(d[O + 31])
    : "r"(a.x), "r"(a.y), "r"(a.z), "r"(a.w), "l"(db));
}
template <int O, int T> __device__ __forceinline__ void wgmma_rs_n64_init(float (&d)[T], const uint4& a, uint64_t db) {
  asm volatile("{\n.reg .pred p;\nsetp.ne.b32 p, 0, 0;\n"
    "wgmma.mma_async.sync.aligned.m64n64k16.f32.bf16.bf16 "
    "{%0, %1, %2, %3, %4, %5, %6, %7, %8, %9, %10, %11, %12, %13, %14, %15, "
    "%16, %17, %18, %19, %20, %21, %22, %23, %24, %25, %26, %27, %28, %29, %30, %31}, "
    "{%32, %33, %34, %35}, %36, p, 1, 1, 1;\n}\n"
    : "=f"(d[O + 0]), "=f"(d[O + 1]), "=f"(d[O + 2]), "=f"(d[O + 3]), "=f"(d[O + 4]), "=f"(d[O + 5]), "=f"(d[O + 6]), "=f"(d[O + 7]),
      "=f"(d[O + 8]), "=f"(d[O + 9]), "=f"(d[O + 10]), "=f"(d[O + 11]), "=f"(d[O + 12]), "=f"(d[O + 13]), "=f"(d[O + 14]), "=f"(d[O + 15]),
      "=f"(d[O + 16]), "=f"(d[O + 17]), "=f"(d[O + 18]), "=f"(d[O + 19]), "=f"(d[O + 20]), "=f"(d[O + 21]), "=f"(d[O + 22]), "=f"(d[O + 23]),
      "=f"(d[O + 24]), "=f"(d[O + 25]), "=f"(d[O + 26]), "=f"(d[O + 27]), "=f"(d[O + 28]), "=f"(d[O + 29]), "=f"(d[O + 30]), "=f"(d[O + 31])
    : "r"(a.x), "r"(a.y), "r"(a.z), "r"(a.w), "l"(db));
}
template <bool INIT, int O, int T> __device__ __forceinline__ void wgmma_n64(float (&d)[T], const uint4& a, uint64_t db) {
  if constexpr (INIT) wgmma_rs_n64_init<O>(d, a, db); else wgmma_rs_n64<O>(d, a, db);
}
template <int O, int T> __device__ __forceinline__ void wgmma_rs_n128(float (&d)[T], const uint4& a, uint64_t db) {
  asm volatile("{\n.reg .pred p;\nsetp.ne.b32 p, 1, 0;\n"
    "wgmma.mma_async.sync.aligned.m64n128k16.f32.bf16.bf16 "
    "{%0, %1, %2, %3, %4, %5, %6, %7, %8, %9, %10, %11, %12, %13, %14, %15, "
    "%16, %17, %18, %19, %20, %21, %22, %23, %24, %25, %26, %27, %28, %29, %30, %31, "
    "%32, %33, %34, %35, %36, %37, %38, %39, %40, %41, %42, %43, %44, %45, %46, %47, "
    "%48, %49, %50, %51, %52, %53, %54, %55, %56, %57, %58, %59, %60, %61, %62, %63}, "
    "{%64, %65, %66, %67}, %68, p, 1, 1, 1;\n}\n"
    : "+f"(d[O + 0]), "+f"(d[O + 1]), "+f"(d[O + 2]), "+f"(d[O + 3]), "+f"(d[O + 4]), "+f"(d[O + 5]), "+f"(d[O + 6]), "+f"(d[O + 7]),
      "+f"(d[O + 8]), "+f"(d[O + 9]), "+f"(d[O + 10]), "+f"(d[O + 11]), "+f"(d[O + 12]), "+f"(d[O + 13]), "+f"(d[O + 14]), "+f"(d[O + 15]),
      "+f"(d[O + 16]), "+f"(d[O + 17]), "+f"(d[O + 18]), "+f"(d[O + 19]), "+f"(d[O + 20]), "+f"(d[O + 21]), "+f"(d[O + 22]), "+f"(d[O + 23]),
      "+f"(d[O + 24]), "+f"(d[O + 25]), "+f"(d[O + 26]), "+f"(d[O + 27]), "+f"(d[O + 28]), "+f"(d[O + 29]), "+f"(d[O + 30]), "+f"(d[O + 31]),
      "+f"(d[O + 32]), "+f"(d[O + 33]), "+f"(d[O + 34]), "+f"(d[O + 35]), "+f"(d[O + 36]), "+f"(d[O + 37]), "+f"(d[O + 38]), "+f"(d[O + 39]),
      "+f"(d[O + 40]), "+f"(d[O + 41]), "+f"(d[O + 42]), "+f"(d[O + 43]), "+f"(d[O + 44]), "+f"(d[O + 45]), "+f"(d[O + 46]), "+f"(d[O + 47]),
      "+f"(d[O + 48]), "+f"(d[O + 49]), "+f"(d[O + 50]), "+f"(d[O + 51]), "+f"(d[O + 52]), "+f"(d[O + 53]), "+f"(d[O + 54]), "+f"(d[O + 55]),
      "+f"(d[O + 56]), "+f"(d[O + 57]), "+f"(d[O + 58]), "+f"(d[O + 59]), "+f"(d[O + 60]), "+f"(d[O + 61]), "+f"(d[O + 62]), "+f"(d[O + 63])
    : "r"(a.x), "r"(a.y), "r"(a.z), "r"(a.w), "l"(db));
}
template <int O, int T> __device__ __forceinline__ void wgmma_rs_n128_init(float (&d)[T], const uint4& a, uint64_t db) {
  asm volatile("{\n.reg .pred p;\nsetp.ne.b32 p, 0, 0;\n"
    "wgmma.mma_async.sync.aligned.m64n128k16.f32.bf16.bf16 "
    "{%0, %1, %2, %3, %4, %5, %6, %7, %8, %9, %10, %11, %12, %13, %14, %15, "
    "%16, %17, %18, %19, %20, %21, %22, %23, %24, %25, %26, %27, %28, %29, %30, %31, "
    "%32, %33, %34, %35, %36, %37, %38, %39, %40, %41, %42, %43, %44, %45, %46, %47, "
    "%48, %49, %50, %51, %52, %53, %54, %55, %56, %57, %58, %59, %60, %61, %62, %63}, "
    "{%64, %65, %66, %67}, %68, p, 1, 1, 1;\n}\n"
    : "=f"(d[O + 0]), "=f"(d[O + 1]), "=f"(d[O + 2]), "=f"(d[O + 3]), "=f"(d[O + 4]), "=f"(d[O + 5]), "=f"(d[O + 6]), "=f"(d[O + 7]),
      "=f"(d[O + 8]), "=f"(d[O + 9]), "=f"(d[O + 10]), "=f"(d[O + 11]), "=f"(d[O + 12]), "=f"(d[O + 13]), "=f"(d[O + 14]), "=f"(d[O + 15]),
      "=f"(d[O + 16]), "=f"(d[O + 17]), "=f"(d[O + 18]), "=f"(d[O + 19]), "=f"(d[O + 20]), "=f"(d[O + 21]), "=f"(d[O + 22]), "=f"(d[O + 23]),
      "=f"(d[O + 24]), "=f"(d[O + 25]), "=f"(d[O + 26]), "=f"(d[O + 27]), "=f"(d[O + 28]), "=f"(d[O + 29]), "=f"(d[O + 30]), "=f"(d[O + 31]),
      "=f"(d[O + 32]), "=f"(d[O + 33]), "=f"(d[O + 34]), "=f"(d[O + 35]), "=f"(d[O + 36]), "=f"(d[O + 37]), "=f"(d[O + 38]), "=f"(d[O + 39]),
      "=f"(d[O + 40]), "=f"(d[O + 41]), "=f"(d[O + 42]), "=f"(d[O + 43]), "=f"(d[O + 44]), "=f"(d[O + 45]), "=f"(d[O + 46]), "=f"(d[O + 47]),
      "=f"(d[O + 48]), "=f"(d[O + 49]), "=f"(d[O + 50]), "=f"(d[O + 51]), "=f"(d[O + 52]), "=f"(d[O + 53]), "=f"(d[O + 54]), "=f"(d[O + 55]),
      "=f"(d[O + 56]), "=f"(d[O + 57]), "=f"(d[O + 58]), "=f"(d[O + 59]), "=f"(d[O + 60]), "=f"(d[O + 61]), "=f"(d[O + 62]), "=f"(d[O + 63])
    : "r"(a.x), "r"(a.y), "r"(a.z), "r"(a.w), "l"(db));
}
template <bool INIT, int O, int T> __device__ __forceinline__ void wgmma_n128(float (&d)[T], const uint4& a, uint64_t db) {
  if constexpr (INIT) wgmma_rs_n128_init<O>(d, a, db); else wgmma_rs_n128<O>(d, a, db);
}
template <int O, int T> __device__ __forceinline__ void wgmma_rs_n192(float (&d)[T], const uint4& a, uint64_t db) {
  asm volatile("{\n.reg .pred p;\nsetp.ne.b32 p, 1, 0;\n"
    "wgmma.mma_async.sync.aligned.m64n192k16.f32.bf16.bf16 "
    "{%0, %1, %2, %3, %4, %5, %6, %7, %8, %9, %10, %11, %12, %13, %14, %15, "
    "%16, %17, %18, %19, %20, %21, %22, %23, %24, %25, %26, %27, %28, %29, %30, %31, "
    "%32, %33, %34, %35, %36, %37, %38, %39, %40, %41, %42, %43, %44, %45, %46, %47, "
    "%48, %49, %50, %51, %52, %53, %54, %55, %56, %57, %58, %59, %60, %61, %62, %63, "
    "%64, %65, %66, %67, %68, %69, %70, %71, %72, %73, %74, %75, %76, %77, %78, %79, "
    "%80, %81, %82, %83, %84, %85, %86, %87, %88, %89, %90, %91, %92, %93, %94, %95}, "
    "{%96, %97, %98, %99}, %100, p, 1, 1, 1;\n}\n"
    : "+f"(d[O + 0]), "+f"(d[O + 1]), "+f"(d[O + 2]), "+f"(d[O + 3]), "+f"(d[O + 4]), "+f"(d[O + 5]), "+f"(d[O + 6]), "+f"(d[O + 7]),
      "+f"(d[O + 8]), "+f"(d[O + 9]), "+f"(d[O + 10]), "+f"(d[O + 11]), "+f"(d[O + 12]), "+f"(d[O + 13]), "+f"(d[O + 14]), "+f"(d[O + 15]),
      "+f"(d[O + 16]), "+f"(d[O + 17]), "+f"(d[O + 18]), "+f"(d[O + 19]), "+f"(d[O + 20]), "+f"(d[O + 21]), "+f"(d[O + 22]), "+f"(d[O + 23]),
      "+f"(d[O + 24]), "+f"(d[O + 25]), "+f"(d[O + 26]), "+f"(d[O + 27]), "+f"(d[O + 28]), "+f"(d[O + 29]), "+f"(d[O + 30]), "+f"(d[O + 31]),
      "+f"(d[O + 32]), "+f"(d[O + 33]), "+f"(d[O + 34]), "+f"(d[O + 35]), "+f"(d[O + 36]), "+f"(d[O + 37]), "+f"(d[O + 38]), "+f"(d[O + 39]),
      "+f"(d[O + 40]), "+f"(d[O + 41]), "+f"(d[O + 42]), "+f"(d[O + 43]), "+f"(d[O + 44]), "+f"(d[O + 45]), "+f"(d[O + 46]), "+f"(d[O + 47]),
      "+f"(d[O + 48]), "+f"(d[O + 49]), "+f"(d[O + 50]), "+f"(d[O + 51]), "+f"(d[O + 52]), "+f"(d[O + 53]), "+f"(d[O + 54]), "+f"(d[O + 55]),
      "+f"(d[O + 56]), "+f"(d[O + 57]), "+f"(d[O + 58]), "+f"(d[O + 59]), "+f"(d[O + 60]), "+f"(d[O + 61]), "+f"(d[O + 62]), "+f"(d[O + 63]),
      "+f"(d[O + 64]), "+f"(d[O + 65]), "+f"(d[O + 66]), "+f"(d[O + 67]), "+f"(d[O + 68]), "+f"(d[O + 69]), "+f"(d[O + 70]), "+f"(d[O + 71]),
      "+f"(d[O + 72]), "+f"(d[O + 73]), "+f"(d[O + 74]), "+f"(d[O + 75]), "+f"(d[O + 76]), "+f"(d[O + 77]), "+f"(d[O + 78]), "+f"(d[O + 79]),
      "+f"(d[O + 80]), "+f"(d[O + 81]), "+f"(d[O + 82]), "+f"(d[O + 83]), "+f"(d[O + 84]), "+f"(d[O + 85]), "+f"(d[O + 86]), "+f"(d[O + 87]),
      "+f"(d[O + 88]), "+f"(d[O + 89]), "+f"(d[O + 90]), "+f"(d[O + 91]), "+f"(d[O + 92]), "+f"(d[O + 93]), "+f"(d[O + 94]), "+f"(d[O + 95])
    : "r"(a.x), "r"(a.y), "r"(a.z), "r"(a.w), "l"(db));
}
template <int O, int T> __device__ __forceinline__ void wgmma_rs_n192_init(float (&d)[T], const uint4& a, uint64_t db) {
  asm volatile("{\n.reg .pred p;\nsetp.ne.b32 p, 0, 0;\n"
    "wgmma.mma_async.sync.aligned.m64n192k16.f32.bf16.bf16 "
    "{%0, %1, %2, %3, %4, %5, %6, %7, %8, %9, %10, %11, %12, %13, %14, %15, "
    "%16, %17, %18, %19, %20, %21, %22, %23, %24, %25, %26, %27, %28, %29, %30, %31, "
    "%32, %33, %34, %35, %36, %37, %38, %39, %40, %41, %42, %43, %44, %45, %46, %47, "
    "%48, %49, %50, %51, %52, %53, %54, %55, %56, %57, %58, %59, %60, %61, %62, %63, "
    "%64, %65, %66, %67, %68, %69, %70, %71, %72, %73, %74, %75, %76, %77, %78, %79, "
    "%80, %81, %82, %83, %84, %85, %86, %87, %88, %89, %90, %91, %92, %93, %94, %95}, "
    "{%96, %97, %98, %99}, %100, p, 1, 1, 1;\n}\n"
    : "=f"(d[O + 0]), "=f"(d[O + 1]), "=f"(d[O + 2]), "=f"(d[O + 3]), "=f"(d[O + 4]), "=f"(d[O + 5]), "=f"(d[O + 6]), "=f"(d[O + 7]),
      "=f"(d[O + 8]), "=f"(d[O + 9]), "=f"(d[O + 10]), "=f"(d[O + 11]), "=f"(d[O + 12]), "=f"(d[O + 13]), "=f"(d[O + 14]), "=f"(d[O + 15]),
      "=f"(d[O + 16]), "=f"(d[O + 17]), "=f"(d[O + 18]), "=f"(d[O + 19]), "=f"(d[O + 20]), "=f"(d[O + 21]), "=f"(d[O + 22]), "=f"(d[O + 23]),
      "=f"(d[O + 24]), "=f"(d[O + 25]), "=f"(d[O + 26]), "=f"(d[O + 27]), "=f"(d[O + 28]), "=f"(d[O + 29]), "=f"(d[O + 30]), "=f"(d[O + 31]),
      "=f"(d[O + 32]), "=f"(d[O + 33]), "=f"(d[O + 34]), "=f"(d[O + 35]), "=f"(d[O + 36]), "=f"(d[O + 37]), "=f"(d[O + 38]), "=f"(d[O + 39]),
      "=f"(d[O + 40]), "=f"(d[O + 41]), "=f"(d[O + 42]), "=f"(d[O + 43]), "=f"(d[O + 44]), "=f"(d[O + 45]), "=f"(d[O + 46]), "=f"(d[O + 47]),
      "=f"(d[O + 48]), "=f"(d[O + 49]), "=f"(d[O + 50]), "=f"(d[O + 51]), "=f"(d[O + 52]), "=f"(d[O + 53]), "=f"(d[O + 54]), "=f"(d[O + 55]),
      "=f"(d[O + 56]), "=f"(d[O + 57]), "=f"(d[O + 58]), "=f"(d[O + 59]), "=f"(d[O + 60]), "=f"(d[O + 61]), "=f"(d[O + 62]), "=f"(d[O + 63]),
      "=f"(d[O + 64]), "=f"(d[O + 65]), "=f"(d[O + 66]), "=f"(d[O + 67]), "=f"(d[O + 68]), "=f"(d[O + 69]), "=f"(d[O + 70]), "=f"(d[O + 71]),
      "=f"(d[O + 72]), "=f"(d[O + 73]), "=f"(d[O + 74]), "=f"(d[O + 75]), "=f"(d[O + 76]), "=f"(d[O + 77]), "=f"(d[O + 78]), "=f"(d[O + 79]),
      "=f"(d[O + 80]), "=f"(d[O + 81]), "=f"(d[O + 82]), "=f"(d[O + 83]), "=f"(d[O + 84]), "=f"(d[O + 85]), "=f"(d[O + 86]), "=f"(d[O + 87]),
      "=f"(d[O + 88]), "=f"(d[O + 89]), "=f"(d[O + 90]), "=f"(d[O + 91]), "=f"(d[O + 92]), "=f"(d[O + 93]), "=f"(d[O + 94]), "=f"(d[O + 95])
    : "r"(a.x), "r"(a.y), "r"(a.z), "r"(a.w), "l"(db));
}
template <bool INIT, int O, int T> __device__ __forceinline__ void wgmma_n192(float (&d)[T], const uint4& a, uint64_t db) {
  if constexpr (INIT) wgmma_rs_n192_init<O>(d, a, db); else wgmma_rs_n192<O>(d, a, db);
}
template <int O, int T> __device__ __forceinline__ void wgmma_rs_n256(float (&d)[T], const uint4& a, uint64_t db) {
  asm volatile("{\n.reg .pred p;\nsetp.ne.b32 p, 1, 0;\n"
    "wgmma.mma_async.sync.aligned.m64n256k16.f32.bf16.bf16 "
    "{%0, %1, %2, %3, %4, %5, %6, %7, %8, %9, %10, %11, %12, %13, %14, %15, "
    "%16, %17, %18, %19, %20, %21, %22, %23, %24, %25, %26, %27, %28, %29, %30, %31, "
    "%32, %33, %34, %35, %36, %37, %38, %39, %40, %41, %42, %43, %44, %45, %46, %47, "
    "%48, %49, %50, %51, %52, %53, %54, %55, %56, %57, %58, %59, %60, %61, %62, %63, "
    "%64, %65, %66, %67, %68, %69, %70, %71, %72, %73, %74, %75, %76, %77, %78, %79, "
    "%80, %81, %82, %83, %84, %85, %86, %87, %88, %89, %90, %91, %92, %93, %94, %95, "
    "%96, %97, %98, %99, %100, %101, %102, %103, %104, %105, %106, %107, %108, %109, %110, %111, "
    "%112, %113, %114, %115, %116, %117, %118, %119, %120, %121, %122, %123, %124, %125, %126, %127}, "
    "{%128, %129, %130, %131}, %132, p, 1, 1, 1;\n}\n"
    : "+f"(d[O + 0]), "+f"(d[O + 1]), "+f"(d[O + 2]), "+f"(d[O + 3]), "+f"(d[O + 4]), "+f"(d[O + 5]), "+f"(d[O + 6]), "+f"(d[O + 7]),
      "+f"(d[O + 8]), "+f"(d[O + 9]), "+f"(d[O + 10]), "+f"(d[O + 11]), "+f"(d[O + 12]), "+f"(d[O + 13]), "+f"(d[O + 14]), "+f"(d[O + 15]),
      "+f"(d[O + 16]), "+f"(d[O + 17]), "+f"(d[O + 18]), "+f"(d[O + 19]), "+f"(d[O + 20]), "+f"(d[O + 21]), "+f"(d[O + 22]), "+f"(d[O + 23]),
      "+f"(d[O + 24]), "+f"(d[O + 25]), "+f"(d[O + 26]), "+f"(d[O + 27]), "+f"(d[O + 28]), "+f"(d[O + 29]), "+f"(d[O + 30]), "+f"(d[O + 31]),
      "+f"(d[O + 32]), "+f"(d[O + 33]), "+f"(d[O + 34]), "+f"(d[O + 35]), "+f"(d[O + 36]), "+f"(d[O + 37]), "+f"(d[O + 38]), "+f"(d[O + 39]),
      "+f"(d[O + 40]), "+f"(d[O + 41]), "+f"(d[O + 42]), "+f"(d[O + 43]), "+f"(d[O + 44]), "+f"(d[O + 45]), "+f"(d[O + 46]), "+f"(d[O + 47]),
      "+f"(d[O + 48]), "+f"(d[O + 49]), "+f"(d[O + 50]), "+f"(d[O + 51]), "+f"(d[O + 52]), "+f"(d[O + 53]), "+f"(d[O + 54]), "+f"(d[O + 55]),
      "+f"(d[O + 56]), "+f"(d[O + 57]), "+f"(d[O + 58]), "+f"(d[O + 59]), "+f"(d[O + 60]), "+f"(d[O + 61]), "+f"(d[O + 62]), "+f"(d[O + 63]),
      "+f"(d[O + 64]), "+f"(d[O + 65]), "+f"(d[O + 66]), "+f"(d[O + 67]), "+f"(d[O + 68]), "+f"(d[O + 69]), "+f"(d[O + 70]), "+f"(d[O + 71]),
      "+f"(d[O + 72]), "+f"(d[O + 73]), "+f"(d[O + 74]), "+f"(d[O + 75]), "+f"(d[O + 76]), "+f"(d[O + 77]), "+f"(d[O + 78]), "+f"(d[O + 79]),
      "+f"(d[O + 80]), "+f"(d[O + 81]), "+f"(d[O + 82]), "+f"(d[O + 83]), "+f"(d[O + 84]), "+f"(d[O + 85]), "+f"(d[O + 86]), "+f"(d[O + 87]),
      "+f"(d[O + 88]), "+f"(d[O + 89]), "+f"(d[O + 90]), "+f"(d[O + 91]), "+f"(d[O + 92]), "+f"(d[O + 93]), "+f"(d[O + 94]), "+f"(d[O + 95]),
      "+f"(d[O + 96]), "+f"(d[O + 97]), "+f"(d[O + 98]), "+f"(d[O + 99]), "+f"(d[O + 100]), "+f"(d[O + 101]), "+f"(d[O + 102]), "+f"(d[O + 103]),
      "+f"(d[O + 104]), "+f"(d[O + 105]), "+f"(d[O + 106]), "+f"(d[O + 107]), "+f"(d[O + 108]), "+f"(d[O + 109]), "+f"(d[O + 110]), "+f"(d[O + 111]),
      "+f"(d[O + 112]), "+f"(d[O + 113]), "+f"(d[O + 114]), "+f"(d[O + 115]), "+f"(d[O + 116]), "+f"(d[O + 117]), "+f"(d[O + 118]), "+f"(d[O + 119]),
      "+f"(d[O + 120]), "+f"(d[O + 121]), "+f"(d[O + 122]), "+f"(d[O + 123]), "+f"(d[O + 124]), "+f"(d[O + 125]), "+f"(d[O + 126]), "+f"(d[O + 127])
    : "r"(a.x), "r"(a.y), "r"(a.z), "r"(a.w), "l"(db));
}
template <int O, int T> __device__ __forceinline__ void wgmma_rs_n256_init(float (&d)[T], const uint4& a, uint64_t db) {
  asm volatile("{\n.reg .pred p;\nsetp.ne.b32 p, 0, 0;\n"
    "wgmma.mma_async.sync.aligned.m64n256k16.f32.bf16.bf16 "
    "{%0, %1, %2, %3, %4, %5, %6, %7, %8, %9, %10, %11, %12, %13, %14, %15, "
    "%16, %17, %18, %19, %20, %21, %22, %23, %24, %25, %26, %27, %28, %29, %30, %31, "
    "%32, %33, %34, %35, %36, %37, %38, %39, %40, %41, %42, %43, %44, %45, %46, %47, "
    "%48, %49, %50, %51, %52, %53, %54, %55, %56, %57, %58, %59, %60, %61, %62, %63, "
    "%64, %65, %66, %67, %68, %69, %70, %71, %72, %73, %74, %75, %76, %77, %78, %79, "
    "%80, %81, %82, %83, %84, %85, %86, %87, %88, %89, %90, %91, %92, %93, %94, %95, "
    "%96, %97, %98, %99, %100, %101, %102, %103, %104, %105, %106, %107, %108, %109, %110, %111, "
    "%112, %113, %114, %115, %116, %117, %118, %119, %120, %121, %122, %123, %124, %125, %126, %127}, "
    "{%128, %129, %130, %131}, %132, p, 1, 1, 1;\n}\n"
    : "=f"(d[O + 0]), "=f"(d[O + 1]), "=f"(d[O + 2]), "=f"(d[O + 3]), "=f"(d[O + 4]), "=f"(d[O + 5]), "=f"(d[O + 6]), "=f"(d[O + 7]),
      "=f"(d[O + 8]), "=f"(d[O + 9]), "=f"(d[O + 10]), "=f"(d[O + 11]), "=f"(d[O + 12]), "=f"(d[O + 13]), "=f"(d[O + 14]), "=f"(d[O + 15]),
      "=f"(d[O + 16]), "=f"(d[O + 17]), "=f"(d[O + 18]), "=f"(d[O + 19]), "=f"(d[O + 20]), "=f"(d[O + 21]), "=f"(d[O + 22]), "=f"(d[O + 23]),
      "=f"(d[O + 24]), "=f"(d[O + 25]), "=f"(d[O + 26]), "=f"(d[O + 27]), "=f"(d[O + 28]), "=f"(d[O + 29]), "=f"(d[O + 30]), "=f"(d[O + 31]),
      "=f"(d[O + 32]), "=f"(d[O + 33]), "=f"(d[O + 34]), "=f"(d[O + 35]), "=f"(d[O + 36]), "=f"(d[O + 37]), "=f"(d[O + 38]), "=f"(d[O + 39]),
      "=f"(d[O + 40]), "=f"(d[O + 41]), "=f"(d[O + 42]), "=f"(d[O + 43]), "=f"(d[O + 44]), "=f"(d[O + 45]), "=f"(d[O + 46]), "=f"(d[O + 47]),
      "=f"(d[O + 48]), "=f"(d[O + 49]), "=f"(d[O + 50]), "=f"(d[O + 51]), "=f"(d[O + 52]), "=f"(d[O + 53]), "=f"(d[O + 54]), "=f"(d[O + 55]),
      "=f"(d[O + 56]), "=f"(d[O + 57]), "=f"(d[O + 58]), "=f"(d[O + 59]), "=f"(d[O + 60]), "=f"(d[O + 61]), "=f"(d[O + 62]), "=f"(d[O + 63]),
      "=f"(d[O + 64]), "=f"(d[O + 65]), "=f"(d[O + 66]), "=f"(d[O + 67]), "=f"(d[O + 68]), "=f"(d[O + 69]), "=f"(d[O + 70]), "=f"(d[O + 71]),
      "=f"(d[O + 72]), "=f"(d[O + 73]), "=f"(d[O + 74]), "=f"(d[O + 75]), "=f"(d[O + 76]), "=f"(d[O + 77]), "=f"(d[O + 78]), "=f"(d[O + 79]),
      "=f"(d[O + 80]), "=f"(d[O + 81]), "=f"(d[O + 82]), "=f"(d[O + 83]), "=f"(d[O + 84]), "=f"(d[O + 85]), "=f"(d[O + 86]), "=f"(d[O + 87]),
      "=f"(d[O + 88]), "=f"(d[O + 89]), "=f"(d[O + 90]), "=f"(d[O + 91]), "=f"(d[O + 92]), "=f"(d[O + 93]), "=f"(d[O + 94]), "=f"(d[O + 95]),
      "=f"(d[O + 96]), "=f"(d[O + 97]), "=f"(d[O + 98]), "=f"(d[O + 99]), "=f"(d[O + 100]), "=f"(d[O + 101]), "=f"(d[O + 102]), "=f"(d[O + 103]),
      "=f"(d[O + 104]), "=f"(d[O + 105]), "=f"(d[O + 106]), "=f"(d[O + 107]), "=f"(d[O + 108]), "=f"(d[O + 109]), "=f"(d[O + 110]), "=f"(d[O + 111]),
      "=f"(d[O + 112]), "=f"(d[O + 113]), "=f"(d[O + 114]), "=f"(d[O + 115]), "=f"(d[O + 116]), "=f"(d[O + 117]), "=f"(d[O + 118]), "=f"(d[O + 119]),
      "=f"(d[O + 120]), "=f"(d[O + 121]), "=f"(d[O + 122]), "=f"(d[O + 123]), "=f"(d[O + 124]), "=f"(d[O + 125]), "=f"(d[O + 126]), "=f"(d[O + 127])
    : "r"(a.x), "r"(a.y), "r"(a.z), "r"(a.w), "l"(db));
}
template <bool INIT, int O, int T> __device__ __forceinline__ void wgmma_n256(float (&d)[T], const uint4& a, uint64_t db) {
  if constexpr (INIT) wgmma_rs_n256_init<O>(d, a, db); else wgmma_rs_n256<O>(d, a, db);
}

template <int N> __device__ __forceinline__ void load_pk(uint4* a, const uint4* p) {
#pragma unroll
  for (int i = 0; i < N; i++) a[i] = ld_ll(p + i * 32);
}
__device__ __forceinline__ uint32_t xor_or(uint32_t a, uint32_t b, uint32_t t) {
  uint32_t r;
  asm("lop3.b32 %0, %1, %2, %3, 0x7E;" : "=r"(r) : "r"(a), "r"(b), "r"(t));
  return r;
}
template <int N> __device__ __forceinline__ bool ok_pk(const uint4* a, uint32_t tag) {
  static_assert(N % 2 == 0, "");
  uint32_t x = xor_or(a[0].x, a[1].x, tag);
#pragma unroll
  for (int i = 2; i < N; i += 2) x |= xor_or(a[i].x, a[i + 1].x, tag);
  return __all_sync(0xffffffffu, (x & 1u) == 0u);
}
template <int N> __device__ __forceinline__ void ensure_pk(uint4* a, const uint4* p, uint32_t tag) {
  if (ok_pk<N>(a, tag)) return;
  uint32_t n = 0;
  do { load_pk<N>(a, p); } while (!ok_pk<N>(a, tag) && ++n < SPIN_LIMIT);
}

constexpr int NSTAGE = 44;
constexpr int ST_WO = 8, ST_G1 = 12, ST_G2 = 20, ST_DN = 28;
__host__ __device__ constexpr int st_len(int s) { return s < ST_WO ? 3 : s < ST_G1 ? 2 : s < ST_G2 ? 4 : s < ST_DN ? 3 : 2; }
__host__ __device__ constexpr int st_g0(int s) {
  int pos = 0, g0 = 0;
  for (int i = 0; i <= s; i++) {
    if (pos + st_len(i) > NGRAN) pos = 0;
    g0 = pos;
    pos += st_len(i);
  }
  return g0;
}
__host__ __device__ constexpr int cnt_first(int g, int s) {
  int n = 0;
  for (int i = 0; i < s; i++) n += (st_g0(i) == g);
  return n;
}
__host__ __device__ constexpr int cnt_cover(int g, int s) {
  int n = 0;
  for (int i = 0; i < s; i++) n += (g >= st_g0(i) && g < st_g0(i) + st_len(i));
  return n;
}
__host__ __device__ constexpr uint32_t flip_mask(int s0, int s1) {
  uint32_t m = 0;
  for (int i = s0; i < s1; i++) m ^= ((1u << st_len(i)) - 1u) << st_g0(i);
  return m;
}
__host__ __device__ constexpr int dn_q(int i) { return i < 3 ? 0 : i < 6 ? 1 : i == 6 ? 0 : i == 7 ? 1 : i < 12 ? 2 : 3; }
__host__ __device__ constexpr int dn_par(int i) { return i < 8 ? (i == 2 || i == 4 || i >= 6) : (i & 1); }
__host__ __device__ constexpr int dn_kh(int i) { return i < 8 ? (i == 1 || i >= 5) : ((i & 3) >= 2); }
template <int I> struct IC { static constexpr int value = I; };
template <int B, int E, typename F> __device__ __forceinline__ void static_for(F&& f) {
  if constexpr (B < E) { f(IC<B>{}); static_for<B + 1, E>(f); }
}
template <int S> __device__ __forceinline__ void cons_acquire(uint32_t sbase, uint32_t L) {
  constexpr int g0 = st_g0(S);
  constexpr uint32_t p0 = cnt_first(g0, S) & 1, odd = cnt_first(g0, NSTAGE) & 1;
  mbar_wait(sbase + SM_MISC + BAR_FULL + 8 * g0, p0 ^ (L & odd));
}
template <int S> __device__ __forceinline__ void cons_release(uint32_t sbase, int lane) {
  if (lane < st_len(S)) mbar_arrive(sbase + SM_MISC + BAR_EMPTY + 8 * st_g0(S) + 8 * lane);
}
__device__ __forceinline__ bool elect_one() {
  uint32_t p;
  asm volatile("{\n.reg .pred P;\nelect.sync _|P, 0xffffffff;\nselp.u32 %0, 1, 0, P;\n}" : "=r"(p));
  return p != 0;
}
struct ProdRing { uint32_t pos, par; };
template <int N> __device__ __forceinline__ uint32_t prod_acquire(uint32_t sbase, ProdRing& r) {
  if (r.pos + N > NGRAN) r.pos = 0;
  const uint32_t g0 = r.pos;
#pragma unroll
  for (uint32_t i = 0; i < N; i++) mbar_wait(sbase + SM_MISC + BAR_EMPTY + 8 * (g0 + i), ((r.par >> (g0 + i)) & 1u) ^ 1u);
  r.par ^= ((1u << N) - 1u) << g0;
  r.pos = g0 + N;
  return g0;
}
template <int S> __device__ __forceinline__ void prod_acquire_static(uint32_t sbase, uint32_t L) {
  constexpr int g0 = st_g0(S);
  static_for<0, st_len(S)>([&](auto I) {
    constexpr int g = g0 + I.value;
    constexpr uint32_t p0 = cnt_cover(g, S) & 1, odd = cnt_cover(g, NSTAGE) & 1;
    mbar_wait(sbase + SM_MISC + BAR_EMPTY + 8 * g, p0 ^ (L & odd) ^ 1u);
  });
}
template <int S, int KSTEP_BYTES, int LBO, int SBO, int SWZ> __device__ __forceinline__ constexpr uint64_t st_desc(int k) {
  return (uint64_t)((SMEM_ORIGIN + st_g0(S) * GRAN + k * KSTEP_BYTES) >> 4) | ((uint64_t)(LBO >> 4) << 16) |
         ((uint64_t)(SBO >> 4) << 32) | ((uint64_t)SWZ << 62);
}

__device__ __forceinline__ void combine_stats(const uint4& p0, const uint4& p1, float& mean_lo, float& rstd_lo, float& mean_hi, float& rstd_hi) {
  float m0 = __uint_as_float(p0.x), q0 = __uint_as_float(p0.y), m0h = __uint_as_float(p0.z), q0h = __uint_as_float(p0.w);
  float m1 = __uint_as_float(p1.x), q1 = __uint_as_float(p1.y), m1h = __uint_as_float(p1.z), q1h = __uint_as_float(p1.w);
  float s = m0 + m1, sh = m0h + m1h;
  s += __shfl_xor_sync(0xffffffffu, s, 1); sh += __shfl_xor_sync(0xffffffffu, sh, 1);
  s += __shfl_xor_sync(0xffffffffu, s, 2); sh += __shfl_xor_sync(0xffffffffu, sh, 2);
  mean_lo = s * 0.125f; mean_hi = sh * 0.125f;
  float d0 = m0 - mean_lo, d1 = m1 - mean_lo, d0h = m0h - mean_hi, d1h = m1h - mean_hi;
  float t = q0 + q1 + 64.f * (d0 * d0 + d1 * d1), th = q0h + q1h + 64.f * (d0h * d0h + d1h * d1h);
  t += __shfl_xor_sync(0xffffffffu, t, 1); th += __shfl_xor_sync(0xffffffffu, th, 1);
  t += __shfl_xor_sync(0xffffffffu, t, 2); th += __shfl_xor_sync(0xffffffffu, th, 2);
  rstd_lo = rsqrtf(t * (1.f / 512.f) + 1e-5f);
  rstd_hi = rsqrtf(th * (1.f / 512.f) + 1e-5f);
}
__device__ __forceinline__ uint4 local_stats(const float (&v)[32]) {
  float s = 0.f, sh = 0.f;
#pragma unroll
  for (int i = 0; i < 4; i++) {
    s += (v[8 * i + 0] + v[8 * i + 1]) + (v[8 * i + 4] + v[8 * i + 5]);
    sh += (v[8 * i + 2] + v[8 * i + 3]) + (v[8 * i + 6] + v[8 * i + 7]);
  }
  s += __shfl_xor_sync(0xffffffffu, s, 1); sh += __shfl_xor_sync(0xffffffffu, sh, 1);
  s += __shfl_xor_sync(0xffffffffu, s, 2); sh += __shfl_xor_sync(0xffffffffu, sh, 2);
  float m = s * (1.f / 64.f), mh = sh * (1.f / 64.f);
  float q = 0.f, qh = 0.f;
#pragma unroll
  for (int i = 0; i < 4; i++) {
    float a = v[8 * i + 0] - m, b = v[8 * i + 1] - m, c = v[8 * i + 4] - m, d = v[8 * i + 5] - m;
    q += (a * a + b * b) + (c * c + d * d);
    float e = v[8 * i + 2] - mh, f = v[8 * i + 3] - mh, g = v[8 * i + 6] - mh, h = v[8 * i + 7] - mh;
    qh += (e * e + f * f) + (g * g + h * h);
  }
  q += __shfl_xor_sync(0xffffffffu, q, 1); qh += __shfl_xor_sync(0xffffffffu, qh, 1);
  q += __shfl_xor_sync(0xffffffffu, q, 2); qh += __shfl_xor_sync(0xffffffffu, qh, 2);
  return make_uint4(__float_as_uint(m), __float_as_uint(q), __float_as_uint(mh), __float_as_uint(qh));
}

__device__ __forceinline__ int slab_row0(int c, int g, int w) { return 1024 * g + 64 * c + 32 * (w >> 1) + (w & 1); }

__device__ __forceinline__ void owner_ln_publish(uint32_t sbase, const float (&v)[32], uint32_t tphase, uint32_t tag_xn, uint4 (&xraw)[4]) {
  PHASE_VARS;
  TS(40 + 4 * tphase);
  uint4 st = local_stats(v);
  if (qc == 0) sts128(sbase + SM_TSTAT + warp * 128 + qr * 16, st);
  uint4* xn = g_xn + ((c * 8 + j) * 32 + 4 * warp) * 32 + lane;
  TS(41 + 4 * tphase);
  asm volatile("bar.sync 3, 256;" ::: "memory");
  TS(42 + 4 * tphase);
  const uint32_t rd = sbase + SM_TSTAT + qc * 256 + qr * 16;
  uint4 p0 = lds128(rd), p1 = lds128(rd + 128);
  float ml, rl, mh, rh;
  combine_stats(p0, p1, ml, rl, mh, rh);
  const float bl = -ml * rl, bh = -mh * rh;
#pragma unroll
  for (int i = 0; i < 4; i++) {
    uint4 o;
    o.x = set_tag(pack2(fmaf(v[8 * i + 0], rl, bl), fmaf(v[8 * i + 1], rl, bl)), tag_xn);
    o.y = pack2(fmaf(v[8 * i + 2], rh, bh), fmaf(v[8 * i + 3], rh, bh));
    o.z = pack2(fmaf(v[8 * i + 4], rl, bl), fmaf(v[8 * i + 5], rl, bl));
    o.w = pack2(fmaf(v[8 * i + 6], rh, bh), fmaf(v[8 * i + 7], rh, bh));
    st_ll(xn + i * 32, o);
  }
#pragma unroll
  for (int i = 0; i < 4; i++) {
    xraw[i].x = set_tag(pack2(v[8 * i + 0], v[8 * i + 1]), 1u);
    xraw[i].y = pack2(v[8 * i + 2], v[8 * i + 3]);
    xraw[i].z = pack2(v[8 * i + 4], v[8 * i + 5]);
    xraw[i].w = pack2(v[8 * i + 6], v[8 * i + 7]);
  }
}

__device__ __forceinline__ uint4 pack8(const float* a) {
  return make_uint4(pack2(a[0], a[1]), pack2(a[2], a[3]), pack2(a[4], a[5]), pack2(a[6], a[7]));
}
template <int U> __device__ __forceinline__ uint4 glu8(const float* g, float cl, float ch) {
  return make_uint4(pack2(g[0] * cl * g[U], g[1] * cl * g[U + 1]), pack2(g[2] * ch * g[U + 2], g[3] * ch * g[U + 3]),
                    pack2(g[4] * cl * g[U + 4], g[5] * cl * g[U + 5]), pack2(g[6] * ch * g[U + 6], g[7] * ch * g[U + 7]));
}
__device__ __forceinline__ uint32_t hfma2(uint32_t a, uint32_t b, uint32_t c) {
  uint32_t d;
  asm("fma.rn.bf16x2 %0, %1, %2, %3;" : "=r"(d) : "r"(a), "r"(b), "r"(c));
  return d;
}
__device__ __forceinline__ void keep4(const uint4 (&a)[4]) { keep(a[0]); keep(a[1]); keep(a[2]); keep(a[3]); }

#define STAGGER 0

__global__ void __launch_bounds__(NTHREADS, 1)
fused_kernel(const __grid_constant__ CUtensorMap m_qkv, const __grid_constant__ CUtensorMap m_wo,
             const __grid_constant__ CUtensorMap m_gu2, const __grid_constant__ CUtensorMap m_gu1,
             const __grid_constant__ CUtensorMap m_guh, const __grid_constant__ CUtensorMap m_wd112,
             const __grid_constant__ CUtensorMap m_wd80, const __grid_constant__ CUtensorMap m_wd32,
             const __nv_bfloat16* __restrict__ x_in,
             __nv_bfloat16* __restrict__ out, const char* __restrict__ w_o, const char* __restrict__ w_g,
             const char* __restrict__ w_u, const char* __restrict__ w_d
) {
  extern __shared__ __align__(1024) unsigned char smem_raw[];
  const uint32_t sbase = smem_u32(smem_raw);
  const uint32_t bars = sbase + SM_MISC;
  if ((sbase & 0xFFFFFFu) != SMEM_ORIGIN) return;
  TG(60);

  uint32_t xw[16];
  if (threadIdx.x < 256) {
    const int cc = blockIdx.x >> 3, jj = blockIdx.x & 7, ln = threadIdx.x & 31;
    const uint32_t* xp = reinterpret_cast<const uint32_t*>(x_in + (size_t)(slab_row0(cc, jj >> 2, jj & 3) + 2 * (ln >> 2)) * 512 + (threadIdx.x >> 5) * 64 + (ln & 3) * 2);
#pragma unroll
    for (int i = 0; i < 4; i++) {
      xw[4 * i] = __ldg(xp + i * 8); xw[4 * i + 1] = __ldg(xp + 16 * 256 + i * 8);
      xw[4 * i + 2] = __ldg(xp + i * 8 + 4); xw[4 * i + 3] = __ldg(xp + 16 * 256 + i * 8 + 4);
    }
  } else if (threadIdx.x == 256) {
    for (int i = 0; i < NGRAN; i++) { mbar_init(bars + BAR_FULL + 8 * i, 1); mbar_init(bars + BAR_EMPTY + 8 * i, 8); }
    for (int i = 0; i < 4; i++) mbar_init(bars + BAR_HRECV + 8 * i, 1);
    for (int i = 0; i < 2; i++) mbar_init(bars + BAR_HREADY + 8 * i, 4);
    asm volatile("fence.mbarrier_init.release.cluster;" ::: "memory");
  }
  __syncthreads();
  asm volatile("barrier.cluster.arrive.release.aligned;" ::: "memory");

  if (threadIdx.x >= 256) {
    asm volatile("setmaxnreg.dec.sync.aligned.u32 40;");
    const int warp = threadIdx.x >> 5, lane = threadIdx.x & 31;
    const int j = blockIdx.x & 7, b = j & 1;
    if (warp == 8) {
      ProdRing r{0u, 0u};
      const int cb0 = 224 * j + 32 * b, hb0 = 224 * j + 192 * (b ^ 1);
      const int jp = j ^ 1, cbp = 224 * jp + 32 * (b ^ 1), hbp = 224 * jp + 192 * b;
#pragma unroll 1
      for (uint32_t L = 0; L < 2; L++) {
        r.pos = 0;
        PSTOP_AT(L == 0 ? 0 : 3);
#pragma unroll 1
        for (int kb = 0; kb < 8; kb++) {
          const uint32_t g0 = prod_acquire<3>(sbase, r);
          if (elect_one()) {
            mbar_expect_tx(bars + BAR_FULL + 8 * g0, 24576);
            tma_3d(sbase + g0 * GRAN, &m_qkv, bars + BAR_FULL + 8 * g0, 64 * j, 64 * kb, 0);
          }
        }
        PSTOP_AT(10 * L + 1);
#pragma unroll 1
        for (int i = 0; i < 4; i++) {
          const uint32_t g0 = prod_acquire<2>(sbase, r);
          if (elect_one()) {
            mbar_expect_tx(bars + BAR_FULL + 8 * g0, 16384);
            tma_2d(sbase + g0 * GRAN, &m_wo, bars + BAR_FULL + 8 * g0, 64 * j, 128 * i);
          }
        }
        PSTOP_AT(10 * L + 2);
#pragma unroll 1
        for (int kb = 0; kb < 8; kb++) {
          const uint32_t g0 = prod_acquire<4>(sbase, r);
          if (elect_one()) {
            mbar_expect_tx(bars + BAR_FULL + 8 * g0, 32768);
            tma_4d(sbase + g0 * GRAN, &m_gu2, bars + BAR_FULL + 8 * g0, cb0, 64 * ((j + kb) & 7), 0, 0);
          }
        }
#pragma unroll 1
        for (int kb = 0; kb < 8; kb++) {
          const uint32_t g0 = prod_acquire<3>(sbase, r);
          if (elect_one()) {
            mbar_expect_tx(bars + BAR_FULL + 8 * g0, 24576);
            tma_4d(sbase + g0 * GRAN, &m_gu1, bars + BAR_FULL + 8 * g0, cb0 + 128, 64 * ((j + kb) & 7), 0, 0);
            tma_3d(sbase + g0 * GRAN + 16384, &m_guh, bars + BAR_FULL + 8 * g0, hb0, 64 * ((j + kb) & 7), 0);
          }
        }
        static_for<0, 16>([&](auto I) {
          constexpr int i = I.value, g0 = st_g0(ST_DN + i);
          prod_acquire_static<ST_DN + i>(sbase, L);
          if (elect_one()) {
            const uint32_t dst = sbase + g0 * GRAN, fb = bars + BAR_FULL + 8 * g0;
            const int n0 = 256 * b + 64 * dn_q(i);
            mbar_expect_tx(fb, 14336);
            if constexpr (dn_kh(i) == 0) {
              tma_2d(dst, &m_wd112, fb, n0, dn_par(i) ? cbp : cb0);
            } else {
              tma_2d(dst, &m_wd80, fb, n0, (dn_par(i) ? cbp : cb0) + 112);
              tma_2d(dst + 10240, &m_wd32, fb, n0, dn_par(i) ? hbp : hb0);
            }
          }
        });
        r.par ^= flip_mask(ST_DN, NSTAGE);
      }
    } else if (warp == 9) {
      const int cta = blockIdx.x;
      if (lane == 0) l2_prefetch(w_o + cta * 4096, 4096);
      if (lane == 1) l2_prefetch(w_g + cta * 14336, 14336);
      if (lane == 2) l2_prefetch(w_u + cta * 14336, 14336);
      if (lane == 3) l2_prefetch(w_d + cta * 14336, 14336);
    }
    __syncwarp();
    asm volatile("barrier.cluster.wait.acquire.aligned; // producer" ::: "memory");
    asm volatile("barrier.cluster.arrive.release.aligned;\nbarrier.cluster.wait.acquire.aligned; // producer" ::: "memory");
  } else {
    asm volatile("setmaxnreg.inc.sync.aligned.u32 232;");
    TS(0);
    TG(61);

    uint4 xraw[4];
    {
      float v[32];
#pragma unroll
      for (int i = 0; i < 16; i++) { v[2 * i] = bf_lo(xw[i]); v[2 * i + 1] = bf_hi(xw[i]); }
      owner_ln_publish(sbase, v, 0u, 1u, xraw);
      asm volatile("barrier.cluster.wait.acquire.aligned; // consumer" ::: "memory");
    }
    STOP_AT(0);
    TS(1);

#pragma unroll 1
    for (uint32_t L = 0; L < 2; L++) {
      const uint32_t tag = L ^ 1;
      {
        PHASE_VARS;
        uint4 qf[4], kf[4], vf[4], pp[4];
        const int blk = 16 * g + c;
        const uint4* halo_src = g_halo + ((((L * 32 + (blk > 0 ? blk - 1 : 0)) * 8 + j) * 2 + (w & 1)) * 4) * 32 + lane;
        {
          float acc[96];
          uint4 A[3][4];
          const uint4* xs = g_xn + ((c * 8 + slab) * 32) * 32 + lane;
          bar_wg(1 + g);
          load_pk<4>(A[0], xs);
          ensure_pk<4>(A[0], xs, tag);
          TS(2 + 20 * L);
          load_pk<4>(A[1], xs + 128);
          static_for<0, 8>([&](auto I) {
            constexpr int kb = I.value;
            cons_acquire<kb>(sbase, L);
            wg_fence();
            static_for<0, 4>([&](auto K) { constexpr int k = K.value; wgmma_n192<kb == 0 && k == 0, 0>(acc, A[kb % 3][k], st_desc<kb, 2048, 8192, 1024, 1>(k)); });
            wg_commit();
            if constexpr (kb > 0) {
              wg_wait<1>();
              keep4(A[(kb + 2) % 3]);
              cons_release<kb - 1>(sbase, lane);
            }
            if constexpr (kb + 1 < 8) ensure_pk<4>(A[(kb + 1) % 3], xs + (kb + 1) * 128, tag);
            if constexpr (kb + 2 < 8) load_pk<4>(A[(kb + 2) % 3], xs + (kb + 2) * 128);
            if constexpr (kb == 2) {
              uint4* xr = g_xraw + ((c * 8 + j) * 32 + 4 * warp) * 32 + lane;
#pragma unroll
              for (int i = 0; i < 4; i++) st_ll(xr + i * 32, xraw[i]);
            }
          });
          wg_wait<0>();
          TS(3 + 20 * L);
          fence_acc(acc);
          keep4(A[1]);
          cons_release<7>(sbase, lane);
#pragma unroll
          for (int h = 0; h < 4; h++) {
            kf[h].y = pack2(acc[32 + 8 * h + 2], acc[32 + 8 * h + 3]); kf[h].w = pack2(acc[32 + 8 * h + 6], acc[32 + 8 * h + 7]);
            vf[h].y = movm(pack2(acc[64 + 8 * h + 2], acc[64 + 8 * h + 3])); vf[h].w = movm(pack2(acc[64 + 8 * h + 6], acc[64 + 8 * h + 7]));
            pp[h] = make_uint4(kf[h].y, kf[h].w, vf[h].y, vf[h].w);
          }
          if (w >= 2 && blk < 31) {
            uint4* hd = g_halo + ((((L * 32 + blk) * 8 + j) * 2 + (w & 1)) * 4) * 32 + lane;
#pragma unroll
            for (int h = 0; h < 4; h++) { uint4 t = pp[h]; t.x |= 1u; st_ll(hd + h * 32, t); }
          }
#pragma unroll
          for (int h = 0; h < 4; h++) sts128(areg + (28 + h) * 2048 + t128 * 16, pp[h]);
          if (w < 2 && blk > 0) load_pk<4>(pp, halo_src);
#pragma unroll
          for (int h = 0; h < 4; h++) {
            kf[h].x = pack2(acc[32 + 8 * h], acc[32 + 8 * h + 1]); kf[h].z = pack2(acc[32 + 8 * h + 4], acc[32 + 8 * h + 5]);
            vf[h].x = movm(pack2(acc[64 + 8 * h], acc[64 + 8 * h + 1])); vf[h].z = movm(pack2(acc[64 + 8 * h + 4], acc[64 + 8 * h + 5]));
          }
#pragma unroll
          for (int h = 0; h < 4; h++) qf[h] = pack8(&acc[8 * h]);
        }
        bar_wg(1 + g);
        const bool first = (w < 2) && (blk == 0);
        if (w >= 2) {
#pragma unroll
          for (int h = 0; h < 4; h++) pp[h] = lds128(areg + (28 + h) * 2048 + (t128 - 64) * 16);
        }
        bar_wg(1 + g);
        if (w < 2 && blk > 0) {
          ensure_pk<4>(pp, halo_src, 1u);
          uint4* hz = const_cast<uint4*>(halo_src);
#pragma unroll
          for (int h = 0; h < 4; h++) st_ll(hz + h * 32, make_uint4(0, 0, 0, 0));
        }
        TS(4 + 20 * L);
        const bool n0 = 2 * qc <= qr, n1 = 2 * qc + 1 <= qr;
        const uint32_t msk = (n0 ? 0xffffu : 0u) | (n1 ? 0xffff0000u : 0u);
        const float sc = 0.25f * 1.4426950408889634f;
        const float NEG = -1e30f;
        uint4* od = g_o + ((c * 8 + slab) * 32 + 4 * j) * 32 + lane;
        float l0[4], l1[4], h0[4], h1[4], ml[4], mh[4];
#pragma unroll
        for (int h = 0; h < 4; h++) {
          float sp[4], s0[4], s1[4];
          mma16816_z(sp, qf[h], pp[h].x, pp[h].y);
          mma16816_z(s0, qf[h], kf[h].x, kf[h].z);
          mma16816_z(s1, qf[h], kf[h].y, kf[h].w);
          if (first) { sp[0] = NEG; sp[1] = NEG; }
          l0[h] = n0 ? s0[0] : sp[0]; l1[h] = n1 ? s0[1] : sp[1];
          h0[h] = n0 ? s1[2] : s0[2]; h1[h] = n1 ? s1[3] : s0[3];
          ml[h] = fmaxf(l0[h], l1[h]); mh[h] = fmaxf(h0[h], h1[h]);
        }
#pragma unroll
        for (int h = 0; h < 4; h++) { ml[h] = fmaxf(ml[h], __shfl_xor_sync(0xffffffffu, ml[h], 1)); mh[h] = fmaxf(mh[h], __shfl_xor_sync(0xffffffffu, mh[h], 1)); }
#pragma unroll
        for (int h = 0; h < 4; h++) { ml[h] = fmaxf(ml[h], __shfl_xor_sync(0xffffffffu, ml[h], 2)); mh[h] = fmaxf(mh[h], __shfl_xor_sync(0xffffffffu, mh[h], 2)); }
        float sl[4], sh[4];
#pragma unroll
        for (int h = 0; h < 4; h++) {
          const float bl = -ml[h] * sc, bh = -mh[h] * sc;
          l0[h] = ex2(fmaf(l0[h], sc, bl)); l1[h] = ex2(fmaf(l1[h], sc, bl));
          h0[h] = ex2(fmaf(h0[h], sc, bh)); h1[h] = ex2(fmaf(h1[h], sc, bh));
          sl[h] = l0[h] + l1[h]; sh[h] = h0[h] + h1[h];
        }
#pragma unroll
        for (int h = 0; h < 4; h++) { sl[h] += __shfl_xor_sync(0xffffffffu, sl[h], 1); sh[h] += __shfl_xor_sync(0xffffffffu, sh[h], 1); }
#pragma unroll
        for (int h = 0; h < 4; h++) { sl[h] += __shfl_xor_sync(0xffffffffu, sl[h], 2); sh[h] += __shfl_xor_sync(0xffffffffu, sh[h], 2); }
#pragma unroll
        for (int h = 0; h < 4; h++) {
          const float il = rcp(sl[h]), ih = rcp(sh[h]);
          const uint32_t pl = pack2(l0[h] * il, l1[h] * il), ph = pack2(h0[h] * ih, h1[h] * ih);
          const uint4 P = make_uint4(pl & msk, ph & ~msk, 0u, ph & msk);
          float o0[4], o1[4];
          mma16816_z(o0, P, vf[h].x, vf[h].y);
          mma16816_z(o1, P, vf[h].z, vf[h].w);
          mma1688(o0, pl & ~msk, 0u, pp[h].z);
          mma1688(o1, pl & ~msk, 0u, pp[h].w);
          st_ll(od + h * 32, make_uint4(set_tag(pack2(o0[0], o0[1]), tag), pack2(o0[2], o0[3]), pack2(o1[0], o1[1]), pack2(o1[2], o1[3])));
        }
      }
      TS(5 + 20 * L);
      if (L == 0) { STOP_AT(1); } else { STOP_AT(11); }
      uint4 x1own[4];
      {
        PHASE_VARS;
        float acc[32];
        uint4 A[32], xr[4];
        const uint4* os = g_o + ((c * 8 + slab) * 32) * 32 + lane;
        uint4* xp = g_xraw + ((c * 8 + slab) * 32 + 4 * j) * 32 + lane;
        load_pk<4>(xr, xp);
        load_pk<4>(A, os);
        ensure_pk<4>(A, os, tag);
        TS(6 + 20 * L);
        load_pk<28>(A + 4, os + 128);
        static_for<0, 8>([&](auto I) {
          constexpr int kb = I.value;
          if constexpr ((kb & 1) == 0) cons_acquire<ST_WO + kb / 2>(sbase, L);
          if constexpr (kb > 0) ensure_pk<4>(A + 4 * kb, os + kb * 128, tag);
          wg_fence();
          static_for<0, 4>([&](auto K) {
            constexpr int k = K.value;
            wgmma_n64<kb == 0 && k == 0, 0>(acc, A[4 * kb + k], st_desc<ST_WO + kb / 2, 2048, 8192, 1024, 1>(4 * (kb & 1) + k));
          });
          wg_commit();
          if constexpr ((kb & 1) == 0 && kb > 0) { wg_wait<1>(); cons_release<ST_WO + kb / 2 - 1>(sbase, lane); }
        });
        wg_wait<0>();
        TS(7 + 20 * L);
        fence_acc(acc);
#pragma unroll
        for (int k = 0; k < 32; k++) keep(A[k]);
        cons_release<ST_WO + 3>(sbase, lane);
        ensure_pk<4>(xr, xp, 1u);
#pragma unroll
        for (int i = 0; i < 4; i++) {
          acc[8 * i + 0] += bf_lo(xr[i].x); acc[8 * i + 1] += bf_hi(xr[i].x); acc[8 * i + 2] += bf_lo(xr[i].y); acc[8 * i + 3] += bf_hi(xr[i].y);
          acc[8 * i + 4] += bf_lo(xr[i].z); acc[8 * i + 5] += bf_hi(xr[i].z); acc[8 * i + 6] += bf_lo(xr[i].w); acc[8 * i + 7] += bf_hi(xr[i].w);
        }
        uint4 st = local_stats(acc);
        st.x = set_tag(st.x, tag);
        if (qc == 0) st_ll(g_stats + ((c * 8 + slab) * 8 + j) * 8 + qr, st);
#pragma unroll
        for (int i = 0; i < 4; i++) {
          x1own[i] = pack8(&acc[8 * i]);
          x1own[i].x = set_tag(x1own[i].x, 0u);
          st_ll(xp + i * 32, x1own[i]);
        }
      }
      TS(8 + 20 * L);
      if (L == 0) { STOP_AT(2); } else { STOP_AT(12); }
      uint4 hs[14];
      {
        PHASE_VARS;
        float acc[128];
        uint4 A[3][4];
        const uint4* xs = g_xraw + ((c * 8 + slab) * 32) * 32 + lane;
        const uint4* sp = g_stats + ((c * 8 + slab) * 8 + 2 * qc) * 8 + qr;
        const uint32_t sm = areg + t128 * 16;
        uint32_t rl2, rh2, bl2, bh2;
        float cl, ch;
        auto xsrc = [&](int p) { return xs + ((j + p) & 7) * 128; };
        {
          uint4 p[2];
#pragma unroll
          for (int k = 0; k < 4; k++) A[0][k] = x1own[k];
          p[0] = ld_ll(sp); p[1] = ld_ll(sp + 8);
          load_pk<4>(A[1], xsrc(1));
          for (uint32_t n = 0; !ok_pk<2>(p, tag) && n < SPIN_LIMIT; n++) { p[0] = ld_ll(sp); p[1] = ld_ll(sp + 8); }
          TS(9 + 20 * L);
          float ml, rl, mh, rh;
          combine_stats(p[0], p[1], ml, rl, mh, rh);
          rl2 = pack2(rl, rl); rh2 = pack2(rh, rh);
          const float rlb = bf_lo(rl2), rhb = bf_lo(rh2);
          bl2 = pack2(-ml * rlb, -ml * rlb); bh2 = pack2(-mh * rhb, -mh * rhb);
          cl = rl / rlb; cl *= cl; ch = rh / rhb; ch *= ch;
        }
        auto normalise = [&](uint4 (&xb)[4], int kb) {
#pragma unroll
          for (int k = 0; k < 4; k++) {
            xb[k].x = hfma2(xb[k].x, rl2, bl2); xb[k].y = hfma2(xb[k].y, rh2, bh2);
            xb[k].z = hfma2(xb[k].z, rl2, bl2); xb[k].w = hfma2(xb[k].w, rh2, bh2);
            sts128(sm + (kb * 4 + k) * 2048, xb[k]);
          }
        };
        normalise(A[0], 0);
        static_for<0, 8>([&](auto I) {
          constexpr int kb = I.value;
          cons_acquire<ST_G1 + kb>(sbase, L);
          wg_fence();
          static_for<0, 4>([&](auto K) { constexpr int k = K.value; wgmma_n256<kb == 0 && k == 0, 0>(acc, A[kb % 3][k], st_desc<ST_G1 + kb, 2048, 8192, 1024, 1>(k)); });
          wg_commit();
          if constexpr (kb > 0) {
            wg_wait<1>();
            keep4(A[(kb + 2) % 3]);
            cons_release<ST_G1 + kb - 1>(sbase, lane);
          }
          if constexpr (kb + 1 < 8) ensure_pk<4>(A[(kb + 1) % 3], xsrc(kb + 1), 0u);
          if constexpr (kb + 2 < 8) load_pk<4>(A[(kb + 2) % 3], xsrc(kb + 2));
          if constexpr (kb + 1 < 8) normalise(A[(kb + 1) % 3], kb + 1);
        });
        wg_wait<0>();
        TS(10 + 20 * L);
        fence_acc(acc);
        keep4(A[1]);
        cons_release<ST_G1 + 7>(sbase, lane);
        uint4 B[2][4];
#pragma unroll
        for (int k = 0; k < 4; k++) B[0][k] = lds128(sm + k * 2048);
#pragma unroll
        for (int s = 0; s < 8; s++) hs[s] = glu8<32>(&acc[64 * (s >> 2) + 8 * (s & 3)], cl, ch);
        float acc2[96];
        const uint32_t hdst = mapa(sm, cbit ^ 1);
        const uint32_t hbar1 = mapa(bars + BAR_HRECV + 16 * g, cbit ^ 1);
        if (t128 == 0) { mbar_expect_tx(bars + BAR_HRECV + 16 * g, 8 * 2048); mbar_expect_tx(bars + BAR_HRECV + 16 * g + 8, 6 * 2048); }
        static_for<0, 8>([&](auto I) {
          constexpr int kb = I.value;
          cons_acquire<ST_G2 + kb>(sbase, L);
          wg_fence();
          static_for<0, 4>([&](auto K) {
            constexpr int k = K.value;
            wgmma_n128<kb == 0 && k == 0, 0>(acc2, B[kb & 1][k], st_desc<ST_G2 + kb, 2048, 8192, 1024, 1>(k));
            wgmma_n64<kb == 0 && k == 0, 64>(acc2, B[kb & 1][k], st_desc<ST_G2 + kb, 1024, 4096, 512, 2>(k) + (16384 >> 4));
          });
          wg_commit();
          if constexpr (kb > 0) {
            wg_wait<1>();
            keep4(B[(kb + 1) & 1]);
            cons_release<ST_G2 + kb - 1>(sbase, lane);
          }
          if constexpr (kb + 1 < 8) {
#pragma unroll
            for (int k = 0; k < 4; k++) B[(kb + 1) & 1][k] = lds128(sm + ((kb + 1) * 4 + k) * 2048);
          }
          if constexpr (kb == 3) {
            __syncwarp();
            if (lane == 0) mbar_arrive_remote(mapa(bars + BAR_HREADY + 8 * g, cbit ^ 1));
          }
          if constexpr (kb >= 4) {
            if constexpr (kb == 4) mbar_wait(bars + BAR_HREADY + 8 * g, L);
            st_async128(hdst + (2 * kb - 8) * 2048, hs[2 * kb - 8], hbar1);
            st_async128(hdst + (2 * kb - 7) * 2048, hs[2 * kb - 7], hbar1);
          }
        });
        wg_wait<0>();
        TS(11 + 20 * L);
        fence_acc(acc2);
        keep4(B[1]);
        cons_release<ST_G2 + 7>(sbase, lane);
#pragma unroll
        for (int s = 0; s < 4; s++) hs[8 + s] = glu8<32>(&acc2[8 * s], cl, ch);
#pragma unroll
        for (int s = 0; s < 2; s++) hs[12 + s] = glu8<16>(&acc2[64 + 8 * s], cl, ch);
      }
      {
        PHASE_VARS;
        TS(12 + 20 * L);
        const uint32_t hdst = mapa(areg + t128 * 16, cbit ^ 1);
        const uint32_t hbar2 = mapa(bars + BAR_HRECV + 16 * g + 8, cbit ^ 1);
        uint4* pd = g_part + ((((c * 8 + slab) * 2 + cbit) * 4 + ca) * 16) * 32 + lane;
        const uint4* ps = g_part + ((((c * 8 + j) * 2 + g) * 4) * 16 + 4 * w) * 32 + lane;
        auto fetch_partials = [&]() {
#pragma unroll
          for (int src = 0; src < 4; src++)
#pragma unroll
            for (int k = 0; k < 4; k++) cp_async16(areg + t128 * 16 + (14 + 4 * src + k) * 2048, ps + src * (16 * 32) + k * 32);
        };
        uint4 hb[7];
        float a0[32], a1[32], a2[32], a3[32];
        auto publish = [&](float (&a)[32], int q, int s0, int s1) {
#pragma unroll
          for (int s = s0; s < s1; s++) {
            uint4 o = pack8(&a[8 * s]);
            o.x = set_tag(o.x, tag);
            st_ll(pd + (4 * q + s) * 32, o);
          }
        };
        static_for<0, 16>([&](auto I) {
          constexpr int i = I.value, q = dn_q(i), par = dn_par(i), kh = dn_kh(i);
          auto mm = [&](auto K) {
            constexpr int k = decltype(K)::value;
            constexpr bool init = (k == 0 && par == 0 && kh == 0);
            constexpr uint64_t db = st_desc<ST_DN + i, 2048, 8192, 1024, 1>(k);
            if constexpr (q == 0) { if constexpr (par) wgmma_n64<init, 0>(a0, hb[k], db); else wgmma_n64<init, 0>(a0, hs[7 * kh + k], db); }
            if constexpr (q == 1) { if constexpr (par) wgmma_n64<init, 0>(a1, hb[k], db); else wgmma_n64<init, 0>(a1, hs[7 * kh + k], db); }
            if constexpr (q == 2) { if constexpr (par) wgmma_n64<init, 0>(a2, hb[k], db); else wgmma_n64<init, 0>(a2, hs[7 * kh + k], db); }
            if constexpr (q == 3) { if constexpr (par) wgmma_n64<init, 0>(a3, hb[k], db); else wgmma_n64<init, 0>(a3, hs[7 * kh + k], db); }
          };
          cons_acquire<ST_DN + i>(sbase, L);
          wg_fence();
          mm(IC<0>{}); mm(IC<1>{}); mm(IC<2>{}); mm(IC<3>{}); mm(IC<4>{}); mm(IC<5>{}); mm(IC<6>{});
          wg_commit();
          if constexpr (i > 0) { wg_wait<1>(); cons_release<ST_DN + i - 1>(sbase, lane); }
          if constexpr (i < 3) {
            st_async128(hdst + (8 + 2 * i) * 2048, hs[8 + 2 * i], hbar2);
            st_async128(hdst + (9 + 2 * i) * 2048, hs[9 + 2 * i], hbar2);
          }
          constexpr int n = i + 1;
          if constexpr (n < 16 && dn_par(n) && n != 4 && n != 7) {
            if constexpr (n == 2) { mbar_wait(bars + BAR_HRECV + 16 * g, L); TS(13 + 20 * L); }
            if constexpr (n == 6) { mbar_wait(bars + BAR_HRECV + 16 * g + 8, L); TS(14 + 20 * L); }
#pragma unroll
            for (int k = 0; k < 7; k++) { if constexpr (n != 2) keep(hb[k]); hb[k] = lds128(areg + t128 * 16 + (7 * dn_kh(n) + k) * 2048); }
          }
          if constexpr (i == 7) { fence_acc(a0); publish(a0, 0, 0, 4); }
          if constexpr (i == 8) { fence_acc(a1); publish(a1, 1, 0, 2); }
          if constexpr (i == 9) publish(a1, 1, 2, 4);
          if constexpr (i == 12) { fence_acc(a2); publish(a2, 2, 0, 2); }
          if constexpr (i == 13) publish(a2, 2, 2, 4);
          if constexpr (i == 10) { if (w == 0) fetch_partials(); }
          if constexpr (i == 12) { if (w == 1) fetch_partials(); }
        });
        wg_wait<0>();
        TS(15 + 20 * L);
        fence_acc(a3);
#pragma unroll
        for (int k = 0; k < 7; k++) { keep(hb[k]); keep(hs[7 + k]); }
        cons_release<NSTAGE - 1>(sbase, lane);
        publish(a3, 3, 0, 4);
        if (w >= 2) fetch_partials();
      }
      {
        PHASE_VARS;
        const uint4* xq = g_xraw + ((c * 8 + j) * 32 + 4 * warp) * 32 + lane;
        const uint4* ps = g_part + ((((c * 8 + j) * 2 + g) * 4) * 16 + 4 * w) * 32 + lane;
        uint4 xr[4], P[4][4];
        float v[32];
        load_pk<4>(xr, xq);
        cp_wait_all();
#pragma unroll
        for (int k = 0; k < 16; k++) P[k >> 2][k & 3] = lds128(areg + t128 * 16 + (14 + k) * 2048);
        for (uint32_t n = 0; !ok_pk<16>(&P[0][0], tag) && n < SPIN_LIMIT; n++) {
#pragma unroll
          for (int src = 0; src < 4; src++) load_pk<4>(P[src], ps + src * (16 * 32));
        }
        TS(16 + 20 * L);
        ensure_pk<4>(xr, xq, 0u);
#pragma unroll
        for (int i = 0; i < 4; i++) {
          v[8 * i + 0] = bf_lo(xr[i].x); v[8 * i + 1] = bf_hi(xr[i].x); v[8 * i + 2] = bf_lo(xr[i].y); v[8 * i + 3] = bf_hi(xr[i].y);
          v[8 * i + 4] = bf_lo(xr[i].z); v[8 * i + 5] = bf_hi(xr[i].z); v[8 * i + 6] = bf_lo(xr[i].w); v[8 * i + 7] = bf_hi(xr[i].w);
          float d[8] = {0, 0, 0, 0, 0, 0, 0, 0};
#pragma unroll
          for (int src = 0; src < 4; src++) {
            const uint4 p = P[src][i];
            d[0] += bf_lo(p.x); d[1] += bf_hi(p.x); d[2] += bf_lo(p.y); d[3] += bf_hi(p.y);
            d[4] += bf_lo(p.z); d[5] += bf_hi(p.z); d[6] += bf_lo(p.w); d[7] += bf_hi(p.w);
          }
#pragma unroll
          for (int k = 0; k < 8; k++) v[8 * i + k] += d[k];
        }
        if (L == 0) {
          owner_ln_publish(sbase, v, 1u, 0u, xraw);
        } else {
#pragma unroll
          for (int i = 0; i < 4; i++) xraw[i] = make_uint4(0, 0, 0, 0);
          uint32_t* op = reinterpret_cast<uint32_t*>(out + (size_t)(slab_row0(c, j >> 2, j & 3) + 2 * qr) * 512 + warp * 64 + qc * 2);
#pragma unroll
          for (int i = 0; i < 4; i++) {
            op[i * 8] = pack2(v[8 * i], v[8 * i + 1]);
            op[16 * 256 + i * 8] = pack2(v[8 * i + 2], v[8 * i + 3]);
            op[i * 8 + 4] = pack2(v[8 * i + 4], v[8 * i + 5]);
            op[16 * 256 + i * 8 + 4] = pack2(v[8 * i + 6], v[8 * i + 7]);
          }
        }
      }
      TS(17 + 20 * L);
      if (L == 0) { STOP_AT(3); }
    }
    TG(62);
    asm volatile("barrier.cluster.arrive.release.aligned;\nbarrier.cluster.wait.acquire.aligned; // consumer" ::: "memory");
    TG(63);
  }
}

typedef CUresult (*EncodeFn)(CUtensorMap*, CUtensorMapDataType, cuuint32_t, void*, const cuuint64_t*, const cuuint64_t*,
                             const cuuint32_t*, const cuuint32_t*, CUtensorMapInterleave, CUtensorMapSwizzle,
                             CUtensorMapL2promotion, CUtensorMapFloatOOBfill);

void encode(EncodeFn fn, CUtensorMap* m, int rank, const void* base, const cuuint64_t* dims, const cuuint64_t* strides,
            const cuuint32_t* box, CUtensorMapSwizzle sw) {
  cuuint32_t es[5] = {1, 1, 1, 1, 1};
  fn(m, CU_TENSOR_MAP_DATA_TYPE_BFLOAT16, (cuuint32_t)rank, const_cast<void*>(base), dims, strides, box, es,
     CU_TENSOR_MAP_INTERLEAVE_NONE, sw, CU_TENSOR_MAP_L2_PROMOTION_L2_128B, CU_TENSOR_MAP_FLOAT_OOB_FILL_NONE);
}

}

extern "C" void kernel_launch(void* const* d_in, const int* in_sizes, int n_in, void* d_out, int out_size) {
  (void)in_sizes; (void)n_in; (void)out_size;
  const __nv_bfloat16* x = (const __nv_bfloat16*)d_in[0];
  const char* wqkv = (const char*)d_in[1];
  const char* wo = (const char*)d_in[2];
  const char* wg = (const char*)d_in[4];
  const char* wu = (const char*)d_in[5];
  const char* wd = (const char*)d_in[6];

  static EncodeFn fn = nullptr;
  if (!fn) {
    void* p = nullptr;
    cudaDriverEntryPointQueryResult st;
    cudaGetDriverEntryPoint("cuTensorMapEncodeTiled", &p, cudaEnableDefault, &st);
    fn = (EncodeFn)p;
    cudaFuncSetAttribute(fused_kernel, cudaFuncAttributeMaxDynamicSharedMemorySize, SMEM_BYTES);
  }
  CUtensorMap m_qkv, m_wo, m_gu2, m_gu1, m_guh, m_wd112, m_wd80, m_wd32;
  {
    cuuint64_t dims[3] = {512, 512, 3}, str[2] = {3072, 1024};
    cuuint32_t box[3] = {64, 64, 3};
    encode(fn, &m_qkv, 3, wqkv, dims, str, box, CU_TENSOR_MAP_SWIZZLE_128B);
  }
  {
    cuuint64_t dims[2] = {512, 512}, str[1] = {1024};
    cuuint32_t box[2] = {64, 128};
    encode(fn, &m_wo, 2, wo, dims, str, box, CU_TENSOR_MAP_SWIZZLE_128B);
  }
  {
    const char* lo = wg < wu ? wg : wu;
    cuuint64_t diff = (cuuint64_t)(wg < wu ? wu - wg : wg - wu);
    cuuint64_t dims[4] = {1792, 512, 2, 2}, str[3] = {3584, diff, 128};
    cuuint32_t box2[4] = {64, 64, 2, 2}, box1[4] = {64, 64, 2, 1}, boxh[3] = {32, 64, 2};
    encode(fn, &m_gu2, 4, lo, dims, str, box2, CU_TENSOR_MAP_SWIZZLE_128B);
    encode(fn, &m_gu1, 4, lo, dims, str, box1, CU_TENSOR_MAP_SWIZZLE_128B);
    encode(fn, &m_guh, 3, lo, dims, str, boxh, CU_TENSOR_MAP_SWIZZLE_64B);
  }
  {
    cuuint64_t dims[2] = {512, 1792}, str[1] = {1024};
    cuuint32_t b112[2] = {64, 112}, b80[2] = {64, 80}, b32[2] = {64, 32};
    encode(fn, &m_wd112, 2, wd, dims, str, b112, CU_TENSOR_MAP_SWIZZLE_128B);
    encode(fn, &m_wd80, 2, wd, dims, str, b80, CU_TENSOR_MAP_SWIZZLE_128B);
    encode(fn, &m_wd32, 2, wd, dims, str, b32, CU_TENSOR_MAP_SWIZZLE_128B);
  }
  cudaLaunchConfig_t cfg = {};
  cfg.gridDim = dim3(128);
  cfg.blockDim = dim3(NTHREADS);
  cfg.dynamicSmemBytes = SMEM_BYTES;
  cfg.stream = cudaStreamPerThread;
  cudaLaunchAttribute at[1];
  at[0].id = cudaLaunchAttributeClusterDimension;
  at[0].val.clusterDim.x = 2; at[0].val.clusterDim.y = 1; at[0].val.clusterDim.z = 1;
  cfg.attrs = at; cfg.numAttrs = 1;
  cudaLaunchKernelEx(&cfg, fused_kernel, m_qkv, m_wo, m_gu2, m_gu1, m_guh, m_wd112, m_wd80, m_wd32, x, (__nv_bfloat16*)d_out, wo, wg, wu, wd
  );
}
```

```cpp
#include <cuda_runtime.h>
#include <cuda_bf16.h>
#include <cuda.h>
#include <stdint.h>

namespace {

constexpr int NTHREADS = 384;
constexpr int GRAN = 8192;
constexpr int NGRAN = 12;
constexpr int SM_AREG = NGRAN * GRAN;
constexpr int SM_MISC = SM_AREG + 131072;
constexpr int SM_TSTAT = SM_MISC + 256;
constexpr int SMEM_BYTES = SM_TSTAT + 1024;
constexpr int BAR_FULL = 0, BAR_EMPTY = 96, BAR_HRECV = 192, BAR_HREADY = 224;

constexpr int AR_XN = 0, AR_XRAW = 8192, AR_O = 16384, AR_STATS = 24576, AR_HALO = 25088, AR_PART = 33280, ARENA = 66048;
__device__ __align__(1024) uint4 g_arena[16 * ARENA];

#define TS(n)
#define TG(n)
#define OPAQUE(x) asm volatile("" : "+r"(x))
#define PHASE_VARS                                                                                   \
  int tid_ = threadIdx.x, bid_ = blockIdx.x;                                                         \
  OPAQUE(tid_); OPAQUE(bid_);                                                                        \
  const int lane = tid_ & 31, warp = tid_ >> 5, g = warp >> 2, w = warp & 3, t128 = tid_ & 127;      \
  const int qr = lane >> 2, qc = lane & 3, slab = warp;                                              \
  const int c = bid_ >> 3, j = bid_ & 7, ca = j >> 1, cbit = j & 1;                                  \
  const uint32_t areg = sbase + SM_AREG + g * 65536;                                                 \
  (void)g; (void)j; (void)w; (void)t128; (void)qr; (void)qc; (void)slab; (void)c; (void)ca; (void)cbit; (void)areg; (void)lane
#define STOP_AT(n)
#define PSTOP_AT(n)

__device__ __forceinline__ uint32_t smem_u32(const void* p) { return (uint32_t)__cvta_generic_to_shared(p); }
__device__ __forceinline__ void mbar_init(uint32_t bar, uint32_t cnt) {
  asm volatile("mbarrier.init.shared::cta.b64 [%0], %1;" ::"r"(bar), "r"(cnt) : "memory");
}
__device__ __forceinline__ void mbar_expect_tx(uint32_t bar, uint32_t bytes) {
  asm volatile("mbarrier.arrive.expect_tx.shared::cta.b64 _, [%0], %1;" ::"r"(bar), "r"(bytes) : "memory");
}
__device__ __forceinline__ void mbar_arrive(uint32_t bar) {
  asm volatile("mbarrier.arrive.shared::cta.b64 _, [%0];" ::"r"(bar) : "memory");
}
__device__ __forceinline__ void mbar_arrive_remote(uint32_t cluster_addr) {
  asm volatile("mbarrier.arrive.relaxed.cluster.shared::cluster.b64 _, [%0];" ::"r"(cluster_addr) : "memory");
}
__device__ __forceinline__ bool mbar_try(uint32_t bar, uint32_t parity) {
  uint32_t ok;
  asm volatile("{\n.reg .pred p;\nmbarrier.try_wait.parity.shared::cta.b64 p, [%1], %2;\nselp.u32 %0, 1, 0, p;\n}"
               : "=r"(ok) : "r"(bar), "r"(parity) : "memory");
  return ok != 0;
}
constexpr uint32_t SPIN_LIMIT = 1u << 16;
constexpr uint32_t SMEM_ORIGIN = 1024;
__device__ __forceinline__ void mbar_wait(uint32_t bar, uint32_t parity) {
  for (uint32_t n = 0; !mbar_try(bar, parity) && n < SPIN_LIMIT; n++) {}
}
__device__ __forceinline__ uint32_t mapa(uint32_t addr, uint32_t rank) {
  uint32_t r;
  asm volatile("mapa.shared::cluster.u32 %0, %1, %2;" : "=r"(r) : "r"(addr), "r"(rank));
  return r;
}

__device__ __forceinline__ void tma_2d(uint32_t dst, const CUtensorMap* m, uint32_t bar, int c0, int c1) {
  asm volatile("cp.async.bulk.tensor.2d.shared::cluster.global.mbarrier::complete_tx::bytes [%0], [%1, {%3, %4}], [%2];"
               ::"r"(dst), "l"(m), "r"(bar), "r"(c0), "r"(c1) : "memory");
}
__device__ __forceinline__ void tma_3d(uint32_t dst, const CUtensorMap* m, uint32_t bar, int c0, int c1, int c2) {
  asm volatile("cp.async.bulk.tensor.3d.shared::cluster.global.mbarrier::complete_tx::bytes [%0], [%1, {%3, %4, %5}], [%2];"
               ::"r"(dst), "l"(m), "r"(bar), "r"(c0), "r"(c1), "r"(c2) : "memory");
}
__device__ __forceinline__ void tma_4d(uint32_t dst, const CUtensorMap* m, uint32_t bar, int c0, int c1, int c2, int c3) {
  asm volatile("cp.async.bulk.tensor.4d.shared::cluster.global.mbarrier::complete_tx::bytes [%0], [%1, {%3, %4, %5, %6}], [%2];"
               ::"r"(dst), "l"(m), "r"(bar), "r"(c0), "r"(c1), "r"(c2), "r"(c3) : "memory");
}
__device__ __forceinline__ void l2_prefetch(const void* p, uint32_t bytes) {
  asm volatile("cp.async.bulk.prefetch.L2.global [%0], %1;" ::"l"(p), "r"(bytes) : "memory");
}

__device__ __forceinline__ uint4 ld_ll(const uint4* p) {
  uint4 v;
  asm volatile("ld.relaxed.gpu.global.v4.u32 {%0,%1,%2,%3}, [%4];" : "=r"(v.x), "=r"(v.y), "=r"(v.z), "=r"(v.w) : "l"(p) : "memory");
  return v;
}
__device__ __forceinline__ void st_ll(uint4* p, uint4 v) {
  asm volatile("st.relaxed.gpu.global.v4.u32 [%0], {%1,%2,%3,%4};" ::"l"(p), "r"(v.x), "r"(v.y), "r"(v.z), "r"(v.w) : "memory");
}
__device__ __forceinline__ uint4 lds128(uint32_t a) {
  uint4 v;
  asm volatile("ld.shared.v4.u32 {%0,%1,%2,%3}, [%4];" : "=r"(v.x), "=r"(v.y), "=r"(v.z), "=r"(v.w) : "r"(a) : "memory");
  return v;
}
__device__ __forceinline__ void sts128(uint32_t a, uint4 v) {
  asm volatile("st.shared.v4.u32 [%0], {%1,%2,%3,%4};" ::"r"(a), "r"(v.x), "r"(v.y), "r"(v.z), "r"(v.w) : "memory");
}
__device__ __forceinline__ void st_async128(uint32_t cluster_addr, uint4 v, uint32_t cluster_bar) {
  asm volatile("st.async.weak.shared::cluster.mbarrier::complete_tx::bytes.v4.b32 [%0], {%1,%2,%3,%4}, [%5];"
               ::"r"(cluster_addr), "r"(v.x), "r"(v.y), "r"(v.z), "r"(v.w), "r"(cluster_bar) : "memory");
}
__device__ __forceinline__ uint32_t pack2(float lo, float hi) {
  uint32_t r;
  asm("cvt.rn.bf16x2.f32 %0, %1, %2;" : "=r"(r) : "f"(hi), "f"(lo));
  return r;
}
__device__ __forceinline__ float bf_lo(uint32_t w) { return __uint_as_float(w << 16); }
__device__ __forceinline__ float bf_hi(uint32_t w) { return __uint_as_float(w & 0xffff0000u); }
__device__ __forceinline__ uint32_t set_tag(uint32_t w, uint32_t tag) { return (w & ~1u) | tag; }
__device__ __forceinline__ uint32_t movm(uint32_t a) {
  uint32_t d;
  asm("movmatrix.sync.aligned.m8n8.trans.b16 %0, %1;" : "=r"(d) : "r"(a));
  return d;
}
__device__ __forceinline__ void mma16816(float (&d)[4], const uint4& a, uint32_t b0, uint32_t b1) {
  asm("mma.sync.aligned.m16n8k16.row.col.f32.bf16.bf16.f32 {%0,%1,%2,%3}, {%4,%5,%6,%7}, {%8,%9}, {%0,%1,%2,%3};"
               : "+f"(d[0]), "+f"(d[1]), "+f"(d[2]), "+f"(d[3])
               : "r"(a.x), "r"(a.y), "r"(a.z), "r"(a.w), "r"(b0), "r"(b1));
}
__device__ __forceinline__ void mma1688(float (&d)[4], uint32_t a0, uint32_t a1, uint32_t b0) {
  asm("mma.sync.aligned.m16n8k8.row.col.f32.bf16.bf16.f32 {%0,%1,%2,%3}, {%4,%5}, {%6}, {%0,%1,%2,%3};"
      : "+f"(d[0]), "+f"(d[1]), "+f"(d[2]), "+f"(d[3])
      : "r"(a0), "r"(a1), "r"(b0));
}
__device__ __forceinline__ void mma16816_z(float (&d)[4], const uint4& a, uint32_t b0, uint32_t b1) {
  asm("mma.sync.aligned.m16n8k16.row.col.f32.bf16.bf16.f32 {%0,%1,%2,%3}, {%4,%5,%6,%7}, {%8,%9}, {%10,%10,%10,%10};"
      : "=f"(d[0]), "=f"(d[1]), "=f"(d[2]), "=f"(d[3])
      : "r"(a.x), "r"(a.y), "r"(a.z), "r"(a.w), "r"(b0), "r"(b1), "f"(0.f));
}
__device__ __forceinline__ float ex2(float x) {
  float y;
  asm("ex2.approx.ftz.f32 %0, %1;" : "=f"(y) : "f"(x));
  return y;
}
__device__ __forceinline__ float rcp(float x) {
  float y;
  asm("rcp.approx.ftz.f32 %0, %1;" : "=f"(y) : "f"(x));
  return y;
}
__device__ __forceinline__ void cp_async16(uint32_t dst, const void* src) {
  asm volatile("cp.async.cg.shared.global [%0], [%1], 16;" ::"r"(dst), "l"(src) : "memory");
}
__device__ __forceinline__ void cp_wait_all() { asm volatile("cp.async.wait_all;" ::: "memory"); }
__device__ __forceinline__ void cp_commit() { asm volatile("cp.async.commit_group;" ::: "memory"); }
template <int N> __device__ __forceinline__ void cp_wait() { asm volatile("cp.async.wait_group %0;" ::"n"(N) : "memory"); }
__device__ __forceinline__ void bar_wg(int id) { asm volatile("bar.sync %0, 128;" ::"r"(id) : "memory"); }
__device__ __forceinline__ void wg_fence() { asm volatile("wgmma.fence.sync.aligned;" ::: "memory"); }
__device__ __forceinline__ void wg_commit() { asm volatile("wgmma.commit_group.sync.aligned;" ::: "memory"); }
template <int N> __device__ __forceinline__ void wg_wait() { asm volatile("wgmma.wait_group.sync.aligned %0;" ::"n"(N) : "memory"); }
__device__ __forceinline__ void keep(const uint4& a) { asm volatile("" ::"r"(a.x), "r"(a.y), "r"(a.z), "r"(a.w) : "memory"); }
template <int T> __device__ __forceinline__ void zero_acc(float (&d)[T]) {
#pragma unroll
  for (int i = 0; i < T; i++) d[i] = 0.f;
}
template <int T> __device__ __forceinline__ void fence_acc(float (&d)[T]) {
#pragma unroll
  for (int i = 0; i < T; i++) asm volatile("" : "+f"(d[i])::"memory");
}

template <int O, int T> __device__ __forceinline__ void wgmma_rs_n64(float (&d)[T], const uint4& a, uint64_t db) {
  asm volatile("{\n.reg .pred p;\nsetp.ne.b32 p, 1, 0;\n"
    "wgmma.mma_async.sync.aligned.m64n64k16.f32.bf16.bf16 "
    "{%0, %1, %2, %3, %4, %5, %6, %7, %8, %9, %10, %11, %12, %13, %14, %15, "
    "%16, %17, %18, %19, %20, %21, %22, %23, %24, %25, %26, %27, %28, %29, %30, %31}, "
    "{%32, %33, %34, %35}, %36, p, 1, 1, 1;\n}\n"
    : "+f"(d[O + 0]), "+f"(d[O + 1]), "+f"(d[O + 2]), "+f"(d[O + 3]), "+f"(d[O + 4]), "+f"(d[O + 5]), "+f"(d[O + 6]), "+f"(d[O + 7]),
      "+f"(d[O + 8]), "+f"(d[O + 9]), "+f"(d[O + 10]), "+f"(d[O + 11]), "+f"(d[O + 12]), "+f"(d[O + 13]), "+f"(d[O + 14]), "+f"(d[O + 15]),
      "+f"(d[O + 16]), "+f"(d[O + 17]), "+f"(d[O + 18]), "+f"(d[O + 19]), "+f"(d[O + 20]), "+f"(d[O + 21]), "+f"(d[O + 22]), "+f"(d[O + 23]),
      "+f"(d[O + 24]), "+f"(d[O + 25]), "+f"(d[O + 26]), "+f"(d[O + 27]), "+f"(d[O + 28]), "+f"(d[O + 29]), "+f"(d[O + 30]), "+f"(d[O + 31])
    : "r"(a.x), "r"(a.y), "r"(a.z), "r"(a.w), "l"(db));
}
template <int O, int T> __device__ __forceinline__ void wgmma_rs_n64_init(float (&d)[T], const uint4& a, uint64_t db) {
  asm volatile("{\n.reg .pred p;\nsetp.ne.b32 p, 0, 0;\n"
    "wgmma.mma_async.sync.aligned.m64n64k16.f32.bf16.bf16 "
    "{%0, %1, %2, %3, %4, %5, %6, %7, %8, %9, %10, %11, %12, %13, %14, %15, "
    "%16, %17, %18, %19, %20, %21, %22, %23, %24, %25, %26, %27, %28, %29, %30, %31}, "
    "{%32, %33, %34, %35}, %36, p, 1, 1, 1;\n}\n"
    : "=f"(d[O + 0]), "=f"(d[O + 1]), "=f"(d[O + 2]), "=f"(d[O + 3]), "=f"(d[O + 4]), "=f"(d[O + 5]), "=f"(d[O + 6]), "=f"(d[O + 7]),
      "=f"(d[O + 8]), "=f"(d[O + 9]), "=f"(d[O + 10]), "=f"(d[O + 11]), "=f"(d[O + 12]), "=f"(d[O + 13]), "=f"(d[O + 14]), "=f"(d[O + 15]),
      "=f"(d[O + 16]), "=f"(d[O + 17]), "=f"(d[O + 18]), "=f"(d[O + 19]), "=f"(d[O + 20]), "=f"(d[O + 21]), "=f"(d[O + 22]), "=f"(d[O + 23]),
      "=f"(d[O + 24]), "=f"(d[O + 25]), "=f"(d[O + 26]), "=f"(d[O + 27]), "=f"(d[O + 28]), "=f"(d[O + 29]), "=f"(d[O + 30]), "=f"(d[O + 31])
    : "r"(a.x), "r"(a.y), "r"(a.z), "r"(a.w), "l"(db));
}
template <bool INIT, int O, int T> __device__ __forceinline__ void wgmma_n64(float (&d)[T], const uint4& a, uint64_t db) {
  if constexpr (INIT) wgmma_rs_n64_init<O>(d, a, db); else wgmma_rs_n64<O>(d, a, db);
}
template <int O, int T> __device__ __forceinline__ void wgmma_rs_n128(float (&d)[T], const uint4& a, uint64_t db) {
  asm volatile("{\n.reg .pred p;\nsetp.ne.b32 p, 1, 0;\n"
    "wgmma.mma_async.sync.aligned.m64n128k16.f32.bf16.bf16 "
    "{%0, %1, %2, %3, %4, %5, %6, %7, %8, %9, %10, %11, %12, %13, %14, %15, "
    "%16, %17, %18, %19, %20, %21, %22, %23, %24, %25, %26, %27, %28, %29, %30, %31, "
    "%32, %33, %34, %35, %36, %37, %38, %39, %40, %41, %42, %43, %44, %45, %46, %47, "
    "%48, %49, %50, %51, %52, %53, %54, %55, %56, %57, %58, %59, %60, %61, %62, %63}, "
    "{%64, %65, %66, %67}, %68, p, 1, 1, 1;\n}\n"
    : "+f"(d[O + 0]), "+f"(d[O + 1]), "+f"(d[O + 2]), "+f"(d[O + 3]), "+f"(d[O + 4]), "+f"(d[O + 5]), "+f"(d[O + 6]), "+f"(d[O + 7]),
      "+f"(d[O + 8]), "+f"(d[O + 9]), "+f"(d[O + 10]), "+f"(d[O + 11]), "+f"(d[O + 12]), "+f"(d[O + 13]), "+f"(d[O + 14]), "+f"(d[O + 15]),
      "+f"(d[O + 16]), "+f"(d[O + 17]), "+f"(d[O + 18]), "+f"(d[O + 19]), "+f"(d[O + 20]), "+f"(d[O + 21]), "+f"(d[O + 22]), "+f"(d[O + 23]),
      "+f"(d[O + 24]), "+f"(d[O + 25]), "+f"(d[O + 26]), "+f"(d[O + 27]), "+f"(d[O + 28]), "+f"(d[O + 29]), "+f"(d[O + 30]), "+f"(d[O + 31]),
      "+f"(d[O + 32]), "+f"(d[O + 33]), "+f"(d[O + 34]), "+f"(d[O + 35]), "+f"(d[O + 36]), "+f"(d[O + 37]), "+f"(d[O + 38]), "+f"(d[O + 39]),
      "+f"(d[O + 40]), "+f"(d[O + 41]), "+f"(d[O + 42]), "+f"(d[O + 43]), "+f"(d[O + 44]), "+f"(d[O + 45]), "+f"(d[O + 46]), "+f"(d[O + 47]),
      "+f"(d[O + 48]), "+f"(d[O + 49]), "+f"(d[O + 50]), "+f"(d[O + 51]), "+f"(d[O + 52]), "+f"(d[O + 53]), "+f"(d[O + 54]), "+f"(d[O + 55]),
      "+f"(d[O + 56]), "+f"(d[O + 57]), "+f"(d[O + 58]), "+f"(d[O + 59]), "+f"(d[O + 60]), "+f"(d[O + 61]), "+f"(d[O + 62]), "+f"(d[O + 63])
    : "r"(a.x), "r"(a.y), "r"(a.z), "r"(a.w), "l"(db));
}
template <int O, int T> __device__ __forceinline__ void wgmma_rs_n128_init(float (&d)[T], const uint4& a, uint64_t db) {
  asm volatile("{\n.reg .pred p;\nsetp.ne.b32 p, 0, 0;\n"
    "wgmma.mma_async.sync.aligned.m64n128k16.f32.bf16.bf16 "
    "{%0, %1, %2, %3, %4, %5, %6, %7, %8, %9, %10, %11, %12, %13, %14, %15, "
    "%16, %17, %18, %19, %20, %21, %22, %23, %24, %25, %26, %27, %28, %29, %30, %31, "
    "%32, %33, %34, %35, %36, %37, %38, %39, %40, %41, %42, %43, %44, %45, %46, %47, "
    "%48, %49, %50, %51, %52, %53, %54, %55, %56, %57, %58, %59, %60, %61, %62, %63}, "
    "{%64, %65, %66, %67}, %68, p, 1, 1, 1;\n}\n"
    : "=f"(d[O + 0]), "=f"(d[O + 1]), "=f"(d[O + 2]), "=f"(d[O + 3]), "=f"(d[O + 4]), "=f"(d[O + 5]), "=f"(d[O + 6]), "=f"(d[O + 7]),
      "=f"(d[O + 8]), "=f"(d[O + 9]), "=f"(d[O + 10]), "=f"(d[O + 11]), "=f"(d[O + 12]), "=f"(d[O + 13]), "=f"(d[O + 14]), "=f"(d[O + 15]),
      "=f"(d[O + 16]), "=f"(d[O + 17]), "=f"(d[O + 18]), "=f"(d[O + 19]), "=f"(d[O + 20]), "=f"(d[O + 21]), "=f"(d[O + 22]), "=f"(d[O + 23]),
      "=f"(d[O + 24]), "=f"(d[O + 25]), "=f"(d[O + 26]), "=f"(d[O + 27]), "=f"(d[O + 28]), "=f"(d[O + 29]), "=f"(d[O + 30]), "=f"(d[O + 31]),
      "=f"(d[O + 32]), "=f"(d[O + 33]), "=f"(d[O + 34]), "=f"(d[O + 35]), "=f"(d[O + 36]), "=f"(d[O + 37]), "=f"(d[O + 38]), "=f"(d[O + 39]),
      "=f"(d[O + 40]), "=f"(d[O + 41]), "=f"(d[O + 42]), "=f"(d[O + 43]), "=f"(d[O + 44]), "=f"(d[O + 45]), "=f"(d[O + 46]), "=f"(d[O + 47]),
      "=f"(d[O + 48]), "=f"(d[O + 49]), "=f"(d[O + 50]), "=f"(d[O + 51]), "=f"(d[O + 52]), "=f"(d[O + 53]), "=f"(d[O + 54]), "=f"(d[O + 55]),
      "=f"(d[O + 56]), "=f"(d[O + 57]), "=f"(d[O + 58]), "=f"(d[O + 59]), "=f"(d[O + 60]), "=f"(d[O + 61]), "=f"(d[O + 62]), "=f"(d[O + 63])
    : "r"(a.x), "r"(a.y), "r"(a.z), "r"(a.w), "l"(db));
}
template <bool INIT, int O, int T> __device__ __forceinline__ void wgmma_n128(float (&d)[T], const uint4& a, uint64_t db) {
  if constexpr (INIT) wgmma_rs_n128_init<O>(d, a, db); else wgmma_rs_n128<O>(d, a, db);
}
template <int O, int T> __device__ __forceinline__ void wgmma_rs_n192(float (&d)[T], const uint4& a, uint64_t db) {
  asm volatile("{\n.reg .pred p;\nsetp.ne.b32 p, 1, 0;\n"
    "wgmma.mma_async.sync.aligned.m64n192k16.f32.bf16.bf16 "
    "{%0, %1, %2, %3, %4, %5, %6, %7, %8, %9, %10, %11, %12, %13, %14, %15, "
    "%16, %17, %18, %19, %20, %21, %22, %23, %24, %25, %26, %27, %28, %29, %30, %31, "
    "%32, %33, %34, %35, %36, %37, %38, %39, %40, %41, %42, %43, %44, %45, %46, %47, "
    "%48, %49, %50, %51, %52, %53, %54, %55, %56, %57, %58, %59, %60, %61, %62, %63, "
    "%64, %65, %66, %67, %68, %69, %70, %71, %72, %73, %74, %75, %76, %77, %78, %79, "
    "%80, %81, %82, %83, %84, %85, %86, %87, %88, %89, %90, %91, %92, %93, %94, %95}, "
    "{%96, %97, %98, %99}, %100, p, 1, 1, 1;\n}\n"
    : "+f"(d[O + 0]), "+f"(d[O + 1]), "+f"(d[O + 2]), "+f"(d[O + 3]), "+f"(d[O + 4]), "+f"(d[O + 5]), "+f"(d[O + 6]), "+f"(d[O + 7]),
      "+f"(d[O + 8]), "+f"(d[O + 9]), "+f"(d[O + 10]), "+f"(d[O + 11]), "+f"(d[O + 12]), "+f"(d[O + 13]), "+f"(d[O + 14]), "+f"(d[O + 15]),
      "+f"(d[O + 16]), "+f"(d[O + 17]), "+f"(d[O + 18]), "+f"(d[O + 19]), "+f"(d[O + 20]), "+f"(d[O + 21]), "+f"(d[O + 22]), "+f"(d[O + 23]),
      "+f"(d[O + 24]), "+f"(d[O + 25]), "+f"(d[O + 26]), "+f"(d[O + 27]), "+f"(d[O + 28]), "+f"(d[O + 29]), "+f"(d[O + 30]), "+f"(d[O + 31]),
      "+f"(d[O + 32]), "+f"(d[O + 33]), "+f"(d[O + 34]), "+f"(d[O + 35]), "+f"(d[O + 36]), "+f"(d[O + 37]), "+f"(d[O + 38]), "+f"(d[O + 39]),
      "+f"(d[O + 40]), "+f"(d[O + 41]), "+f"(d[O + 42]), "+f"(d[O + 43]), "+f"(d[O + 44]), "+f"(d[O + 45]), "+f"(d[O + 46]), "+f"(d[O + 47]),
      "+f"(d[O + 48]), "+f"(d[O + 49]), "+f"(d[O + 50]), "+f"(d[O + 51]), "+f"(d[O + 52]), "+f"(d[O + 53]), "+f"(d[O + 54]), "+f"(d[O + 55]),
      "+f"(d[O + 56]), "+f"(d[O + 57]), "+f"(d[O + 58]), "+f"(d[O + 59]), "+f"(d[O + 60]), "+f"(d[O + 61]), "+f"(d[O + 62]), "+f"(d[O + 63]),
      "+f"(d[O + 64]), "+f"(d[O + 65]), "+f"(d[O + 66]), "+f"(d[O + 67]), "+f"(d[O + 68]), "+f"(d[O + 69]), "+f"(d[O + 70]), "+f"(d[O + 71]),
      "+f"(d[O + 72]), "+f"(d[O + 73]), "+f"(d[O + 74]), "+f"(d[O + 75]), "+f"(d[O + 76]), "+f"(d[O + 77]), "+f"(d[O + 78]), "+f"(d[O + 79]),
      "+f"(d[O + 80]), "+f"(d[O + 81]), "+f"(d[O + 82]), "+f"(d[O + 83]), "+f"(d[O + 84]), "+f"(d[O + 85]), "+f"(d[O + 86]), "+f"(d[O + 87]),
      "+f"(d[O + 88]), "+f"(d[O + 89]), "+f"(d[O + 90]), "+f"(d[O + 91]), "+f"(d[O + 92]), "+f"(d[O + 93]), "+f"(d[O + 94]), "+f"(d[O + 95])
    : "r"(a.x), "r"(a.y), "r"(a.z), "r"(a.w), "l"(db));
}
template <int O, int T> __device__ __forceinline__ void wgmma_rs_n192_init(float (&d)[T], const uint4& a, uint64_t db) {
  asm volatile("{\n.reg .pred p;\nsetp.ne.b32 p, 0, 0;\n"
    "wgmma.mma_async.sync.aligned.m64n192k16.f32.bf16.bf16 "
    "{%0, %1, %2, %3, %4, %5, %6, %7, %8, %9, %10, %11, %12, %13, %14, %15, "
    "%16, %17, %18, %19, %20, %21, %22, %23, %24, %25, %26, %27, %28, %29, %30, %31, "
    "%32, %33, %34, %35, %36, %37, %38, %39, %40, %41, %42, %43, %44, %45, %46, %47, "
    "%48, %49, %50, %51, %52, %53, %54, %55, %56, %57, %58, %59, %60, %61, %62, %63, "
    "%64, %65, %66, %67, %68, %69, %70, %71, %72, %73, %74, %75, %76, %77, %78, %79, "
    "%80, %81, %82, %83, %84, %85, %86, %87, %88, %89, %90, %91, %92, %93, %94, %95}, "
    "{%96, %97, %98, %99}, %100, p, 1, 1, 1;\n}\n"
    : "=f"(d[O + 0]), "=f"(d[O + 1]), "=f"(d[O + 2]), "=f"(d[O + 3]), "=f"(d[O + 4]), "=f"(d[O + 5]), "=f"(d[O + 6]), "=f"(d[O + 7]),
      "=f"(d[O + 8]), "=f"(d[O + 9]), "=f"(d[O + 10]), "=f"(d[O + 11]), "=f"(d[O + 12]), "=f"(d[O + 13]), "=f"(d[O + 14]), "=f"(d[O + 15]),
      "=f"(d[O + 16]), "=f"(d[O + 17]), "=f"(d[O + 18]), "=f"(d[O + 19]), "=f"(d[O + 20]), "=f"(d[O + 21]), "=f"(d[O + 22]), "=f"(d[O + 23]),
      "=f"(d[O + 24]), "=f"(d[O + 25]), "=f"(d[O + 26]), "=f"(d[O + 27]), "=f"(d[O + 28]), "=f"(d[O + 29]), "=f"(d[O + 30]), "=f"(d[O + 31]),
      "=f"(d[O + 32]), "=f"(d[O + 33]), "=f"(d[O + 34]), "=f"(d[O + 35]), "=f"(d[O + 36]), "=f"(d[O + 37]), "=f"(d[O + 38]), "=f"(d[O + 39]),
      "=f"(d[O + 40]), "=f"(d[O + 41]), "=f"(d[O + 42]), "=f"(d[O + 43]), "=f"(d[O + 44]), "=f"(d[O + 45]), "=f"(d[O + 46]), "=f"(d[O + 47]),
      "=f"(d[O + 48]), "=f"(d[O + 49]), "=f"(d[O + 50]), "=f"(d[O + 51]), "=f"(d[O + 52]), "=f"(d[O + 53]), "=f"(d[O + 54]), "=f"(d[O + 55]),
      "=f"(d[O + 56]), "=f"(d[O + 57]), "=f"(d[O + 58]), "=f"(d[O + 59]), "=f"(d[O + 60]), "=f"(d[O + 61]), "=f"(d[O + 62]), "=f"(d[O + 63]),
      "=f"(d[O + 64]), "=f"(d[O + 65]), "=f"(d[O + 66]), "=f"(d[O + 67]), "=f"(d[O + 68]), "=f"(d[O + 69]), "=f"(d[O + 70]), "=f"(d[O + 71]),
      "=f"(d[O + 72]), "=f"(d[O + 73]), "=f"(d[O + 74]), "=f"(d[O + 75]), "=f"(d[O + 76]), "=f"(d[O + 77]), "=f"(d[O + 78]), "=f"(d[O + 79]),
      "=f"(d[O + 80]), "=f"(d[O + 81]), "=f"(d[O + 82]), "=f"(d[O + 83]), "=f"(d[O + 84]), "=f"(d[O + 85]), "=f"(d[O + 86]), "=f"(d[O + 87]),
      "=f"(d[O + 88]), "=f"(d[O + 89]), "=f"(d[O + 90]), "=f"(d[O + 91]), "=f"(d[O + 92]), "=f"(d[O + 93]), "=f"(d[O + 94]), "=f"(d[O + 95])
    : "r"(a.x), "r"(a.y), "r"(a.z), "r"(a.w), "l"(db));
}
template <bool INIT, int O, int T> __device__ __forceinline__ void wgmma_n192(float (&d)[T], const uint4& a, uint64_t db) {
  if constexpr (INIT) wgmma_rs_n192_init<O>(d, a, db); else wgmma_rs_n192<O>(d, a, db);
}
template <int O, int T> __device__ __forceinline__ void wgmma_rs_n256(float (&d)[T], const uint4& a, uint64_t db) {
  asm volatile("{\n.reg .pred p;\nsetp.ne.b32 p, 1, 0;\n"
    "wgmma.mma_async.sync.aligned.m64n256k16.f32.bf16.bf16 "
    "{%0, %1, %2, %3, %4, %5, %6, %7, %8, %9, %10, %11, %12, %13, %14, %15, "
    "%16, %17, %18, %19, %20, %21, %22, %23, %24, %25, %26, %27, %28, %29, %30, %31, "
    "%32, %33, %34, %35, %36, %37, %38, %39, %40, %41, %42, %43, %44, %45, %46, %47, "
    "%48, %49, %50, %51, %52, %53, %54, %55, %56, %57, %58, %59, %60, %61, %62, %63, "
    "%64, %65, %66, %67, %68, %69, %70, %71, %72, %73, %74, %75, %76, %77, %78, %79, "
    "%80, %81, %82, %83, %84, %85, %86, %87, %88, %89, %90, %91, %92, %93, %94, %95, "
    "%96, %97, %98, %99, %100, %101, %102, %103, %104, %105, %106, %107, %108, %109, %110, %111, "
    "%112, %113, %114, %115, %116, %117, %118, %119, %120, %121, %122, %123, %124, %125, %126, %127}, "
    "{%128, %129, %130, %131}, %132, p, 1, 1, 1;\n}\n"
    : "+f"(d[O + 0]), "+f"(d[O + 1]), "+f"(d[O + 2]), "+f"(d[O + 3]), "+f"(d[O + 4]), "+f"(d[O + 5]), "+f"(d[O + 6]), "+f"(d[O + 7]),
      "+f"(d[O + 8]), "+f"(d[O + 9]), "+f"(d[O + 10]), "+f"(d[O + 11]), "+f"(d[O + 12]), "+f"(d[O + 13]), "+f"(d[O + 14]), "+f"(d[O + 15]),
      "+f"(d[O + 16]), "+f"(d[O + 17]), "+f"(d[O + 18]), "+f"(d[O + 19]), "+f"(d[O + 20]), "+f"(d[O + 21]), "+f"(d[O + 22]), "+f"(d[O + 23]),
      "+f"(d[O + 24]), "+f"(d[O + 25]), "+f"(d[O + 26]), "+f"(d[O + 27]), "+f"(d[O + 28]), "+f"(d[O + 29]), "+f"(d[O + 30]), "+f"(d[O + 31]),
      "+f"(d[O + 32]), "+f"(d[O + 33]), "+f"(d[O + 34]), "+f"(d[O + 35]), "+f"(d[O + 36]), "+f"(d[O + 37]), "+f"(d[O + 38]), "+f"(d[O + 39]),
      "+f"(d[O + 40]), "+f"(d[O + 41]), "+f"(d[O + 42]), "+f"(d[O + 43]), "+f"(d[O + 44]), "+f"(d[O + 45]), "+f"(d[O + 46]), "+f"(d[O + 47]),
      "+f"(d[O + 48]), "+f"(d[O + 49]), "+f"(d[O + 50]), "+f"(d[O + 51]), "+f"(d[O + 52]), "+f"(d[O + 53]), "+f"(d[O + 54]), "+f"(d[O + 55]),
      "+f"(d[O + 56]), "+f"(d[O + 57]), "+f"(d[O + 58]), "+f"(d[O + 59]), "+f"(d[O + 60]), "+f"(d[O + 61]), "+f"(d[O + 62]), "+f"(d[O + 63]),
      "+f"(d[O + 64]), "+f"(d[O + 65]), "+f"(d[O + 66]), "+f"(d[O + 67]), "+f"(d[O + 68]), "+f"(d[O + 69]), "+f"(d[O + 70]), "+f"(d[O + 71]),
      "+f"(d[O + 72]), "+f"(d[O + 73]), "+f"(d[O + 74]), "+f"(d[O + 75]), "+f"(d[O + 76]), "+f"(d[O + 77]), "+f"(d[O + 78]), "+f"(d[O + 79]),
      "+f"(d[O + 80]), "+f"(d[O + 81]), "+f"(d[O + 82]), "+f"(d[O + 83]), "+f"(d[O + 84]), "+f"(d[O + 85]), "+f"(d[O + 86]), "+f"(d[O + 87]),
      "+f"(d[O + 88]), "+f"(d[O + 89]), "+f"(d[O + 90]), "+f"(d[O + 91]), "+f"(d[O + 92]), "+f"(d[O + 93]), "+f"(d[O + 94]), "+f"(d[O + 95]),
      "+f"(d[O + 96]), "+f"(d[O + 97]), "+f"(d[O + 98]), "+f"(d[O + 99]), "+f"(d[O + 100]), "+f"(d[O + 101]), "+f"(d[O + 102]), "+f"(d[O + 103]),
      "+f"(d[O + 104]), "+f"(d[O + 105]), "+f"(d[O + 106]), "+f"(d[O + 107]), "+f"(d[O + 108]), "+f"(d[O + 109]), "+f"(d[O + 110]), "+f"(d[O + 111]),
      "+f"(d[O + 112]), "+f"(d[O + 113]), "+f"(d[O + 114]), "+f"(d[O + 115]), "+f"(d[O + 116]), "+f"(d[O + 117]), "+f"(d[O + 118]), "+f"(d[O + 119]),
      "+f"(d[O + 120]), "+f"(d[O + 121]), "+f"(d[O + 122]), "+f"(d[O + 123]), "+f"(d[O + 124]), "+f"(d[O + 125]), "+f"(d[O + 126]), "+f"(d[O + 127])
    : "r"(a.x), "r"(a.y), "r"(a.z), "r"(a.w), "l"(db));
}
template <int O, int T> __device__ __forceinline__ void wgmma_rs_n256_init(float (&d)[T], const uint4& a, uint64_t db) {
  asm volatile("{\n.reg .pred p;\nsetp.ne.b32 p, 0, 0;\n"
    "wgmma.mma_async.sync.aligned.m64n256k16.f32.bf16.bf16 "
    "{%0, %1, %2, %3, %4, %5, %6, %7, %8, %9, %10, %11, %12, %13, %14, %15, "
    "%16, %17, %18, %19, %20, %21, %22, %23, %24, %25, %26, %27, %28, %29, %30, %31, "
    "%32, %33, %34, %35, %36, %37, %38, %39, %40, %41, %42, %43, %44, %45, %46, %47, "
    "%48, %49, %50, %51, %52, %53, %54, %55, %56, %57, %58, %59, %60, %61, %62, %63, "
    "%64, %65, %66, %67, %68, %69, %70, %71, %72, %73, %74, %75, %76, %77, %78, %79, "
    "%80, %81, %82, %83, %84, %85, %86, %87, %88, %89, %90, %91, %92, %93, %94, %95, "
    "%96, %97, %98, %99, %100, %101, %102, %103, %104, %105, %106, %107, %108, %109, %110, %111, "
    "%112, %113, %114, %115, %116, %117, %118, %119, %120, %121, %122, %123, %124, %125, %126, %127}, "
    "{%128, %129, %130, %131}, %132, p, 1, 1, 1;\n}\n"
    : "=f"(d[O + 0]), "=f"(d[O + 1]), "=f"(d[O + 2]), "=f"(d[O + 3]), "=f"(d[O + 4]), "=f"(d[O + 5]), "=f"(d[O + 6]), "=f"(d[O + 7]),
      "=f"(d[O + 8]), "=f"(d[O + 9]), "=f"(d[O + 10]), "=f"(d[O + 11]), "=f"(d[O + 12]), "=f"(d[O + 13]), "=f"(d[O + 14]), "=f"(d[O + 15]),
      "=f"(d[O + 16]), "=f"(d[O + 17]), "=f"(d[O + 18]), "=f"(d[O + 19]), "=f"(d[O + 20]), "=f"(d[O + 21]), "=f"(d[O + 22]), "=f"(d[O + 23]),
      "=f"(d[O + 24]), "=f"(d[O + 25]), "=f"(d[O + 26]), "=f"(d[O + 27]), "=f"(d[O + 28]), "=f"(d[O + 29]), "=f"(d[O + 30]), "=f"(d[O + 31]),
      "=f"(d[O + 32]), "=f"(d[O + 33]), "=f"(d[O + 34]), "=f"(d[O + 35]), "=f"(d[O + 36]), "=f"(d[O + 37]), "=f"(d[O + 38]), "=f"(d[O + 39]),
      "=f"(d[O + 40]), "=f"(d[O + 41]), "=f"(d[O + 42]), "=f"(d[O + 43]), "=f"(d[O + 44]), "=f"(d[O + 45]), "=f"(d[O + 46]), "=f"(d[O + 47]),
      "=f"(d[O + 48]), "=f"(d[O + 49]), "=f"(d[O + 50]), "=f"(d[O + 51]), "=f"(d[O + 52]), "=f"(d[O + 53]), "=f"(d[O + 54]), "=f"(d[O + 55]),
      "=f"(d[O + 56]), "=f"(d[O + 57]), "=f"(d[O + 58]), "=f"(d[O + 59]), "=f"(d[O + 60]), "=f"(d[O + 61]), "=f"(d[O + 62]), "=f"(d[O + 63]),
      "=f"(d[O + 64]), "=f"(d[O + 65]), "=f"(d[O + 66]), "=f"(d[O + 67]), "=f"(d[O + 68]), "=f"(d[O + 69]), "=f"(d[O + 70]), "=f"(d[O + 71]),
      "=f"(d[O + 72]), "=f"(d[O + 73]), "=f"(d[O + 74]), "=f"(d[O + 75]), "=f"(d[O + 76]), "=f"(d[O + 77]), "=f"(d[O + 78]), "=f"(d[O + 79]),
      "=f"(d[O + 80]), "=f"(d[O + 81]), "=f"(d[O + 82]), "=f"(d[O + 83]), "=f"(d[O + 84]), "=f"(d[O + 85]), "=f"(d[O + 86]), "=f"(d[O + 87]),
      "=f"(d[O + 88]), "=f"(d[O + 89]), "=f"(d[O + 90]), "=f"(d[O + 91]), "=f"(d[O + 92]), "=f"(d[O + 93]), "=f"(d[O + 94]), "=f"(d[O + 95]),
      "=f"(d[O + 96]), "=f"(d[O + 97]), "=f"(d[O + 98]), "=f"(d[O + 99]), "=f"(d[O + 100]), "=f"(d[O + 101]), "=f"(d[O + 102]), "=f"(d[O + 103]),
      "=f"(d[O + 104]), "=f"(d[O + 105]), "=f"(d[O + 106]), "=f"(d[O + 107]), "=f"(d[O + 108]), "=f"(d[O + 109]), "=f"(d[O + 110]), "=f"(d[O + 111]),
      "=f"(d[O + 112]), "=f"(d[O + 113]), "=f"(d[O + 114]), "=f"(d[O + 115]), "=f"(d[O + 116]), "=f"(d[O + 117]), "=f"(d[O + 118]), "=f"(d[O + 119]),
      "=f"(d[O + 120]), "=f"(d[O + 121]), "=f"(d[O + 122]), "=f"(d[O + 123]), "=f"(d[O + 124]), "=f"(d[O + 125]), "=f"(d[O + 126]), "=f"(d[O + 127])
    : "r"(a.x), "r"(a.y), "r"(a.z), "r"(a.w), "l"(db));
}
template <bool INIT, int O, int T> __device__ __forceinline__ void wgmma_n256(float (&d)[T], const uint4& a, uint64_t db) {
  if constexpr (INIT) wgmma_rs_n256_init<O>(d, a, db); else wgmma_rs_n256<O>(d, a, db);
}

template <int N> __device__ __forceinline__ void load_pk(uint4* a, const uint4* p) {
#pragma unroll
  for (int i = 0; i < N; i++) a[i] = ld_ll(p + i * 32);
}
__device__ __forceinline__ uint32_t xor_or(uint32_t a, uint32_t b, uint32_t t) {
  uint32_t r;
  asm("lop3.b32 %0, %1, %2, %3, 0x7E;" : "=r"(r) : "r"(a), "r"(b), "r"(t));
  return r;
}
template <int N> __device__ __forceinline__ bool ok_pk(const uint4* a, uint32_t tag) {
  static_assert(N % 2 == 0, "");
  uint32_t x = xor_or(a[0].x, a[1].x, tag);
#pragma unroll
  for (int i = 2; i < N; i += 2) x |= xor_or(a[i].x, a[i + 1].x, tag);
  return __all_sync(0xffffffffu, (x & 1u) == 0u);
}
template <int N> __device__ __forceinline__ void ensure_pk(uint4* a, const uint4* p, uint32_t tag) {
  if (ok_pk<N>(a, tag)) return;
  uint32_t n = 0;
  do { load_pk<N>(a, p); } while (!ok_pk<N>(a, tag) && ++n < SPIN_LIMIT);
}

constexpr int NSTAGE = 44;
constexpr int ST_WO = 8, ST_G1 = 12, ST_G2 = 20, ST_DN = 28;
__host__ __device__ constexpr int st_len(int s) { return s < ST_WO ? 3 : s < ST_G1 ? 2 : s < ST_G2 ? 4 : s < ST_DN ? 3 : 2; }
__host__ __device__ constexpr int st_g0(int s) {
  int pos = 0, g0 = 0;
  for (int i = 0; i <= s; i++) {
    if (pos + st_len(i) > NGRAN) pos = 0;
    g0 = pos;
    pos += st_len(i);
  }
  return g0;
}
__host__ __device__ constexpr int cnt_first(int g, int s) {
  int n = 0;
  for (int i = 0; i < s; i++) n += (st_g0(i) == g);
  return n;
}
__host__ __device__ constexpr int cnt_cover(int g, int s) {
  int n = 0;
  for (int i = 0; i < s; i++) n += (g >= st_g0(i) && g < st_g0(i) + st_len(i));
  return n;
}
__host__ __device__ constexpr uint32_t flip_mask(int s0, int s1) {
  uint32_t m = 0;
  for (int i = s0; i < s1; i++) m ^= ((1u << st_len(i)) - 1u) << st_g0(i);
  return m;
}
__host__ __device__ constexpr int dn_q(int i) { return i < 3 ? 0 : i < 6 ? 1 : i == 6 ? 0 : i == 7 ? 1 : i < 12 ? 2 : 3; }
__host__ __device__ constexpr int dn_par(int i) { return i < 8 ? (i == 2 || i == 4 || i >= 6) : (i & 1); }
__host__ __device__ constexpr int dn_kh(int i) { return i < 8 ? (i == 1 || i >= 5) : ((i & 3) >= 2); }
template <int I> struct IC { static constexpr int value = I; };
template <int B, int E, typename F> __device__ __forceinline__ void static_for(F&& f) {
  if constexpr (B < E) { f(IC<B>{}); static_for<B + 1, E>(f); }
}
template <int S> __device__ __forceinline__ void cons_acquire(uint32_t sbase, uint32_t L) {
  constexpr int g0 = st_g0(S);
  constexpr uint32_t p0 = cnt_first(g0, S) & 1, odd = cnt_first(g0, NSTAGE) & 1;
  mbar_wait(sbase + SM_MISC + BAR_FULL + 8 * g0, p0 ^ (L & odd));
}
template <int S> __device__ __forceinline__ void cons_release(uint32_t sbase, int lane) {
  if (lane < st_len(S)) mbar_arrive(sbase + SM_MISC + BAR_EMPTY + 8 * st_g0(S) + 8 * lane);
}
__device__ __forceinline__ bool elect_one() {
  uint32_t p;
  asm volatile("{\n.reg .pred P;\nelect.sync _|P, 0xffffffff;\nselp.u32 %0, 1, 0, P;\n}" : "=r"(p));
  return p != 0;
}
struct ProdRing { uint32_t pos, par; };
template <int N> __device__ __forceinline__ uint32_t prod_acquire(uint32_t sbase, ProdRing& r) {
  if (r.pos + N > NGRAN) r.pos = 0;
  const uint32_t g0 = r.pos;
#pragma unroll
  for (uint32_t i = 0; i < N; i++) mbar_wait(sbase + SM_MISC + BAR_EMPTY + 8 * (g0 + i), ((r.par >> (g0 + i)) & 1u) ^ 1u);
  r.par ^= ((1u << N) - 1u) << g0;
  r.pos = g0 + N;
  return g0;
}
template <int S> __device__ __forceinline__ void prod_acquire_static(uint32_t sbase, uint32_t L) {
  constexpr int g0 = st_g0(S);
  static_for<0, st_len(S)>([&](auto I) {
    constexpr int g = g0 + I.value;
    constexpr uint32_t p0 = cnt_cover(g, S) & 1, odd = cnt_cover(g, NSTAGE) & 1;
    mbar_wait(sbase + SM_MISC + BAR_EMPTY + 8 * g, p0 ^ (L & odd) ^ 1u);
  });
}
template <int S, int KSTEP_BYTES, int LBO, int SBO, int SWZ> __device__ __forceinline__ constexpr uint64_t st_desc(int k) {
  return (uint64_t)((SMEM_ORIGIN + st_g0(S) * GRAN + k * KSTEP_BYTES) >> 4) | ((uint64_t)(LBO >> 4) << 16) |
         ((uint64_t)(SBO >> 4) << 32) | ((uint64_t)SWZ << 62);
}

__device__ __forceinline__ void combine_stats(const uint4& p0, const uint4& p1, float& mean_lo, float& rstd_lo, float& mean_hi, float& rstd_hi) {
  float m0 = __uint_as_float(p0.x), q0 = __uint_as_float(p0.y), m0h = __uint_as_float(p0.z), q0h = __uint_as_float(p0.w);
  float m1 = __uint_as_float(p1.x), q1 = __uint_as_float(p1.y), m1h = __uint_as_float(p1.z), q1h = __uint_as_float(p1.w);
  float s = m0 + m1, sh = m0h + m1h;
  s += __shfl_xor_sync(0xffffffffu, s, 1); sh += __shfl_xor_sync(0xffffffffu, sh, 1);
  s += __shfl_xor_sync(0xffffffffu, s, 2); sh += __shfl_xor_sync(0xffffffffu, sh, 2);
  mean_lo = s * 0.125f; mean_hi = sh * 0.125f;
  float d0 = m0 - mean_lo, d1 = m1 - mean_lo, d0h = m0h - mean_hi, d1h = m1h - mean_hi;
  float t = q0 + q1 + 64.f * (d0 * d0 + d1 * d1), th = q0h + q1h + 64.f * (d0h * d0h + d1h * d1h);
  t += __shfl_xor_sync(0xffffffffu, t, 1); th += __shfl_xor_sync(0xffffffffu, th, 1);
  t += __shfl_xor_sync(0xffffffffu, t, 2); th += __shfl_xor_sync(0xffffffffu, th, 2);
  rstd_lo = rsqrtf(t * (1.f / 512.f) + 1e-5f);
  rstd_hi = rsqrtf(th * (1.f / 512.f) + 1e-5f);
}
__device__ __forceinline__ uint4 local_stats(const float (&v)[32]) {
  float s = 0.f, sh = 0.f;
#pragma unroll
  for (int i = 0; i < 4; i++) {
    s += (v[8 * i + 0] + v[8 * i + 1]) + (v[8 * i + 4] + v[8 * i + 5]);
    sh += (v[8 * i + 2] + v[8 * i + 3]) + (v[8 * i + 6] + v[8 * i + 7]);
  }
  s += __shfl_xor_sync(0xffffffffu, s, 1); sh += __shfl_xor_sync(0xffffffffu, sh, 1);
  s += __shfl_xor_sync(0xffffffffu, s, 2); sh += __shfl_xor_sync(0xffffffffu, sh, 2);
  float m = s * (1.f / 64.f), mh = sh * (1.f / 64.f);
  float q = 0.f, qh = 0.f;
#pragma unroll
  for (int i = 0; i < 4; i++) {
    float a = v[8 * i + 0] - m, b = v[8 * i + 1] - m, c = v[8 * i + 4] - m, d = v[8 * i + 5] - m;
    q += (a * a + b * b) + (c * c + d * d);
    float e = v[8 * i + 2] - mh, f = v[8 * i + 3] - mh, g = v[8 * i + 6] - mh, h = v[8 * i + 7] - mh;
    qh += (e * e + f * f) + (g * g + h * h);
  }
  q += __shfl_xor_sync(0xffffffffu, q, 1); qh += __shfl_xor_sync(0xffffffffu, qh, 1);
  q += __shfl_xor_sync(0xffffffffu, q, 2); qh += __shfl_xor_sync(0xffffffffu, qh, 2);
  return make_uint4(__float_as_uint(m), __float_as_uint(q), __float_as_uint(mh), __float_as_uint(qh));
}

__device__ __forceinline__ int slab_row0(int c, int g, int w) { return 1024 * g + 64 * c + 32 * (w >> 1) + (w & 1); }

__device__ __forceinline__ void owner_ln_publish(uint32_t sbase, const float (&v)[32], uint32_t tphase, uint32_t tag_xn, uint4 (&xraw)[4]) {
  PHASE_VARS;
  TS(40 + 4 * tphase);
  uint4 st = local_stats(v);
  if (qc == 0) sts128(sbase + SM_TSTAT + warp * 128 + qr * 16, st);
  uint4* xn = g_arena + c * ARENA + AR_XN + ((j) * 32 + 4 * warp) * 32 + lane;
  TS(41 + 4 * tphase);
  asm volatile("bar.sync 3, 256;" ::: "memory");
  TS(42 + 4 * tphase);
  const uint32_t rd = sbase + SM_TSTAT + qc * 256 + qr * 16;
  uint4 p0 = lds128(rd), p1 = lds128(rd + 128);
  float ml, rl, mh, rh;
  combine_stats(p0, p1, ml, rl, mh, rh);
  const float bl = -ml * rl, bh = -mh * rh;
#pragma unroll
  for (int i = 0; i < 4; i++) {
    uint4 o;
    o.x = set_tag(pack2(fmaf(v[8 * i + 0], rl, bl), fmaf(v[8 * i + 1], rl, bl)), tag_xn);
    o.y = pack2(fmaf(v[8 * i + 2], rh, bh), fmaf(v[8 * i + 3], rh, bh));
    o.z = pack2(fmaf(v[8 * i + 4], rl, bl), fmaf(v[8 * i + 5], rl, bl));
    o.w = pack2(fmaf(v[8 * i + 6], rh, bh), fmaf(v[8 * i + 7], rh, bh));
    st_ll(xn + i * 32, o);
  }
#pragma unroll
  for (int i = 0; i < 4; i++) {
    xraw[i].x = set_tag(pack2(v[8 * i + 0], v[8 * i + 1]), 1u);
    xraw[i].y = pack2(v[8 * i + 2], v[8 * i + 3]);
    xraw[i].z = pack2(v[8 * i + 4], v[8 * i + 5]);
    xraw[i].w = pack2(v[8 * i + 6], v[8 * i + 7]);
  }
}

__device__ __forceinline__ uint4 pack8(const float* a) {
  return make_uint4(pack2(a[0], a[1]), pack2(a[2], a[3]), pack2(a[4], a[5]), pack2(a[6], a[7]));
}
template <int U> __device__ __forceinline__ uint4 glu8(const float* g, float cl, float ch) {
  return make_uint4(pack2(g[0] * cl * g[U], g[1] * cl * g[U + 1]), pack2(g[2] * ch * g[U + 2], g[3] * ch * g[U + 3]),
                    pack2(g[4] * cl * g[U + 4], g[5] * cl * g[U + 5]), pack2(g[6] * ch * g[U + 6], g[7] * ch * g[U + 7]));
}
__device__ __forceinline__ uint32_t hfma2(uint32_t a, uint32_t b, uint32_t c) {
  uint32_t d;
  asm("fma.rn.bf16x2 %0, %1, %2, %3;" : "=r"(d) : "r"(a), "r"(b), "r"(c));
  return d;
}
__device__ __forceinline__ void keep4(const uint4 (&a)[4]) { keep(a[0]); keep(a[1]); keep(a[2]); keep(a[3]); }

#define STAGGER 0

__global__ void __launch_bounds__(NTHREADS, 1)
fused_kernel(const __grid_constant__ CUtensorMap m_qkv, const __grid_constant__ CUtensorMap m_wo,
             const __grid_constant__ CUtensorMap m_gu2, const __grid_constant__ CUtensorMap m_gu1,
             const __grid_constant__ CUtensorMap m_guh, const __grid_constant__ CUtensorMap m_wd112,
             const __grid_constant__ CUtensorMap m_wd80, const __grid_constant__ CUtensorMap m_wd32,
             const __nv_bfloat16* __restrict__ x_in,
             __nv_bfloat16* __restrict__ out, const char* __restrict__ w_o, const char* __restrict__ w_g,
             const char* __restrict__ w_u, const char* __restrict__ w_d
) {
  extern __shared__ __align__(1024) unsigned char smem_raw[];
  const uint32_t sbase = smem_u32(smem_raw);
  const uint32_t bars = sbase + SM_MISC;
  if ((sbase & 0xFFFFFFu) != SMEM_ORIGIN) return;
  TG(60);

  uint32_t xw[16];
  if (threadIdx.x < 256) {
    const int cc = blockIdx.x >> 3, jj = blockIdx.x & 7, ln = threadIdx.x & 31;
    const uint32_t* xp = reinterpret_cast<const uint32_t*>(x_in + (size_t)(slab_row0(cc, jj >> 2, jj & 3) + 2 * (ln >> 2)) * 512 + (threadIdx.x >> 5) * 64 + (ln & 3) * 2);
#pragma unroll
    for (int i = 0; i < 4; i++) {
      xw[4 * i] = __ldg(xp + i * 8); xw[4 * i + 1] = __ldg(xp + 16 * 256 + i * 8);
      xw[4 * i + 2] = __ldg(xp + i * 8 + 4); xw[4 * i + 3] = __ldg(xp + 16 * 256 + i * 8 + 4);
    }
  } else if (threadIdx.x == 256) {
    for (int i = 0; i < NGRAN; i++) { mbar_init(bars + BAR_FULL + 8 * i, 1); mbar_init(bars + BAR_EMPTY + 8 * i, 8); }
    for (int i = 0; i < 4; i++) mbar_init(bars + BAR_HRECV + 8 * i, 1);
    for (int i = 0; i < 2; i++) mbar_init(bars + BAR_HREADY + 8 * i, 4);
    asm volatile("fence.mbarrier_init.release.cluster;" ::: "memory");
  }
  __syncthreads();
  asm volatile("barrier.cluster.arrive.release.aligned;" ::: "memory");

  if (threadIdx.x >= 256) {
    asm volatile("setmaxnreg.dec.sync.aligned.u32 40;");
    const int warp = threadIdx.x >> 5, lane = threadIdx.x & 31;
    const int j = blockIdx.x & 7, b = j & 1;
    if (warp == 8) {
      ProdRing r{0u, 0u};
      const int cb0 = 224 * j + 32 * b, hb0 = 224 * j + 192 * (b ^ 1);
      const int jp = j ^ 1, cbp = 224 * jp + 32 * (b ^ 1), hbp = 224 * jp + 192 * b;
#pragma unroll 1
      for (uint32_t L = 0; L < 2; L++) {
        r.pos = 0;
        PSTOP_AT(L == 0 ? 0 : 3);
#pragma unroll 1
        for (int kb = 0; kb < 8; kb++) {
          const uint32_t g0 = prod_acquire<3>(sbase, r);
          if (elect_one()) {
            mbar_expect_tx(bars + BAR_FULL + 8 * g0, 24576);
            tma_3d(sbase + g0 * GRAN, &m_qkv, bars + BAR_FULL + 8 * g0, 64 * j, 64 * kb, 0);
          }
        }
        PSTOP_AT(10 * L + 1);
#pragma unroll 1
        for (int i = 0; i < 4; i++) {
          const uint32_t g0 = prod_acquire<2>(sbase, r);
          if (elect_one()) {
            mbar_expect_tx(bars + BAR_FULL + 8 * g0, 16384);
            tma_2d(sbase + g0 * GRAN, &m_wo, bars + BAR_FULL + 8 * g0, 64 * j, 128 * i);
          }
        }
        PSTOP_AT(10 * L + 2);
#pragma unroll 1
        for (int kb = 0; kb < 8; kb++) {
          const uint32_t g0 = prod_acquire<4>(sbase, r);
          if (elect_one()) {
            mbar_expect_tx(bars + BAR_FULL + 8 * g0, 32768);
            tma_4d(sbase + g0 * GRAN, &m_gu2, bars + BAR_FULL + 8 * g0, cb0, 64 * ((j + kb) & 7), 0, 0);
          }
        }
#pragma unroll 1
        for (int kb = 0; kb < 8; kb++) {
          const uint32_t g0 = prod_acquire<3>(sbase, r);
          if (elect_one()) {
            mbar_expect_tx(bars + BAR_FULL + 8 * g0, 24576);
            tma_4d(sbase + g0 * GRAN, &m_gu1, bars + BAR_FULL + 8 * g0, cb0 + 128, 64 * ((j + kb) & 7), 0, 0);
            tma_3d(sbase + g0 * GRAN + 16384, &m_guh, bars + BAR_FULL + 8 * g0, hb0, 64 * ((j + kb) & 7), 0);
          }
        }
        static_for<0, 16>([&](auto I) {
          constexpr int i = I.value, g0 = st_g0(ST_DN + i);
          prod_acquire_static<ST_DN + i>(sbase, L);
          if (elect_one()) {
            const uint32_t dst = sbase + g0 * GRAN, fb = bars + BAR_FULL + 8 * g0;
            const int n0 = 256 * b + 64 * dn_q(i);
            mbar_expect_tx(fb, 14336);
            if constexpr (dn_kh(i) == 0) {
              tma_2d(dst, &m_wd112, fb, n0, dn_par(i) ? cbp : cb0);
            } else {
              tma_2d(dst, &m_wd80, fb, n0, (dn_par(i) ? cbp : cb0) + 112);
              tma_2d(dst + 10240, &m_wd32, fb, n0, dn_par(i) ? hbp : hb0);
            }
          }
        });
        r.par ^= flip_mask(ST_DN, NSTAGE);
      }
    } else if (warp == 9) {
      const int cta = blockIdx.x;
      if (lane == 0) l2_prefetch(w_o + cta * 4096, 4096);
      if (lane == 1) l2_prefetch(w_g + cta * 14336, 14336);
      if (lane == 2) l2_prefetch(w_u + cta * 14336, 14336);
      if (lane == 3) l2_prefetch(w_d + cta * 14336, 14336);
    }
    __syncwarp();
    asm volatile("barrier.cluster.wait.acquire.aligned; // producer" ::: "memory");
    asm volatile("barrier.cluster.arrive.release.aligned;\nbarrier.cluster.wait.acquire.aligned; // producer" ::: "memory");
  } else {
    asm volatile("setmaxnreg.inc.sync.aligned.u32 232;");
    TS(0);
    TG(61);

    uint4 xraw[4];
    {
      float v[32];
#pragma unroll
      for (int i = 0; i < 16; i++) { v[2 * i] = bf_lo(xw[i]); v[2 * i + 1] = bf_hi(xw[i]); }
      owner_ln_publish(sbase, v, 0u, 1u, xraw);
      asm volatile("barrier.cluster.wait.acquire.aligned; // consumer" ::: "memory");
    }
    STOP_AT(0);
    TS(1);

#pragma unroll 1
    for (uint32_t L = 0; L < 2; L++) {
      const uint32_t tag = L ^ 1;
      {
        PHASE_VARS;
        uint4 qf[4], kf[4], vf[4], pp[4];
        const int blk = 16 * g + c;
        const int pb = blk > 0 ? blk - 1 : 0;
        const uint4* halo_src = g_arena + (pb & 15) * ARENA + AR_HALO + (((((L * 2 + (pb >> 4)) * 8 + j) * 2 + (w & 1)) * 4) * 32) + lane;
        {
          float acc[96];
          uint4 A[3][4];
          const uint4* xs = g_arena + c * ARENA + AR_XN + ((slab) * 32) * 32 + lane;
          bar_wg(1 + g);
          load_pk<4>(A[0], xs);
          ensure_pk<4>(A[0], xs, tag);
          TS(2 + 20 * L);
          load_pk<4>(A[1], xs + 128);
          static_for<0, 8>([&](auto I) {
            constexpr int kb = I.value;
            cons_acquire<kb>(sbase, L);
            wg_fence();
            static_for<0, 4>([&](auto K) { constexpr int k = K.value; wgmma_n192<kb == 0 && k == 0, 0>(acc, A[kb % 3][k], st_desc<kb, 2048, 8192, 1024, 1>(k)); });
            wg_commit();
            if constexpr (kb > 0) {
              wg_wait<1>();
              keep4(A[(kb + 2) % 3]);
              cons_release<kb - 1>(sbase, lane);
            }
            if constexpr (kb + 1 < 8) ensure_pk<4>(A[(kb + 1) % 3], xs + (kb + 1) * 128, tag);
            if constexpr (kb + 2 < 8) load_pk<4>(A[(kb + 2) % 3], xs + (kb + 2) * 128);
            if constexpr (kb == 2) {
              uint4* xr = g_arena + c * ARENA + AR_XRAW + ((j) * 32 + 4 * warp) * 32 + lane;
#pragma unroll
              for (int i = 0; i < 4; i++) st_ll(xr + i * 32, xraw[i]);
            }
          });
          wg_wait<0>();
          TS(3 + 20 * L);
          fence_acc(acc);
          keep4(A[1]);
          cons_release<7>(sbase, lane);
#pragma unroll
          for (int h = 0; h < 4; h++) {
            kf[h].y = pack2(acc[32 + 8 * h + 2], acc[32 + 8 * h + 3]); kf[h].w = pack2(acc[32 + 8 * h + 6], acc[32 + 8 * h + 7]);
            vf[h].y = movm(pack2(acc[64 + 8 * h + 2], acc[64 + 8 * h + 3])); vf[h].w = movm(pack2(acc[64 + 8 * h + 6], acc[64 + 8 * h + 7]));
            pp[h] = make_uint4(kf[h].y, kf[h].w, vf[h].y, vf[h].w);
          }
          if (w >= 2 && blk < 31) {
            uint4* hd = g_arena + c * ARENA + AR_HALO + (((((L * 2 + g) * 8 + j) * 2 + (w & 1)) * 4) * 32) + lane;
#pragma unroll
            for (int h = 0; h < 4; h++) { uint4 t = pp[h]; t.x |= 1u; st_ll(hd + h * 32, t); }
          }
#pragma unroll
          for (int h = 0; h < 4; h++) sts128(areg + (28 + h) * 2048 + t128 * 16, pp[h]);
          if (w < 2 && blk > 0) load_pk<4>(pp, halo_src);
#pragma unroll
          for (int h = 0; h < 4; h++) {
            kf[h].x = pack2(acc[32 + 8 * h], acc[32 + 8 * h + 1]); kf[h].z = pack2(acc[32 + 8 * h + 4], acc[32 + 8 * h + 5]);
            vf[h].x = movm(pack2(acc[64 + 8 * h], acc[64 + 8 * h + 1])); vf[h].z = movm(pack2(acc[64 + 8 * h + 4], acc[64 + 8 * h + 5]));
          }
#pragma unroll
          for (int h = 0; h < 4; h++) qf[h] = pack8(&acc[8 * h]);
        }
        bar_wg(1 + g);
        const bool first = (w < 2) && (blk == 0);
        if (w >= 2) {
#pragma unroll
          for (int h = 0; h < 4; h++) pp[h] = lds128(areg + (28 + h) * 2048 + (t128 - 64) * 16);
        }
        bar_wg(1 + g);
        if (w < 2 && blk > 0) {
          ensure_pk<4>(pp, halo_src, 1u);
          uint4* hz = const_cast<uint4*>(halo_src);
#pragma unroll
          for (int h = 0; h < 4; h++) st_ll(hz + h * 32, make_uint4(0, 0, 0, 0));
        }
        TS(4 + 20 * L);
        const bool n0 = 2 * qc <= qr, n1 = 2 * qc + 1 <= qr;
        const uint32_t msk = (n0 ? 0xffffu : 0u) | (n1 ? 0xffff0000u : 0u);
        const float sc = 0.25f * 1.4426950408889634f;
        const float NEG = -1e30f;
        uint4* od = g_arena + c * ARENA + AR_O + ((slab) * 32 + 4 * j) * 32 + lane;
        float l0[4], l1[4], h0[4], h1[4], ml[4], mh[4];
#pragma unroll
        for (int h = 0; h < 4; h++) {
          float sp[4], s0[4], s1[4];
          mma16816_z(sp, qf[h], pp[h].x, pp[h].y);
          mma16816_z(s0, qf[h], kf[h].x, kf[h].z);
          mma16816_z(s1, qf[h], kf[h].y, kf[h].w);
          if (first) { sp[0] = NEG; sp[1] = NEG; }
          l0[h] = n0 ? s0[0] : sp[0]; l1[h] = n1 ? s0[1] : sp[1];
          h0[h] = n0 ? s1[2] : s0[2]; h1[h] = n1 ? s1[3] : s0[3];
          ml[h] = fmaxf(l0[h], l1[h]); mh[h] = fmaxf(h0[h], h1[h]);
        }
#pragma unroll
        for (int h = 0; h < 4; h++) { ml[h] = fmaxf(ml[h], __shfl_xor_sync(0xffffffffu, ml[h], 1)); mh[h] = fmaxf(mh[h], __shfl_xor_sync(0xffffffffu, mh[h], 1)); }
#pragma unroll
        for (int h = 0; h < 4; h++) { ml[h] = fmaxf(ml[h], __shfl_xor_sync(0xffffffffu, ml[h], 2)); mh[h] = fmaxf(mh[h], __shfl_xor_sync(0xffffffffu, mh[h], 2)); }
        float sl[4], sh[4];
#pragma unroll
        for (int h = 0; h < 4; h++) {
          const float bl = -ml[h] * sc, bh = -mh[h] * sc;
          l0[h] = ex2(fmaf(l0[h], sc, bl)); l1[h] = ex2(fmaf(l1[h], sc, bl));
          h0[h] = ex2(fmaf(h0[h], sc, bh)); h1[h] = ex2(fmaf(h1[h], sc, bh));
          sl[h] = l0[h] + l1[h]; sh[h] = h0[h] + h1[h];
        }
#pragma unroll
        for (int h = 0; h < 4; h++) { sl[h] += __shfl_xor_sync(0xffffffffu, sl[h], 1); sh[h] += __shfl_xor_sync(0xffffffffu, sh[h], 1); }
#pragma unroll
        for (int h = 0; h < 4; h++) { sl[h] += __shfl_xor_sync(0xffffffffu, sl[h], 2); sh[h] += __shfl_xor_sync(0xffffffffu, sh[h], 2); }
#pragma unroll
        for (int h = 0; h < 4; h++) {
          const float il = rcp(sl[h]), ih = rcp(sh[h]);
          const uint32_t pl = pack2(l0[h] * il, l1[h] * il), ph = pack2(h0[h] * ih, h1[h] * ih);
          const uint4 P = make_uint4(pl & msk, ph & ~msk, 0u, ph & msk);
          float o0[4], o1[4];
          mma16816_z(o0, P, vf[h].x, vf[h].y);
          mma16816_z(o1, P, vf[h].z, vf[h].w);
          mma1688(o0, pl & ~msk, 0u, pp[h].z);
          mma1688(o1, pl & ~msk, 0u, pp[h].w);
          st_ll(od + h * 32, make_uint4(set_tag(pack2(o0[0], o0[1]), tag), pack2(o0[2], o0[3]), pack2(o1[0], o1[1]), pack2(o1[2], o1[3])));
        }
      }
      TS(5 + 20 * L);
      if (L == 0) { STOP_AT(1); } else { STOP_AT(11); }
      uint4 x1own[4];
      {
        PHASE_VARS;
        float acc[32];
        uint4 A[32], xr[4];
        const uint4* os = g_arena + c * ARENA + AR_O + ((slab) * 32) * 32 + lane;
        uint4* xp = g_arena + c * ARENA + AR_XRAW + ((slab) * 32 + 4 * j) * 32 + lane;
        load_pk<4>(xr, xp);
        load_pk<4>(A, os);
        ensure_pk<4>(A, os, tag);
        TS(6 + 20 * L);
        load_pk<28>(A + 4, os + 128);
        static_for<0, 8>([&](auto I) {
          constexpr int kb = I.value;
          if constexpr ((kb & 1) == 0) cons_acquire<ST_WO + kb / 2>(sbase, L);
          if constexpr (kb > 0) ensure_pk<4>(A + 4 * kb, os + kb * 128, tag);
          wg_fence();
          static_for<0, 4>([&](auto K) {
            constexpr int k = K.value;
            wgmma_n64<kb == 0 && k == 0, 0>(acc, A[4 * kb + k], st_desc<ST_WO + kb / 2, 2048, 8192, 1024, 1>(4 * (kb & 1) + k));
          });
          wg_commit();
          if constexpr ((kb & 1) == 0 && kb > 0) { wg_wait<1>(); cons_release<ST_WO + kb / 2 - 1>(sbase, lane); }
        });
        wg_wait<0>();
        TS(7 + 20 * L);
        fence_acc(acc);
#pragma unroll
        for (int k = 0; k < 32; k++) keep(A[k]);
        cons_release<ST_WO + 3>(sbase, lane);
        ensure_pk<4>(xr, xp, 1u);
#pragma unroll
        for (int i = 0; i < 4; i++) {
          acc[8 * i + 0] += bf_lo(xr[i].x); acc[8 * i + 1] += bf_hi(xr[i].x); acc[8 * i + 2] += bf_lo(xr[i].y); acc[8 * i + 3] += bf_hi(xr[i].y);
          acc[8 * i + 4] += bf_lo(xr[i].z); acc[8 * i + 5] += bf_hi(xr[i].z); acc[8 * i + 6] += bf_lo(xr[i].w); acc[8 * i + 7] += bf_hi(xr[i].w);
        }
        uint4 st = local_stats(acc);
        st.x = set_tag(st.x, tag);
        if (qc == 0) st_ll(g_arena + c * ARENA + AR_STATS + (slab * 8 + j) * 8 + qr, st);
#pragma unroll
        for (int i = 0; i < 4; i++) {
          x1own[i] = pack8(&acc[8 * i]);
          x1own[i].x = set_tag(x1own[i].x, 0u);
          st_ll(xp + i * 32, x1own[i]);
        }
      }
      TS(8 + 20 * L);
      if (L == 0) { STOP_AT(2); } else { STOP_AT(12); }
      uint4 hs[14];
      {
        PHASE_VARS;
        float acc[128];
        uint4 A[3][4];
        const uint4* xs = g_arena + c * ARENA + AR_XRAW + ((slab) * 32) * 32 + lane;
        const uint4* sp = g_arena + c * ARENA + AR_STATS + (slab * 8 + 2 * qc) * 8 + qr;
        const uint32_t sm = areg + t128 * 16;
        uint32_t rl2, rh2, bl2, bh2;
        float cl, ch;
        auto xsrc = [&](int p) { return xs + ((j + p) & 7) * 128; };
        {
          uint4 p[2];
#pragma unroll
          for (int k = 0; k < 4; k++) A[0][k] = x1own[k];
          p[0] = ld_ll(sp); p[1] = ld_ll(sp + 8);
          load_pk<4>(A[1], xsrc(1));
          for (uint32_t n = 0; !ok_pk<2>(p, tag) && n < SPIN_LIMIT; n++) { p[0] = ld_ll(sp); p[1] = ld_ll(sp + 8); }
          TS(9 + 20 * L);
          float ml, rl, mh, rh;
          combine_stats(p[0], p[1], ml, rl, mh, rh);
          rl2 = pack2(rl, rl); rh2 = pack2(rh, rh);
          const float rlb = bf_lo(rl2), rhb = bf_lo(rh2);
          bl2 = pack2(-ml * rlb, -ml * rlb); bh2 = pack2(-mh * rhb, -mh * rhb);
          cl = rl / rlb; cl *= cl; ch = rh / rhb; ch *= ch;
        }
        auto normalise = [&](uint4 (&xb)[4], int kb) {
#pragma unroll
          for (int k = 0; k < 4; k++) {
            xb[k].x = hfma2(xb[k].x, rl2, bl2); xb[k].y = hfma2(xb[k].y, rh2, bh2);
            xb[k].z = hfma2(xb[k].z, rl2, bl2); xb[k].w = hfma2(xb[k].w, rh2, bh2);
            sts128(sm + (kb * 4 + k) * 2048, xb[k]);
          }
        };
        normalise(A[0], 0);
        static_for<0, 8>([&](auto I) {
          constexpr int kb = I.value;
          cons_acquire<ST_G1 + kb>(sbase, L);
          wg_fence();
          static_for<0, 4>([&](auto K) { constexpr int k = K.value; wgmma_n256<kb == 0 && k == 0, 0>(acc, A[kb % 3][k], st_desc<ST_G1 + kb, 2048, 8192, 1024, 1>(k)); });
          wg_commit();
          if constexpr (kb > 0) {
            wg_wait<1>();
            keep4(A[(kb + 2) % 3]);
            cons_release<ST_G1 + kb - 1>(sbase, lane);
          }
          if constexpr (kb + 1 < 8) ensure_pk<4>(A[(kb + 1) % 3], xsrc(kb + 1), 0u);
          if constexpr (kb + 2 < 8) load_pk<4>(A[(kb + 2) % 3], xsrc(kb + 2));
          if constexpr (kb + 1 < 8) normalise(A[(kb + 1) % 3], kb + 1);
        });
        wg_wait<0>();
        TS(10 + 20 * L);
        fence_acc(acc);
        keep4(A[1]);
        cons_release<ST_G1 + 7>(sbase, lane);
        uint4 B[2][4];
#pragma unroll
        for (int k = 0; k < 4; k++) B[0][k] = lds128(sm + k * 2048);
#pragma unroll
        for (int s = 0; s < 8; s++) hs[s] = glu8<32>(&acc[64 * (s >> 2) + 8 * (s & 3)], cl, ch);
        float acc2[96];
        const uint32_t hdst = mapa(sm, cbit ^ 1);
        const uint32_t hbar1 = mapa(bars + BAR_HRECV + 16 * g, cbit ^ 1);
        if (t128 == 0) { mbar_expect_tx(bars + BAR_HRECV + 16 * g, 8 * 2048); mbar_expect_tx(bars + BAR_HRECV + 16 * g + 8, 6 * 2048); }
        static_for<0, 8>([&](auto I) {
          constexpr int kb = I.value;
          cons_acquire<ST_G2 + kb>(sbase, L);
          wg_fence();
          static_for<0, 4>([&](auto K) {
            constexpr int k = K.value;
            wgmma_n128<kb == 0 && k == 0, 0>(acc2, B[kb & 1][k], st_desc<ST_G2 + kb, 2048, 8192, 1024, 1>(k));
            wgmma_n64<kb == 0 && k == 0, 64>(acc2, B[kb & 1][k], st_desc<ST_G2 + kb, 1024, 4096, 512, 2>(k) + (16384 >> 4));
          });
          wg_commit();
          if constexpr (kb > 0) {
            wg_wait<1>();
            keep4(B[(kb + 1) & 1]);
            cons_release<ST_G2 + kb - 1>(sbase, lane);
          }
          if constexpr (kb + 1 < 8) {
#pragma unroll
            for (int k = 0; k < 4; k++) B[(kb + 1) & 1][k] = lds128(sm + ((kb + 1) * 4 + k) * 2048);
          }
          if constexpr (kb == 3) {
            __syncwarp();
            if (lane == 0) mbar_arrive_remote(mapa(bars + BAR_HREADY + 8 * g, cbit ^ 1));
          }
          if constexpr (kb >= 4) {
            if constexpr (kb == 4) mbar_wait(bars + BAR_HREADY + 8 * g, L);
            st_async128(hdst + (2 * kb - 8) * 2048, hs[2 * kb - 8], hbar1);
            st_async128(hdst + (2 * kb - 7) * 2048, hs[2 * kb - 7], hbar1);
          }
        });
        wg_wait<0>();
        TS(11 + 20 * L);
        fence_acc(acc2);
        keep4(B[1]);
        cons_release<ST_G2 + 7>(sbase, lane);
#pragma unroll
        for (int s = 0; s < 4; s++) hs[8 + s] = glu8<32>(&acc2[8 * s], cl, ch);
#pragma unroll
        for (int s = 0; s < 2; s++) hs[12 + s] = glu8<16>(&acc2[64 + 8 * s], cl, ch);
      }
      {
        PHASE_VARS;
        TS(12 + 20 * L);
        const uint32_t hdst = mapa(areg + t128 * 16, cbit ^ 1);
        const uint32_t hbar2 = mapa(bars + BAR_HRECV + 16 * g + 8, cbit ^ 1);
        uint4* pd = g_arena + c * ARENA + AR_PART + (((slab * 2 + cbit) * 4 + ca) * 16) * 32 + lane;
        const uint4* ps = g_arena + c * ARENA + AR_PART + (((j * 2 + g) * 4) * 16 + 4 * w) * 32 + lane;
        auto fetch_partials = [&]() {
#pragma unroll
          for (int src = 0; src < 4; src++)
#pragma unroll
            for (int k = 0; k < 4; k++) cp_async16(areg + t128 * 16 + (14 + 4 * src + k) * 2048, ps + src * (16 * 32) + k * 32);
        };
        uint4 hb[7];
        float a0[32], a1[32], a2[32], a3[32];
        auto publish = [&](float (&a)[32], int q, int s0, int s1) {
#pragma unroll
          for (int s = s0; s < s1; s++) {
            uint4 o = pack8(&a[8 * s]);
            o.x = set_tag(o.x, tag);
            st_ll(pd + (4 * q + s) * 32, o);
          }
        };
        static_for<0, 16>([&](auto I) {
          constexpr int i = I.value, q = dn_q(i), par = dn_par(i), kh = dn_kh(i);
          auto mm = [&](auto K) {
            constexpr int k = decltype(K)::value;
            constexpr bool init = (k == 0 && par == 0 && kh == 0);
            constexpr uint64_t db = st_desc<ST_DN + i, 2048, 8192, 1024, 1>(k);
            if constexpr (q == 0) { if constexpr (par) wgmma_n64<init, 0>(a0, hb[k], db); else wgmma_n64<init, 0>(a0, hs[7 * kh + k], db); }
            if constexpr (q == 1) { if constexpr (par) wgmma_n64<init, 0>(a1, hb[k], db); else wgmma_n64<init, 0>(a1, hs[7 * kh + k], db); }
            if constexpr (q == 2) { if constexpr (par) wgmma_n64<init, 0>(a2, hb[k], db); else wgmma_n64<init, 0>(a2, hs[7 * kh + k], db); }
            if constexpr (q == 3) { if constexpr (par) wgmma_n64<init, 0>(a3, hb[k], db); else wgmma_n64<init, 0>(a3, hs[7 * kh + k], db); }
          };
          cons_acquire<ST_DN + i>(sbase, L);
          wg_fence();
          mm(IC<0>{}); mm(IC<1>{}); mm(IC<2>{}); mm(IC<3>{}); mm(IC<4>{}); mm(IC<5>{}); mm(IC<6>{});
          wg_commit();
          if constexpr (i > 0) { wg_wait<1>(); cons_release<ST_DN + i - 1>(sbase, lane); }
          if constexpr (i < 3) {
            st_async128(hdst + (8 + 2 * i) * 2048, hs[8 + 2 * i], hbar2);
            st_async128(hdst + (9 + 2 * i) * 2048, hs[9 + 2 * i], hbar2);
          }
          constexpr int n = i + 1;
          if constexpr (n < 16 && dn_par(n) && n != 4 && n != 7) {
            if constexpr (n == 2) { mbar_wait(bars + BAR_HRECV + 16 * g, L); TS(13 + 20 * L); }
            if constexpr (n == 6) { mbar_wait(bars + BAR_HRECV + 16 * g + 8, L); TS(14 + 20 * L); }
#pragma unroll
            for (int k = 0; k < 7; k++) { if constexpr (n != 2) keep(hb[k]); hb[k] = lds128(areg + t128 * 16 + (7 * dn_kh(n) + k) * 2048); }
          }
          if constexpr (i == 7) { fence_acc(a0); publish(a0, 0, 0, 4); }
          if constexpr (i == 8) { fence_acc(a1); publish(a1, 1, 0, 2); }
          if constexpr (i == 9) publish(a1, 1, 2, 4);
          if constexpr (i == 12) { fence_acc(a2); publish(a2, 2, 0, 2); }
          if constexpr (i == 13) publish(a2, 2, 2, 4);
          if constexpr (i == 10) { if (w == 0) fetch_partials(); }
          if constexpr (i == 12) { if (w == 1) fetch_partials(); }
        });
        wg_wait<0>();
        TS(15 + 20 * L);
        fence_acc(a3);
#pragma unroll
        for (int k = 0; k < 7; k++) { keep(hb[k]); keep(hs[7 + k]); }
        cons_release<NSTAGE - 1>(sbase, lane);
        publish(a3, 3, 0, 4);
        if (w >= 2) fetch_partials();
      }
      {
        PHASE_VARS;
        const uint4* xq = g_arena + c * ARENA + AR_XRAW + ((j) * 32 + 4 * warp) * 32 + lane;
        const uint4* ps = g_arena + c * ARENA + AR_PART + (((j * 2 + g) * 4) * 16 + 4 * w) * 32 + lane;
        uint4 xr[4], P[4][4];
        float v[32];
        load_pk<4>(xr, xq);
        cp_wait_all();
#pragma unroll
        for (int k = 0; k < 16; k++) P[k >> 2][k & 3] = lds128(areg + t128 * 16 + (14 + k) * 2048);
        for (uint32_t n = 0; !ok_pk<16>(&P[0][0], tag) && n < SPIN_LIMIT; n++) {
#pragma unroll
          for (int src = 0; src < 4; src++) load_pk<4>(P[src], ps + src * (16 * 32));
        }
        TS(16 + 20 * L);
        ensure_pk<4>(xr, xq, 0u);
#pragma unroll
        for (int i = 0; i < 4; i++) {
          v[8 * i + 0] = bf_lo(xr[i].x); v[8 * i + 1] = bf_hi(xr[i].x); v[8 * i + 2] = bf_lo(xr[i].y); v[8 * i + 3] = bf_hi(xr[i].y);
          v[8 * i + 4] = bf_lo(xr[i].z); v[8 * i + 5] = bf_hi(xr[i].z); v[8 * i + 6] = bf_lo(xr[i].w); v[8 * i + 7] = bf_hi(xr[i].w);
          float d[8] = {0, 0, 0, 0, 0, 0, 0, 0};
#pragma unroll
          for (int src = 0; src < 4; src++) {
            const uint4 p = P[src][i];
            d[0] += bf_lo(p.x); d[1] += bf_hi(p.x); d[2] += bf_lo(p.y); d[3] += bf_hi(p.y);
            d[4] += bf_lo(p.z); d[5] += bf_hi(p.z); d[6] += bf_lo(p.w); d[7] += bf_hi(p.w);
          }
#pragma unroll
          for (int k = 0; k < 8; k++) v[8 * i + k] += d[k];
        }
        if (L == 0) {
          owner_ln_publish(sbase, v, 1u, 0u, xraw);
        } else {
#pragma unroll
          for (int i = 0; i < 4; i++) xraw[i] = make_uint4(0, 0, 0, 0);
          uint32_t* op = reinterpret_cast<uint32_t*>(out + (size_t)(slab_row0(c, j >> 2, j & 3) + 2 * qr) * 512 + warp * 64 + qc * 2);
#pragma unroll
          for (int i = 0; i < 4; i++) {
            op[i * 8] = pack2(v[8 * i], v[8 * i + 1]);
            op[16 * 256 + i * 8] = pack2(v[8 * i + 2], v[8 * i + 3]);
            op[i * 8 + 4] = pack2(v[8 * i + 4], v[8 * i + 5]);
            op[16 * 256 + i * 8 + 4] = pack2(v[8 * i + 6], v[8 * i + 7]);
          }
        }
      }
      TS(17 + 20 * L);
      if (L == 0) { STOP_AT(3); }
    }
    TG(62);
    asm volatile("barrier.cluster.arrive.release.aligned;\nbarrier.cluster.wait.acquire.aligned; // consumer" ::: "memory");
    TG(63);
  }
}

typedef CUresult (*EncodeFn)(CUtensorMap*, CUtensorMapDataType, cuuint32_t, void*, const cuuint64_t*, const cuuint64_t*,
                             const cuuint32_t*, const cuuint32_t*, CUtensorMapInterleave, CUtensorMapSwizzle,
                             CUtensorMapL2promotion, CUtensorMapFloatOOBfill);

void encode(EncodeFn fn, CUtensorMap* m, int rank, const void* base, const cuuint64_t* dims, const cuuint64_t* strides,
            const cuuint32_t* box, CUtensorMapSwizzle sw) {
  cuuint32_t es[5] = {1, 1, 1, 1, 1};
  fn(m, CU_TENSOR_MAP_DATA_TYPE_BFLOAT16, (cuuint32_t)rank, const_cast<void*>(base), dims, strides, box, es,
     CU_TENSOR_MAP_INTERLEAVE_NONE, sw, CU_TENSOR_MAP_L2_PROMOTION_L2_128B, CU_TENSOR_MAP_FLOAT_OOB_FILL_NONE);
}

}

extern "C" void kernel_launch(void* const* d_in, const int* in_sizes, int n_in, void* d_out, int out_size) {
  (void)in_sizes; (void)n_in; (void)out_size;
  const __nv_bfloat16* x = (const __nv_bfloat16*)d_in[0];
  const char* wqkv = (const char*)d_in[1];
  const char* wo = (const char*)d_in[2];
  const char* wg = (const char*)d_in[4];
  const char* wu = (const char*)d_in[5];
  const char* wd = (const char*)d_in[6];

  static EncodeFn fn = nullptr;
  if (!fn) {
    void* p = nullptr;
    cudaDriverEntryPointQueryResult st;
    cudaGetDriverEntryPoint("cuTensorMapEncodeTiled", &p, cudaEnableDefault, &st);
    fn = (EncodeFn)p;
    cudaFuncSetAttribute(fused_kernel, cudaFuncAttributeMaxDynamicSharedMemorySize, SMEM_BYTES);
  }
  CUtensorMap m_qkv, m_wo, m_gu2, m_gu1, m_guh, m_wd112, m_wd80, m_wd32;
  {
    cuuint64_t dims[3] = {512, 512, 3}, str[2] = {3072, 1024};
    cuuint32_t box[3] = {64, 64, 3};
    encode(fn, &m_qkv, 3, wqkv, dims, str, box, CU_TENSOR_MAP_SWIZZLE_128B);
  }
  {
    cuuint64_t dims[2] = {512, 512}, str[1] = {1024};
    cuuint32_t box[2] = {64, 128};
    encode(fn, &m_wo, 2, wo, dims, str, box, CU_TENSOR_MAP_SWIZZLE_128B);
  }
  {
    const char* lo = wg < wu ? wg : wu;
    cuuint64_t diff = (cuuint64_t)(wg < wu ? wu - wg : wg - wu);
    cuuint64_t dims[4] = {1792, 512, 2, 2}, str[3] = {3584, diff, 128};
    cuuint32_t box2[4] = {64, 64, 2, 2}, box1[4] = {64, 64, 2, 1}, boxh[3] = {32, 64, 2};
    encode(fn, &m_gu2, 4, lo, dims, str, box2, CU_TENSOR_MAP_SWIZZLE_128B);
    encode(fn, &m_gu1, 4, lo, dims, str, box1, CU_TENSOR_MAP_SWIZZLE_128B);
    encode(fn, &m_guh, 3, lo, dims, str, boxh, CU_TENSOR_MAP_SWIZZLE_64B);
  }
  {
    cuuint64_t dims[2] = {512, 1792}, str[1] = {1024};
    cuuint32_t b112[2] = {64, 112}, b80[2] = {64, 80}, b32[2] = {64, 32};
    encode(fn, &m_wd112, 2, wd, dims, str, b112, CU_TENSOR_MAP_SWIZZLE_128B);
    encode(fn, &m_wd80, 2, wd, dims, str, b80, CU_TENSOR_MAP_SWIZZLE_128B);
    encode(fn, &m_wd32, 2, wd, dims, str, b32, CU_TENSOR_MAP_SWIZZLE_128B);
  }
  cudaLaunchConfig_t cfg = {};
  cfg.gridDim = dim3(128);
  cfg.blockDim = dim3(NTHREADS);
  cfg.dynamicSmemBytes = SMEM_BYTES;
  cfg.stream = cudaStreamPerThread;
  cudaLaunchAttribute at[1];
  at[0].id = cudaLaunchAttributeClusterDimension;
  at[0].val.clusterDim.x = 2; at[0].val.clusterDim.y = 1; at[0].val.clusterDim.z = 1;
  cfg.attrs = at; cfg.numAttrs = 1;
  cudaLaunchKernelEx(&cfg, fused_kernel, m_qkv, m_wo, m_gu2, m_gu1, m_guh, m_wd112, m_wd80, m_wd32, x, (__nv_bfloat16*)d_out, wo, wg, wu, wd
  );
}
```

```cpp
#include <cuda_runtime.h>
#include <cuda_bf16.h>
#include <cuda.h>
#include <stdint.h>

namespace {

constexpr int NTHREADS = 384;
constexpr int GRAN = 8192;
constexpr int NGRAN = 12;
constexpr int SM_AREG = NGRAN * GRAN;
constexpr int SM_MISC = SM_AREG + 131072;
constexpr int SM_TSTAT = SM_MISC + 256;
constexpr int SMEM_BYTES = SM_TSTAT + 1024;
constexpr int BAR_FULL = 0, BAR_EMPTY = 96, BAR_HRECV = 192, BAR_HREADY = 224;

constexpr int AR_XN = 0, AR_XRAW = 8192, AR_O = 16384, AR_STATS = 24576, AR_HALO = 25088, AR_PART = 33280, ARENA = 66048;
__device__ __align__(1024) uint4 g_arena[16 * ARENA];

#define TS(n)
#define TG(n)
#define OPAQUE(x) asm volatile("" : "+r"(x))
#define PHASE_VARS                                                                                   \
  int tid_ = threadIdx.x, bid_ = blockIdx.x;                                                         \
  OPAQUE(tid_); OPAQUE(bid_);                                                                        \
  const int lane = tid_ & 31, warp = tid_ >> 5, g = warp >> 2, w = warp & 3, t128 = tid_ & 127;      \
  const int qr = lane >> 2, qc = lane & 3, slab = warp;                                              \
  const int c = bid_ >> 3, j = bid_ & 7, ca = j >> 1, cbit = j & 1;                                  \
  const uint32_t areg = sbase + SM_AREG + g * 65536;                                                 \
  (void)g; (void)j; (void)w; (void)t128; (void)qr; (void)qc; (void)slab; (void)c; (void)ca; (void)cbit; (void)areg; (void)lane
#define STOP_AT(n)
#define PSTOP_AT(n)

__device__ __forceinline__ uint32_t smem_u32(const void* p) { return (uint32_t)__cvta_generic_to_shared(p); }
__device__ __forceinline__ void mbar_init(uint32_t bar, uint32_t cnt) {
  asm volatile("mbarrier.init.shared::cta.b64 [%0], %1;" ::"r"(bar), "r"(cnt) : "memory");
}
__device__ __forceinline__ void mbar_expect_tx(uint32_t bar, uint32_t bytes) {
  asm volatile("mbarrier.arrive.expect_tx.shared::cta.b64 _, [%0], %1;" ::"r"(bar), "r"(bytes) : "memory");
}
__device__ __forceinline__ void mbar_arrive(uint32_t bar) {
  asm volatile("mbarrier.arrive.shared::cta.b64 _, [%0];" ::"r"(bar) : "memory");
}
__device__ __forceinline__ void mbar_arrive_remote(uint32_t cluster_addr) {
  asm volatile("mbarrier.arrive.relaxed.cluster.shared::cluster.b64 _, [%0];" ::"r"(cluster_addr) : "memory");
}
__device__ __forceinline__ bool mbar_try(uint32_t bar, uint32_t parity) {
  uint32_t ok;
  asm volatile("{\n.reg .pred p;\nmbarrier.try_wait.parity.shared::cta.b64 p, [%1], %2;\nselp.u32 %0, 1, 0, p;\n}"
               : "=r"(ok) : "r"(bar), "r"(parity) : "memory");
  return ok != 0;
}
constexpr uint32_t SPIN_LIMIT = 1u << 16;
constexpr uint32_t SMEM_ORIGIN = 1024;
__device__ __forceinline__ void mbar_wait(uint32_t bar, uint32_t parity) {
  for (uint32_t n = 0; !mbar_try(bar, parity) && n < SPIN_LIMIT; n++) {}
}
__device__ __forceinline__ uint32_t mapa(uint32_t addr, uint32_t rank) {
  uint32_t r;
  asm volatile("mapa.shared::cluster.u32 %0, %1, %2;" : "=r"(r) : "r"(addr), "r"(rank));
  return r;
}

__device__ __forceinline__ void tma_2d(uint32_t dst, const CUtensorMap* m, uint32_t bar, int c0, int c1) {
  asm volatile("cp.async.bulk.tensor.2d.shared::cluster.global.mbarrier::complete_tx::bytes [%0], [%1, {%3, %4}], [%2];"
               ::"r"(dst), "l"(m), "r"(bar), "r"(c0), "r"(c1) : "memory");
}
__device__ __forceinline__ void tma_3d(uint32_t dst, const CUtensorMap* m, uint32_t bar, int c0, int c1, int c2) {
  asm volatile("cp.async.bulk.tensor.3d.shared::cluster.global.mbarrier::complete_tx::bytes [%0], [%1, {%3, %4, %5}], [%2];"
               ::"r"(dst), "l"(m), "r"(bar), "r"(c0), "r"(c1), "r"(c2) : "memory");
}
__device__ __forceinline__ void tma_4d(uint32_t dst, const CUtensorMap* m, uint32_t bar, int c0, int c1, int c2, int c3) {
  asm volatile("cp.async.bulk.tensor.4d.shared::cluster.global.mbarrier::complete_tx::bytes [%0], [%1, {%3, %4, %5, %6}], [%2];"
               ::"r"(dst), "l"(m), "r"(bar), "r"(c0), "r"(c1), "r"(c2), "r"(c3) : "memory");
}
__device__ __forceinline__ void l2_prefetch(const void* p, uint32_t bytes) {
  asm volatile("cp.async.bulk.prefetch.L2.global [%0], %1;" ::"l"(p), "r"(bytes) : "memory");
}

__device__ __forceinline__ uint4 ld_ll(const uint4* p) {
  uint4 v;
  asm volatile("ld.relaxed.gpu.global.v4.u32 {%0,%1,%2,%3}, [%4];" : "=r"(v.x), "=r"(v.y), "=r"(v.z), "=r"(v.w) : "l"(p) : "memory");
  return v;
}
__device__ __forceinline__ void st_ll(uint4* p, uint4 v) {
  asm volatile("st.relaxed.gpu.global.v4.u32 [%0], {%1,%2,%3,%4};" ::"l"(p), "r"(v.x), "r"(v.y), "r"(v.z), "r"(v.w) : "memory");
}
__device__ __forceinline__ uint4 lds128(uint32_t a) {
  uint4 v;
  asm volatile("ld.shared.v4.u32 {%0,%1,%2,%3}, [%4];" : "=r"(v.x), "=r"(v.y), "=r"(v.z), "=r"(v.w) : "r"(a) : "memory");
  return v;
}
__device__ __forceinline__ void sts128(uint32_t a, uint4 v) {
  asm volatile("st.shared.v4.u32 [%0], {%1,%2,%3,%4};" ::"r"(a), "r"(v.x), "r"(v.y), "r"(v.z), "r"(v.w) : "memory");
}
__device__ __forceinline__ void st_async128(uint32_t cluster_addr, uint4 v, uint32_t cluster_bar) {
  asm volatile("st.async.weak.shared::cluster.mbarrier::complete_tx::bytes.v4.b32 [%0], {%1,%2,%3,%4}, [%5];"
               ::"r"(cluster_addr), "r"(v.x), "r"(v.y), "r"(v.z), "r"(v.w), "r"(cluster_bar) : "memory");
}
__device__ __forceinline__ uint32_t pack2(float lo, float hi) {
  uint32_t r;
  asm("cvt.rn.bf16x2.f32 %0, %1, %2;" : "=r"(r) : "f"(hi), "f"(lo));
  return r;
}
__device__ __forceinline__ float bf_lo(uint32_t w) { return __uint_as_float(w << 16); }
__device__ __forceinline__ float bf_hi(uint32_t w) { return __uint_as_float(w & 0xffff0000u); }
__device__ __forceinline__ uint32_t set_tag(uint32_t w, uint32_t tag) { return (w & ~1u) | tag; }
__device__ __forceinline__ uint32_t movm(uint32_t a) {
  uint32_t d;
  asm("movmatrix.sync.aligned.m8n8.trans.b16 %0, %1;" : "=r"(d) : "r"(a));
  return d;
}
__device__ __forceinline__ void mma16816(float (&d)[4], const uint4& a, uint32_t b0, uint32_t b1) {
  asm("mma.sync.aligned.m16n8k16.row.col.f32.bf16.bf16.f32 {%0,%1,%2,%3}, {%4,%5,%6,%7}, {%8,%9}, {%0,%1,%2,%3};"
               : "+f"(d[0]), "+f"(d[1]), "+f"(d[2]), "+f"(d[3])
               : "r"(a.x), "r"(a.y), "r"(a.z), "r"(a.w), "r"(b0), "r"(b1));
}
__device__ __forceinline__ void mma1688(float (&d)[4], uint32_t a0, uint32_t a1, uint32_t b0) {
  asm("mma.sync.aligned.m16n8k8.row.col.f32.bf16.bf16.f32 {%0,%1,%2,%3}, {%4,%5}, {%6}, {%0,%1,%2,%3};"
      : "+f"(d[0]), "+f"(d[1]), "+f"(d[2]), "+f"(d[3])
      : "r"(a0), "r"(a1), "r"(b0));
}
__device__ __forceinline__ void mma16816_z(float (&d)[4], const uint4& a, uint32_t b0, uint32_t b1) {
  asm("mma.sync.aligned.m16n8k16.row.col.f32.bf16.bf16.f32 {%0,%1,%2,%3}, {%4,%5,%6,%7}, {%8,%9}, {%10,%10,%10,%10};"
      : "=f"(d[0]), "=f"(d[1]), "=f"(d[2]), "=f"(d[3])
      : "r"(a.x), "r"(a.y), "r"(a.z), "r"(a.w), "r"(b0), "r"(b1), "f"(0.f));
}
__device__ __forceinline__ float ex2(float x) {
  float y;
  asm("ex2.approx.ftz.f32 %0, %1;" : "=f"(y) : "f"(x));
  return y;
}
__device__ __forceinline__ float rcp(float x) {
  float y;
  asm("rcp.approx.ftz.f32 %0, %1;" : "=f"(y) : "f"(x));
  return y;
}
__device__ __forceinline__ void cp_async16(uint32_t dst, const void* src) {
  asm volatile("cp.async.cg.shared.global [%0], [%1], 16;" ::"r"(dst), "l"(src) : "memory");
}
__device__ __forceinline__ void cp_wait_all() { asm volatile("cp.async.wait_all;" ::: "memory"); }
__device__ __forceinline__ void cp_commit() { asm volatile("cp.async.commit_group;" ::: "memory"); }
template <int N> __device__ __forceinline__ void cp_wait() { asm volatile("cp.async.wait_group %0;" ::"n"(N) : "memory"); }
__device__ __forceinline__ void bar_wg(int id) { asm volatile("bar.sync %0, 128;" ::"r"(id) : "memory"); }
#define COLD_DELAY 900
__device__ __forceinline__ void cold_delay(uint32_t L) {
  if (L == 0) {
    const uint32_t t0 = (uint32_t)clock();
    while ((uint32_t)clock() - t0 < COLD_DELAY) {}
  }
}
__device__ __forceinline__ void wg_fence() { asm volatile("wgmma.fence.sync.aligned;" ::: "memory"); }
__device__ __forceinline__ void wg_commit() { asm volatile("wgmma.commit_group.sync.aligned;" ::: "memory"); }
template <int N> __device__ __forceinline__ void wg_wait() { asm volatile("wgmma.wait_group.sync.aligned %0;" ::"n"(N) : "memory"); }
__device__ __forceinline__ void keep(const uint4& a) { asm volatile("" ::"r"(a.x), "r"(a.y), "r"(a.z), "r"(a.w) : "memory"); }
template <int T> __device__ __forceinline__ void zero_acc(float (&d)[T]) {
#pragma unroll
  for (int i = 0; i < T; i++) d[i] = 0.f;
}
template <int T> __device__ __forceinline__ void fence_acc(float (&d)[T]) {
#pragma unroll
  for (int i = 0; i < T; i++) asm volatile("" : "+f"(d[i])::"memory");
}

template <int O, int T> __device__ __forceinline__ void wgmma_rs_n64(float (&d)[T], const uint4& a, uint64_t db) {
  asm volatile("{\n.reg .pred p;\nsetp.ne.b32 p, 1, 0;\n"
    "wgmma.mma_async.sync.aligned.m64n64k16.f32.bf16.bf16 "
    "{%0, %1, %2, %3, %4, %5, %6, %7, %8, %9, %10, %11, %12, %13, %14, %15, "
    "%16, %17, %18, %19, %20, %21, %22, %23, %24, %25, %26, %27, %28, %29, %30, %31}, "
    "{%32, %33, %34, %35}, %36, p, 1, 1, 1;\n}\n"
    : "+f"(d[O + 0]), "+f"(d[O + 1]), "+f"(d[O + 2]), "+f"(d[O + 3]), "+f"(d[O + 4]), "+f"(d[O + 5]), "+f"(d[O + 6]), "+f"(d[O + 7]),
      "+f"(d[O + 8]), "+f"(d[O + 9]), "+f"(d[O + 10]), "+f"(d[O + 11]), "+f"(d[O + 12]), "+f"(d[O + 13]), "+f"(d[O + 14]), "+f"(d[O + 15]),
      "+f"(d[O + 16]), "+f"(d[O + 17]), "+f"(d[O + 18]), "+f"(d[O + 19]), "+f"(d[O + 20]), "+f"(d[O + 21]), "+f"(d[O + 22]), "+f"(d[O + 23]),
      "+f"(d[O + 24]), "+f"(d[O + 25]), "+f"(d[O + 26]), "+f"(d[O + 27]), "+f"(d[O + 28]), "+f"(d[O + 29]), "+f"(d[O + 30]), "+f"(d[O + 31])
    : "r"(a.x), "r"(a.y), "r"(a.z), "r"(a.w), "l"(db));
}
template <int O, int T> __device__ __forceinline__ void wgmma_rs_n64_init(float (&d)[T], const uint4& a, uint64_t db) {
  asm volatile("{\n.reg .pred p;\nsetp.ne.b32 p, 0, 0;\n"
    "wgmma.mma_async.sync.aligned.m64n64k16.f32.bf16.bf16 "
    "{%0, %1, %2, %3, %4, %5, %6, %7, %8, %9, %10, %11, %12, %13, %14, %15, "
    "%16, %17, %18, %19, %20, %21, %22, %23, %24, %25, %26, %27, %28, %29, %30, %31}, "
    "{%32, %33, %34, %35}, %36, p, 1, 1, 1;\n}\n"
    : "=f"(d[O + 0]), "=f"(d[O + 1]), "=f"(d[O + 2]), "=f"(d[O + 3]), "=f"(d[O + 4]), "=f"(d[O + 5]), "=f"(d[O + 6]), "=f"(d[O + 7]),
      "=f"(d[O + 8]), "=f"(d[O + 9]), "=f"(d[O + 10]), "=f"(d[O + 11]), "=f"(d[O + 12]), "=f"(d[O + 13]), "=f"(d[O + 14]), "=f"(d[O + 15]),
      "=f"(d[O + 16]), "=f"(d[O + 17]), "=f"(d[O + 18]), "=f"(d[O + 19]), "=f"(d[O + 20]), "=f"(d[O + 21]), "=f"(d[O + 22]), "=f"(d[O + 23]),
      "=f"(d[O + 24]), "=f"(d[O + 25]), "=f"(d[O + 26]), "=f"(d[O + 27]), "=f"(d[O + 28]), "=f"(d[O + 29]), "=f"(d[O + 30]), "=f"(d[O + 31])
    : "r"(a.x), "r"(a.y), "r"(a.z), "r"(a.w), "l"(db));
}
template <bool INIT, int O, int T> __device__ __forceinline__ void wgmma_n64(float (&d)[T], const uint4& a, uint64_t db) {
  if constexpr (INIT) wgmma_rs_n64_init<O>(d, a, db); else wgmma_rs_n64<O>(d, a, db);
}
template <int O, int T> __device__ __forceinline__ void wgmma_rs_n128(float (&d)[T], const uint4& a, uint64_t db) {
  asm volatile("{\n.reg .pred p;\nsetp.ne.b32 p, 1, 0;\n"
    "wgmma.mma_async.sync.aligned.m64n128k16.f32.bf16.bf16 "
    "{%0, %1, %2, %3, %4, %5, %6, %7, %8, %9, %10, %11, %12, %13, %14, %15, "
    "%16, %17, %18, %19, %20, %21, %22, %23, %24, %25, %26, %27, %28, %29, %30, %31, "
    "%32, %33, %34, %35, %36, %37, %38, %39, %40, %41, %42, %43, %44, %45, %46, %47, "
    "%48, %49, %50, %51, %52, %53, %54, %55, %56, %57, %58, %59, %60, %61, %62, %63}, "
    "{%64, %65, %66, %67}, %68, p, 1, 1, 1;\n}\n"
    : "+f"(d[O + 0]), "+f"(d[O + 1]), "+f"(d[O + 2]), "+f"(d[O + 3]), "+f"(d[O + 4]), "+f"(d[O + 5]), "+f"(d[O + 6]), "+f"(d[O + 7]),
      "+f"(d[O + 8]), "+f"(d[O + 9]), "+f"(d[O + 10]), "+f"(d[O + 11]), "+f"(d[O + 12]), "+f"(d[O + 13]), "+f"(d[O + 14]), "+f"(d[O + 15]),
      "+f"(d[O + 16]), "+f"(d[O + 17]), "+f"(d[O + 18]), "+f"(d[O + 19]), "+f"(d[O + 20]), "+f"(d[O + 21]), "+f"(d[O + 22]), "+f"(d[O + 23]),
      "+f"(d[O + 24]), "+f"(d[O + 25]), "+f"(d[O + 26]), "+f"(d[O + 27]), "+f"(d[O + 28]), "+f"(d[O + 29]), "+f"(d[O + 30]), "+f"(d[O + 31]),
      "+f"(d[O + 32]), "+f"(d[O + 33]), "+f"(d[O + 34]), "+f"(d[O + 35]), "+f"(d[O + 36]), "+f"(d[O + 37]), "+f"(d[O + 38]), "+f"(d[O + 39]),
      "+f"(d[O + 40]), "+f"(d[O + 41]), "+f"(d[O + 42]), "+f"(d[O + 43]), "+f"(d[O + 44]), "+f"(d[O + 45]), "+f"(d[O + 46]), "+f"(d[O + 47]),
      "+f"(d[O + 48]), "+f"(d[O + 49]), "+f"(d[O + 50]), "+f"(d[O + 51]), "+f"(d[O + 52]), "+f"(d[O + 53]), "+f"(d[O + 54]), "+f"(d[O + 55]),
      "+f"(d[O + 56]), "+f"(d[O + 57]), "+f"(d[O + 58]), "+f"(d[O + 59]), "+f"(d[O + 60]), "+f"(d[O + 61]), "+f"(d[O + 62]), "+f"(d[O + 63])
    : "r"(a.x), "r"(a.y), "r"(a.z), "r"(a.w), "l"(db));
}
template <int O, int T> __device__ __forceinline__ void wgmma_rs_n128_init(float (&d)[T], const uint4& a, uint64_t db) {
  asm volatile("{\n.reg .pred p;\nsetp.ne.b32 p, 0, 0;\n"
    "wgmma.mma_async.sync.aligned.m64n128k16.f32.bf16.bf16 "
    "{%0, %1, %2, %3, %4, %5, %6, %7, %8, %9, %10, %11, %12, %13, %14, %15, "
    "%16, %17, %18, %19, %20, %21, %22, %23, %24, %25, %26, %27, %28, %29, %30, %31, "
    "%32, %33, %34, %35, %36, %37, %38, %39, %40, %41, %42, %43, %44, %45, %46, %47, "
    "%48, %49, %50, %51, %52, %53, %54, %55, %56, %57, %58, %59, %60, %61, %62, %63}, "
    "{%64, %65, %66, %67}, %68, p, 1, 1, 1;\n}\n"
    : "=f"(d[O + 0]), "=f"(d[O + 1]), "=f"(d[O + 2]), "=f"(d[O + 3]), "=f"(d[O + 4]), "=f"(d[O + 5]), "=f"(d[O + 6]), "=f"(d[O + 7]),
      "=f"(d[O + 8]), "=f"(d[O + 9]), "=f"(d[O + 10]), "=f"(d[O + 11]), "=f"(d[O + 12]), "=f"(d[O + 13]), "=f"(d[O + 14]), "=f"(d[O + 15]),
      "=f"(d[O + 16]), "=f"(d[O + 17]), "=f"(d[O + 18]), "=f"(d[O + 19]), "=f"(d[O + 20]), "=f"(d[O + 21]), "=f"(d[O + 22]), "=f"(d[O + 23]),
      "=f"(d[O + 24]), "=f"(d[O + 25]), "=f"(d[O + 26]), "=f"(d[O + 27]), "=f"(d[O + 28]), "=f"(d[O + 29]), "=f"(d[O + 30]), "=f"(d[O + 31]),
      "=f"(d[O + 32]), "=f"(d[O + 33]), "=f"(d[O + 34]), "=f"(d[O + 35]), "=f"(d[O + 36]), "=f"(d[O + 37]), "=f"(d[O + 38]), "=f"(d[O + 39]),
      "=f"(d[O + 40]), "=f"(d[O + 41]), "=f"(d[O + 42]), "=f"(d[O + 43]), "=f"(d[O + 44]), "=f"(d[O + 45]), "=f"(d[O + 46]), "=f"(d[O + 47]),
      "=f"(d[O + 48]), "=f"(d[O + 49]), "=f"(d[O + 50]), "=f"(d[O + 51]), "=f"(d[O + 52]), "=f"(d[O + 53]), "=f"(d[O + 54]), "=f"(d[O + 55]),
      "=f"(d[O + 56]), "=f"(d[O + 57]), "=f"(d[O + 58]), "=f"(d[O + 59]), "=f"(d[O + 60]), "=f"(d[O + 61]), "=f"(d[O + 62]), "=f"(d[O + 63])
    : "r"(a.x), "r"(a.y), "r"(a.z), "r"(a.w), "l"(db));
}
template <bool INIT, int O, int T> __device__ __forceinline__ void wgmma_n128(float (&d)[T], const uint4& a, uint64_t db) {
  if constexpr (INIT) wgmma_rs_n128_init<O>(d, a, db); else wgmma_rs_n128<O>(d, a, db);
}
template <int O, int T> __device__ __forceinline__ void wgmma_rs_n192(float (&d)[T], const uint4& a, uint64_t db) {
  asm volatile("{\n.reg .pred p;\nsetp.ne.b32 p, 1, 0;\n"
    "wgmma.mma_async.sync.aligned.m64n192k16.f32.bf16.bf16 "
    "{%0, %1, %2, %3, %4, %5, %6, %7, %8, %9, %10, %11, %12, %13, %14, %15, "
    "%16, %17, %18, %19, %20, %21, %22, %23, %24, %25, %26, %27, %28, %29, %30, %31, "
    "%32, %33, %34, %35, %36, %37, %38, %39, %40, %41, %42, %43, %44, %45, %46, %47, "
    "%48, %49, %50, %51, %52, %53, %54, %55, %56, %57, %58, %59, %60, %61, %62, %63, "
    "%64, %65, %66, %67, %68, %69, %70, %71, %72, %73, %74, %75, %76, %77, %78, %79, "
    "%80, %81, %82, %83, %84, %85, %86, %87, %88, %89, %90, %91, %92, %93, %94, %95}, "
    "{%96, %97, %98, %99}, %100, p, 1, 1, 1;\n}\n"
    : "+f"(d[O + 0]), "+f"(d[O + 1]), "+f"(d[O + 2]), "+f"(d[O + 3]), "+f"(d[O + 4]), "+f"(d[O + 5]), "+f"(d[O + 6]), "+f"(d[O + 7]),
      "+f"(d[O + 8]), "+f"(d[O + 9]), "+f"(d[O + 10]), "+f"(d[O + 11]), "+f"(d[O + 12]), "+f"(d[O + 13]), "+f"(d[O + 14]), "+f"(d[O + 15]),
      "+f"(d[O + 16]), "+f"(d[O + 17]), "+f"(d[O + 18]), "+f"(d[O + 19]), "+f"(d[O + 20]), "+f"(d[O + 21]), "+f"(d[O + 22]), "+f"(d[O + 23]),
      "+f"(d[O + 24]), "+f"(d[O + 25]), "+f"(d[O + 26]), "+f"(d[O + 27]), "+f"(d[O + 28]), "+f"(d[O + 29]), "+f"(d[O + 30]), "+f"(d[O + 31]),
      "+f"(d[O + 32]), "+f"(d[O + 33]), "+f"(d[O + 34]), "+f"(d[O + 35]), "+f"(d[O + 36]), "+f"(d[O + 37]), "+f"(d[O + 38]), "+f"(d[O + 39]),
      "+f"(d[O + 40]), "+f"(d[O + 41]), "+f"(d[O + 42]), "+f"(d[O + 43]), "+f"(d[O + 44]), "+f"(d[O + 45]), "+f"(d[O + 46]), "+f"(d[O + 47]),
      "+f"(d[O + 48]), "+f"(d[O + 49]), "+f"(d[O + 50]), "+f"(d[O + 51]), "+f"(d[O + 52]), "+f"(d[O + 53]), "+f"(d[O + 54]), "+f"(d[O + 55]),
      "+f"(d[O + 56]), "+f"(d[O + 57]), "+f"(d[O + 58]), "+f"(d[O + 59]), "+f"(d[O + 60]), "+f"(d[O + 61]), "+f"(d[O + 62]), "+f"(d[O + 63]),
      "+f"(d[O + 64]), "+f"(d[O + 65]), "+f"(d[O + 66]), "+f"(d[O + 67]), "+f"(d[O + 68]), "+f"(d[O + 69]), "+f"(d[O + 70]), "+f"(d[O + 71]),
      "+f"(d[O + 72]), "+f"(d[O + 73]), "+f"(d[O + 74]), "+f"(d[O + 75]), "+f"(d[O + 76]), "+f"(d[O + 77]), "+f"(d[O + 78]), "+f"(d[O + 79]),
      "+f"(d[O + 80]), "+f"(d[O + 81]), "+f"(d[O + 82]), "+f"(d[O + 83]), "+f"(d[O + 84]), "+f"(d[O + 85]), "+f"(d[O + 86]), "+f"(d[O + 87]),
      "+f"(d[O + 88]), "+f"(d[O + 89]), "+f"(d[O + 90]), "+f"(d[O + 91]), "+f"(d[O + 92]), "+f"(d[O + 93]), "+f"(d[O + 94]), "+f"(d[O + 95])
    : "r"(a.x), "r"(a.y), "r"(a.z), "r"(a.w), "l"(db));
}
template <int O, int T> __device__ __forceinline__ void wgmma_rs_n192_init(float (&d)[T], const uint4& a, uint64_t db) {
  asm volatile("{\n.reg .pred p;\nsetp.ne.b32 p, 0, 0;\n"
    "wgmma.mma_async.sync.aligned.m64n192k16.f32.bf16.bf16 "
    "{%0, %1, %2, %3, %4, %5, %6, %7, %8, %9, %10, %11, %12, %13, %14, %15, "
    "%16, %17, %18, %19, %20, %21, %22, %23, %24, %25, %26, %27, %28, %29, %30, %31, "
    "%32, %33, %34, %35, %36, %37, %38, %39, %40, %41, %42, %43, %44, %45, %46, %47, "
    "%48, %49, %50, %51, %52, %53, %54, %55, %56, %57, %58, %59, %60, %61, %62, %63, "
    "%64, %65, %66, %67, %68, %69, %70, %71, %72, %73, %74, %75, %76, %77, %78, %79, "
    "%80, %81, %82, %83, %84, %85, %86, %87, %88, %89, %90, %91, %92, %93, %94, %95}, "
    "{%96, %97, %98, %99}, %100, p, 1, 1, 1;\n}\n"
    : "=f"(d[O + 0]), "=f"(d[O + 1]), "=f"(d[O + 2]), "=f"(d[O + 3]), "=f"(d[O + 4]), "=f"(d[O + 5]), "=f"(d[O + 6]), "=f"(d[O + 7]),
      "=f"(d[O + 8]), "=f"(d[O + 9]), "=f"(d[O + 10]), "=f"(d[O + 11]), "=f"(d[O + 12]), "=f"(d[O + 13]), "=f"(d[O + 14]), "=f"(d[O + 15]),
      "=f"(d[O + 16]), "=f"(d[O + 17]), "=f"(d[O + 18]), "=f"(d[O + 19]), "=f"(d[O + 20]), "=f"(d[O + 21]), "=f"(d[O + 22]), "=f"(d[O + 23]),
      "=f"(d[O + 24]), "=f"(d[O + 25]), "=f"(d[O + 26]), "=f"(d[O + 27]), "=f"(d[O + 28]), "=f"(d[O + 29]), "=f"(d[O + 30]), "=f"(d[O + 31]),
      "=f"(d[O + 32]), "=f"(d[O + 33]), "=f"(d[O + 34]), "=f"(d[O + 35]), "=f"(d[O + 36]), "=f"(d[O + 37]), "=f"(d[O + 38]), "=f"(d[O + 39]),
      "=f"(d[O + 40]), "=f"(d[O + 41]), "=f"(d[O + 42]), "=f"(d[O + 43]), "=f"(d[O + 44]), "=f"(d[O + 45]), "=f"(d[O + 46]), "=f"(d[O + 47]),
      "=f"(d[O + 48]), "=f"(d[O + 49]), "=f"(d[O + 50]), "=f"(d[O + 51]), "=f"(d[O + 52]), "=f"(d[O + 53]), "=f"(d[O + 54]), "=f"(d[O + 55]),
      "=f"(d[O + 56]), "=f"(d[O + 57]), "=f"(d[O + 58]), "=f"(d[O + 59]), "=f"(d[O + 60]), "=f"(d[O + 61]), "=f"(d[O + 62]), "=f"(d[O + 63]),
      "=f"(d[O + 64]), "=f"(d[O + 65]), "=f"(d[O + 66]), "=f"(d[O + 67]), "=f"(d[O + 68]), "=f"(d[O + 69]), "=f"(d[O + 70]), "=f"(d[O + 71]),
      "=f"(d[O + 72]), "=f"(d[O + 73]), "=f"(d[O + 74]), "=f"(d[O + 75]), "=f"(d[O + 76]), "=f"(d[O + 77]), "=f"(d[O + 78]), "=f"(d[O + 79]),
      "=f"(d[O + 80]), "=f"(d[O + 81]), "=f"(d[O + 82]), "=f"(d[O + 83]), "=f"(d[O + 84]), "=f"(d[O + 85]), "=f"(d[O + 86]), "=f"(d[O + 87]),
      "=f"(d[O + 88]), "=f"(d[O + 89]), "=f"(d[O + 90]), "=f"(d[O + 91]), "=f"(d[O + 92]), "=f"(d[O + 93]), "=f"(d[O + 94]), "=f"(d[O + 95])
    : "r"(a.x), "r"(a.y), "r"(a.z), "r"(a.w), "l"(db));
}
template <bool INIT, int O, int T> __device__ __forceinline__ void wgmma_n192(float (&d)[T], const uint4& a, uint64_t db) {
  if constexpr (INIT) wgmma_rs_n192_init<O>(d, a, db); else wgmma_rs_n192<O>(d, a, db);
}
template <int O, int T> __device__ __forceinline__ void wgmma_rs_n256(float (&d)[T], const uint4& a, uint64_t db) {
  asm volatile("{\n.reg .pred p;\nsetp.ne.b32 p, 1, 0;\n"
    "wgmma.mma_async.sync.aligned.m64n256k16.f32.bf16.bf16 "
    "{%0, %1, %2, %3, %4, %5, %6, %7, %8, %9, %10, %11, %12, %13, %14, %15, "
    "%16, %17, %18, %19, %20, %21, %22, %23, %24, %25, %26, %27, %28, %29, %30, %31, "
    "%32, %33, %34, %35, %36, %37, %38, %39, %40, %41, %42, %43, %44, %45, %46, %47, "
    "%48, %49, %50, %51, %52, %53, %54, %55, %56, %57, %58, %59, %60, %61, %62, %63, "
    "%64, %65, %66, %67, %68, %69, %70, %71, %72, %73, %74, %75, %76, %77, %78, %79, "
    "%80, %81, %82, %83, %84, %85, %86, %87, %88, %89, %90, %91, %92, %93, %94, %95, "
    "%96, %97, %98, %99, %100, %101, %102, %103, %104, %105, %106, %107, %108, %109, %110, %111, "
    "%112, %113, %114, %115, %116, %117, %118, %119, %120, %121, %122, %123, %124, %125, %126, %127}, "
    "{%128, %129, %130, %131}, %132, p, 1, 1, 1;\n}\n"
    : "+f"(d[O + 0]), "+f"(d[O + 1]), "+f"(d[O + 2]), "+f"(d[O + 3]), "+f"(d[O + 4]), "+f"(d[O + 5]), "+f"(d[O + 6]), "+f"(d[O + 7]),
      "+f"(d[O + 8]), "+f"(d[O + 9]), "+f"(d[O + 10]), "+f"(d[O + 11]), "+f"(d[O + 12]), "+f"(d[O + 13]), "+f"(d[O + 14]), "+f"(d[O + 15]),
      "+f"(d[O + 16]), "+f"(d[O + 17]), "+f"(d[O + 18]), "+f"(d[O + 19]), "+f"(d[O + 20]), "+f"(d[O + 21]), "+f"(d[O + 22]), "+f"(d[O + 23]),
      "+f"(d[O + 24]), "+f"(d[O + 25]), "+f"(d[O + 26]), "+f"(d[O + 27]), "+f"(d[O + 28]), "+f"(d[O + 29]), "+f"(d[O + 30]), "+f"(d[O + 31]),
      "+f"(d[O + 32]), "+f"(d[O + 33]), "+f"(d[O + 34]), "+f"(d[O + 35]), "+f"(d[O + 36]), "+f"(d[O + 37]), "+f"(d[O + 38]), "+f"(d[O + 39]),
      "+f"(d[O + 40]), "+f"(d[O + 41]), "+f"(d[O + 42]), "+f"(d[O + 43]), "+f"(d[O + 44]), "+f"(d[O + 45]), "+f"(d[O + 46]), "+f"(d[O + 47]),
      "+f"(d[O + 48]), "+f"(d[O + 49]), "+f"(d[O + 50]), "+f"(d[O + 51]), "+f"(d[O + 52]), "+f"(d[O + 53]), "+f"(d[O + 54]), "+f"(d[O + 55]),
      "+f"(d[O + 56]), "+f"(d[O + 57]), "+f"(d[O + 58]), "+f"(d[O + 59]), "+f"(d[O + 60]), "+f"(d[O + 61]), "+f"(d[O + 62]), "+f"(d[O + 63]),
      "+f"(d[O + 64]), "+f"(d[O + 65]), "+f"(d[O + 66]), "+f"(d[O + 67]), "+f"(d[O + 68]), "+f"(d[O + 69]), "+f"(d[O + 70]), "+f"(d[O + 71]),
      "+f"(d[O + 72]), "+f"(d[O + 73]), "+f"(d[O + 74]), "+f"(d[O + 75]), "+f"(d[O + 76]), "+f"(d[O + 77]), "+f"(d[O + 78]), "+f"(d[O + 79]),
      "+f"(d[O + 80]), "+f"(d[O + 81]), "+f"(d[O + 82]), "+f"(d[O + 83]), "+f"(d[O + 84]), "+f"(d[O + 85]), "+f"(d[O + 86]), "+f"(d[O + 87]),
      "+f"(d[O + 88]), "+f"(d[O + 89]), "+f"(d[O + 90]), "+f"(d[O + 91]), "+f"(d[O + 92]), "+f"(d[O + 93]), "+f"(d[O + 94]), "+f"(d[O + 95]),
      "+f"(d[O + 96]), "+f"(d[O + 97]), "+f"(d[O + 98]), "+f"(d[O + 99]), "+f"(d[O + 100]), "+f"(d[O + 101]), "+f"(d[O + 102]), "+f"(d[O + 103]),
      "+f"(d[O + 104]), "+f"(d[O + 105]), "+f"(d[O + 106]), "+f"(d[O + 107]), "+f"(d[O + 108]), "+f"(d[O + 109]), "+f"(d[O + 110]), "+f"(d[O + 111]),
      "+f"(d[O + 112]), "+f"(d[O + 113]), "+f"(d[O + 114]), "+f"(d[O + 115]), "+f"(d[O + 116]), "+f"(d[O + 117]), "+f"(d[O + 118]), "+f"(d[O + 119]),
      "+f"(d[O + 120]), "+f"(d[O + 121]), "+f"(d[O + 122]), "+f"(d[O + 123]), "+f"(d[O + 124]), "+f"(d[O + 125]), "+f"(d[O + 126]), "+f"(d[O + 127])
    : "r"(a.x), "r"(a.y), "r"(a.z), "r"(a.w), "l"(db));
}
template <int O, int T> __device__ __forceinline__ void wgmma_rs_n256_init(float (&d)[T], const uint4& a, uint64_t db) {
  asm volatile("{\n.reg .pred p;\nsetp.ne.b32 p, 0, 0;\n"
    "wgmma.mma_async.sync.aligned.m64n256k16.f32.bf16.bf16 "
    "{%0, %1, %2, %3, %4, %5, %6, %7, %8, %9, %10, %11, %12, %13, %14, %15, "
    "%16, %17, %18, %19, %20, %21, %22, %23, %24, %25, %26, %27, %28, %29, %30, %31, "
    "%32, %33, %34, %35, %36, %37, %38, %39, %40, %41, %42, %43, %44, %45, %46, %47, "
    "%48, %49, %50, %51, %52, %53, %54, %55, %56, %57, %58, %59, %60, %61, %62, %63, "
    "%64, %65, %66, %67, %68, %69, %70, %71, %72, %73, %74, %75, %76, %77, %78, %79, "
    "%80, %81, %82, %83, %84, %85, %86, %87, %88, %89, %90, %91, %92, %93, %94, %95, "
    "%96, %97, %98, %99, %100, %101, %102, %103, %104, %105, %106, %107, %108, %109, %110, %111, "
    "%112, %113, %114, %115, %116, %117, %118, %119, %120, %121, %122, %123, %124, %125, %126, %127}, "
    "{%128, %129, %130, %131}, %132, p, 1, 1, 1;\n}\n"
    : "=f"(d[O + 0]), "=f"(d[O + 1]), "=f"(d[O + 2]), "=f"(d[O + 3]), "=f"(d[O + 4]), "=f"(d[O + 5]), "=f"(d[O + 6]), "=f"(d[O + 7]),
      "=f"(d[O + 8]), "=f"(d[O + 9]), "=f"(d[O + 10]), "=f"(d[O + 11]), "=f"(d[O + 12]), "=f"(d[O + 13]), "=f"(d[O + 14]), "=f"(d[O + 15]),
      "=f"(d[O + 16]), "=f"(d[O + 17]), "=f"(d[O + 18]), "=f"(d[O + 19]), "=f"(d[O + 20]), "=f"(d[O + 21]), "=f"(d[O + 22]), "=f"(d[O + 23]),
      "=f"(d[O + 24]), "=f"(d[O + 25]), "=f"(d[O + 26]), "=f"(d[O + 27]), "=f"(d[O + 28]), "=f"(d[O + 29]), "=f"(d[O + 30]), "=f"(d[O + 31]),
      "=f"(d[O + 32]), "=f"(d[O + 33]), "=f"(d[O + 34]), "=f"(d[O + 35]), "=f"(d[O + 36]), "=f"(d[O + 37]), "=f"(d[O + 38]), "=f"(d[O + 39]),
      "=f"(d[O + 40]), "=f"(d[O + 41]), "=f"(d[O + 42]), "=f"(d[O + 43]), "=f"(d[O + 44]), "=f"(d[O + 45]), "=f"(d[O + 46]), "=f"(d[O + 47]),
      "=f"(d[O + 48]), "=f"(d[O + 49]), "=f"(d[O + 50]), "=f"(d[O + 51]), "=f"(d[O + 52]), "=f"(d[O + 53]), "=f"(d[O + 54]), "=f"(d[O + 55]),
      "=f"(d[O + 56]), "=f"(d[O + 57]), "=f"(d[O + 58]), "=f"(d[O + 59]), "=f"(d[O + 60]), "=f"(d[O + 61]), "=f"(d[O + 62]), "=f"(d[O + 63]),
      "=f"(d[O + 64]), "=f"(d[O + 65]), "=f"(d[O + 66]), "=f"(d[O + 67]), "=f"(d[O + 68]), "=f"(d[O + 69]), "=f"(d[O + 70]), "=f"(d[O + 71]),
      "=f"(d[O + 72]), "=f"(d[O + 73]), "=f"(d[O + 74]), "=f"(d[O + 75]), "=f"(d[O + 76]), "=f"(d[O + 77]), "=f"(d[O + 78]), "=f"(d[O + 79]),
      "=f"(d[O + 80]), "=f"(d[O + 81]), "=f"(d[O + 82]), "=f"(d[O + 83]), "=f"(d[O + 84]), "=f"(d[O + 85]), "=f"(d[O + 86]), "=f"(d[O + 87]),
      "=f"(d[O + 88]), "=f"(d[O + 89]), "=f"(d[O + 90]), "=f"(d[O + 91]), "=f"(d[O + 92]), "=f"(d[O + 93]), "=f"(d[O + 94]), "=f"(d[O + 95]),
      "=f"(d[O + 96]), "=f"(d[O + 97]), "=f"(d[O + 98]), "=f"(d[O + 99]), "=f"(d[O + 100]), "=f"(d[O + 101]), "=f"(d[O + 102]), "=f"(d[O + 103]),
      "=f"(d[O + 104]), "=f"(d[O + 105]), "=f"(d[O + 106]), "=f"(d[O + 107]), "=f"(d[O + 108]), "=f"(d[O + 109]), "=f"(d[O + 110]), "=f"(d[O + 111]),
      "=f"(d[O + 112]), "=f"(d[O + 113]), "=f"(d[O + 114]), "=f"(d[O + 115]), "=f"(d[O + 116]), "=f"(d[O + 117]), "=f"(d[O + 118]), "=f"(d[O + 119]),
      "=f"(d[O + 120]), "=f"(d[O + 121]), "=f"(d[O + 122]), "=f"(d[O + 123]), "=f"(d[O + 124]), "=f"(d[O + 125]), "=f"(d[O + 126]), "=f"(d[O + 127])
    : "r"(a.x), "r"(a.y), "r"(a.z), "r"(a.w), "l"(db));
}
template <bool INIT, int O, int T> __device__ __forceinline__ void wgmma_n256(float (&d)[T], const uint4& a, uint64_t db) {
  if constexpr (INIT) wgmma_rs_n256_init<O>(d, a, db); else wgmma_rs_n256<O>(d, a, db);
}

template <int N> __device__ __forceinline__ void load_pk(uint4* a, const uint4* p) {
#pragma unroll
  for (int i = 0; i < N; i++) a[i] = ld_ll(p + i * 32);
}
__device__ __forceinline__ uint32_t xor_or(uint32_t a, uint32_t b, uint32_t t) {
  uint32_t r;
  asm("lop3.b32 %0, %1, %2, %3, 0x7E;" : "=r"(r) : "r"(a), "r"(b), "r"(t));
  return r;
}
template <int N> __device__ __forceinline__ bool ok_pk(const uint4* a, uint32_t tag) {
  static_assert(N % 2 == 0, "");
  uint32_t x = xor_or(a[0].x, a[1].x, tag);
#pragma unroll
  for (int i = 2; i < N; i += 2) x |= xor_or(a[i].x, a[i + 1].x, tag);
  return __all_sync(0xffffffffu, (x & 1u) == 0u);
}
template <int N> __device__ __forceinline__ void ensure_pk(uint4* a, const uint4* p, uint32_t tag) {
  if (ok_pk<N>(a, tag)) return;
  uint32_t n = 0;
  do { load_pk<N>(a, p); } while (!ok_pk<N>(a, tag) && ++n < SPIN_LIMIT);
}

constexpr int NSTAGE = 44;
constexpr int ST_WO = 8, ST_G1 = 12, ST_G2 = 20, ST_DN = 28;
__host__ __device__ constexpr int st_len(int s) { return s < ST_WO ? 3 : s < ST_G1 ? 2 : s < ST_G2 ? 4 : s < ST_DN ? 3 : 2; }
__host__ __device__ constexpr int st_g0(int s) {
  int pos = 0, g0 = 0;
  for (int i = 0; i <= s; i++) {
    if (pos + st_len(i) > NGRAN) pos = 0;
    g0 = pos;
    pos += st_len(i);
  }
  return g0;
}
__host__ __device__ constexpr int cnt_first(int g, int s) {
  int n = 0;
  for (int i = 0; i < s; i++) n += (st_g0(i) == g);
  return n;
}
__host__ __device__ constexpr int cnt_cover(int g, int s) {
  int n = 0;
  for (int i = 0; i < s; i++) n += (g >= st_g0(i) && g < st_g0(i) + st_len(i));
  return n;
}
__host__ __device__ constexpr uint32_t flip_mask(int s0, int s1) {
  uint32_t m = 0;
  for (int i = s0; i < s1; i++) m ^= ((1u << st_len(i)) - 1u) << st_g0(i);
  return m;
}
__host__ __device__ constexpr int dn_q(int i) { return i < 3 ? 0 : i < 6 ? 1 : i == 6 ? 0 : i == 7 ? 1 : i < 12 ? 2 : 3; }
__host__ __device__ constexpr int dn_par(int i) { return i < 8 ? (i == 2 || i == 4 || i >= 6) : (i & 1); }
__host__ __device__ constexpr int dn_kh(int i) { return i < 8 ? (i == 1 || i >= 5) : ((i & 3) >= 2); }
template <int I> struct IC { static constexpr int value = I; };
template <int B, int E, typename F> __device__ __forceinline__ void static_for(F&& f) {
  if constexpr (B < E) { f(IC<B>{}); static_for<B + 1, E>(f); }
}
template <int S> __device__ __forceinline__ void cons_acquire(uint32_t sbase, uint32_t L) {
  constexpr int g0 = st_g0(S);
  constexpr uint32_t p0 = cnt_first(g0, S) & 1, odd = cnt_first(g0, NSTAGE) & 1;
  mbar_wait(sbase + SM_MISC + BAR_FULL + 8 * g0, p0 ^ (L & odd));
}
template <int S> __device__ __forceinline__ void cons_release(uint32_t sbase, int lane) {
  if (lane < st_len(S)) mbar_arrive(sbase + SM_MISC + BAR_EMPTY + 8 * st_g0(S) + 8 * lane);
}
__device__ __forceinline__ bool elect_one() {
  uint32_t p;
  asm volatile("{\n.reg .pred P;\nelect.sync _|P, 0xffffffff;\nselp.u32 %0, 1, 0, P;\n}" : "=r"(p));
  return p != 0;
}
struct ProdRing { uint32_t pos, par; };
template <int N> __device__ __forceinline__ uint32_t prod_acquire(uint32_t sbase, ProdRing& r) {
  if (r.pos + N > NGRAN) r.pos = 0;
  const uint32_t g0 = r.pos;
#pragma unroll
  for (uint32_t i = 0; i < N; i++) mbar_wait(sbase + SM_MISC + BAR_EMPTY + 8 * (g0 + i), ((r.par >> (g0 + i)) & 1u) ^ 1u);
  r.par ^= ((1u << N) - 1u) << g0;
  r.pos = g0 + N;
  return g0;
}
template <int S> __device__ __forceinline__ void prod_acquire_static(uint32_t sbase, uint32_t L) {
  constexpr int g0 = st_g0(S);
  static_for<0, st_len(S)>([&](auto I) {
    constexpr int g = g0 + I.value;
    constexpr uint32_t p0 = cnt_cover(g, S) & 1, odd = cnt_cover(g, NSTAGE) & 1;
    mbar_wait(sbase + SM_MISC + BAR_EMPTY + 8 * g, p0 ^ (L & odd) ^ 1u);
  });
}
template <int S, int KSTEP_BYTES, int LBO, int SBO, int SWZ> __device__ __forceinline__ constexpr uint64_t st_desc(int k) {
  return (uint64_t)((SMEM_ORIGIN + st_g0(S) * GRAN + k * KSTEP_BYTES) >> 4) | ((uint64_t)(LBO >> 4) << 16) |
         ((uint64_t)(SBO >> 4) << 32) | ((uint64_t)SWZ << 62);
}

__device__ __forceinline__ void combine_stats(const uint4& p0, const uint4& p1, float& mean_lo, float& rstd_lo, float& mean_hi, float& rstd_hi) {
  float m0 = __uint_as_float(p0.x), q0 = __uint_as_float(p0.y), m0h = __uint_as_float(p0.z), q0h = __uint_as_float(p0.w);
  float m1 = __uint_as_float(p1.x), q1 = __uint_as_float(p1.y), m1h = __uint_as_float(p1.z), q1h = __uint_as_float(p1.w);
  float s = m0 + m1, sh = m0h + m1h;
  s += __shfl_xor_sync(0xffffffffu, s, 1); sh += __shfl_xor_sync(0xffffffffu, sh, 1);
  s += __shfl_xor_sync(0xffffffffu, s, 2); sh += __shfl_xor_sync(0xffffffffu, sh, 2);
  mean_lo = s * 0.125f; mean_hi = sh * 0.125f;
  float d0 = m0 - mean_lo, d1 = m1 - mean_lo, d0h = m0h - mean_hi, d1h = m1h - mean_hi;
  float t = q0 + q1 + 64.f * (d0 * d0 + d1 * d1), th = q0h + q1h + 64.f * (d0h * d0h + d1h * d1h);
  t += __shfl_xor_sync(0xffffffffu, t, 1); th += __shfl_xor_sync(0xffffffffu, th, 1);
  t += __shfl_xor_sync(0xffffffffu, t, 2); th += __shfl_xor_sync(0xffffffffu, th, 2);
  rstd_lo = rsqrtf(t * (1.f / 512.f) + 1e-5f);
  rstd_hi = rsqrtf(th * (1.f / 512.f) + 1e-5f);
}
__device__ __forceinline__ uint4 local_stats(const float (&v)[32]) {
  float s = 0.f, sh = 0.f;
#pragma unroll
  for (int i = 0; i < 4; i++) {
    s += (v[8 * i + 0] + v[8 * i + 1]) + (v[8 * i + 4] + v[8 * i + 5]);
    sh += (v[8 * i + 2] + v[8 * i + 3]) + (v[8 * i + 6] + v[8 * i + 7]);
  }
  s += __shfl_xor_sync(0xffffffffu, s, 1); sh += __shfl_xor_sync(0xffffffffu, sh, 1);
  s += __shfl_xor_sync(0xffffffffu, s, 2); sh += __shfl_xor_sync(0xffffffffu, sh, 2);
  float m = s * (1.f / 64.f), mh = sh * (1.f / 64.f);
  float q = 0.f, qh = 0.f;
#pragma unroll
  for (int i = 0; i < 4; i++) {
    float a = v[8 * i + 0] - m, b = v[8 * i + 1] - m, c = v[8 * i + 4] - m, d = v[8 * i + 5] - m;
    q += (a * a + b * b) + (c * c + d * d);
    float e = v[8 * i + 2] - mh, f = v[8 * i + 3] - mh, g = v[8 * i + 6] - mh, h = v[8 * i + 7] - mh;
    qh += (e * e + f * f) + (g * g + h * h);
  }
  q += __shfl_xor_sync(0xffffffffu, q, 1); qh += __shfl_xor_sync(0xffffffffu, qh, 1);
  q += __shfl_xor_sync(0xffffffffu, q, 2); qh += __shfl_xor_sync(0xffffffffu, qh, 2);
  return make_uint4(__float_as_uint(m), __float_as_uint(q), __float_as_uint(mh), __float_as_uint(qh));
}

__device__ __forceinline__ int slab_row0(int c, int g, int w) { return 1024 * g + 64 * c + 32 * (w >> 1) + (w & 1); }

__device__ __forceinline__ void owner_ln_publish(uint32_t sbase, const float (&v)[32], uint32_t tphase, uint32_t tag_xn, uint4 (&xraw)[4]) {
  PHASE_VARS;
  TS(40 + 4 * tphase);
  uint4 st = local_stats(v);
  if (qc == 0) sts128(sbase + SM_TSTAT + warp * 128 + qr * 16, st);
  uint4* xn = g_arena + c * ARENA + AR_XN + ((j) * 32 + 4 * warp) * 32 + lane;
  TS(41 + 4 * tphase);
  asm volatile("bar.sync 3, 256;" ::: "memory");
  TS(42 + 4 * tphase);
  const uint32_t rd = sbase + SM_TSTAT + qc * 256 + qr * 16;
  uint4 p0 = lds128(rd), p1 = lds128(rd + 128);
  float ml, rl, mh, rh;
  combine_stats(p0, p1, ml, rl, mh, rh);
  const float bl = -ml * rl, bh = -mh * rh;
#pragma unroll
  for (int i = 0; i < 4; i++) {
    uint4 o;
    o.x = set_tag(pack2(fmaf(v[8 * i + 0], rl, bl), fmaf(v[8 * i + 1], rl, bl)), tag_xn);
    o.y = pack2(fmaf(v[8 * i + 2], rh, bh), fmaf(v[8 * i + 3], rh, bh));
    o.z = pack2(fmaf(v[8 * i + 4], rl, bl), fmaf(v[8 * i + 5], rl, bl));
    o.w = pack2(fmaf(v[8 * i + 6], rh, bh), fmaf(v[8 * i + 7], rh, bh));
    st_ll(xn + i * 32, o);
  }
#pragma unroll
  for (int i = 0; i < 4; i++) {
    xraw[i].x = set_tag(pack2(v[8 * i + 0], v[8 * i + 1]), 1u);
    xraw[i].y = pack2(v[8 * i + 2], v[8 * i + 3]);
    xraw[i].z = pack2(v[8 * i + 4], v[8 * i + 5]);
    xraw[i].w = pack2(v[8 * i + 6], v[8 * i + 7]);
  }
}

__device__ __forceinline__ uint4 pack8(const float* a) {
  return make_uint4(pack2(a[0], a[1]), pack2(a[2], a[3]), pack2(a[4], a[5]), pack2(a[6], a[7]));
}
template <int U> __device__ __forceinline__ uint4 glu8(const float* g, float cl, float ch) {
  return make_uint4(pack2(g[0] * cl * g[U], g[1] * cl * g[U + 1]), pack2(g[2] * ch * g[U + 2], g[3] * ch * g[U + 3]),
                    pack2(g[4] * cl * g[U + 4], g[5] * cl * g[U + 5]), pack2(g[6] * ch * g[U + 6], g[7] * ch * g[U + 7]));
}
__device__ __forceinline__ uint32_t hfma2(uint32_t a, uint32_t b, uint32_t c) {
  uint32_t d;
  asm("fma.rn.bf16x2 %0, %1, %2, %3;" : "=r"(d) : "r"(a), "r"(b), "r"(c));
  return d;
}
__device__ __forceinline__ void keep4(const uint4 (&a)[4]) { keep(a[0]); keep(a[1]); keep(a[2]); keep(a[3]); }

#define STAGGER 0

__global__ void __launch_bounds__(NTHREADS, 1)
fused_kernel(const __grid_constant__ CUtensorMap m_qkv, const __grid_constant__ CUtensorMap m_wo,
             const __grid_constant__ CUtensorMap m_gu2, const __grid_constant__ CUtensorMap m_gu1,
             const __grid_constant__ CUtensorMap m_guh, const __grid_constant__ CUtensorMap m_wd112,
             const __grid_constant__ CUtensorMap m_wd80, const __grid_constant__ CUtensorMap m_wd32,
             const __nv_bfloat16* __restrict__ x_in,
             __nv_bfloat16* __restrict__ out, const char* __restrict__ w_o, const char* __restrict__ w_g,
             const char* __restrict__ w_u, const char* __restrict__ w_d
) {
  extern __shared__ __align__(1024) unsigned char smem_raw[];
  const uint32_t sbase = smem_u32(smem_raw);
  const uint32_t bars = sbase + SM_MISC;
  if ((sbase & 0xFFFFFFu) != SMEM_ORIGIN) return;
  TG(60);

  uint32_t xw[16];
  if (threadIdx.x < 256) {
    const int cc = blockIdx.x >> 3, jj = blockIdx.x & 7, ln = threadIdx.x & 31;
    const uint32_t* xp = reinterpret_cast<const uint32_t*>(x_in + (size_t)(slab_row0(cc, jj >> 2, jj & 3) + 2 * (ln >> 2)) * 512 + (threadIdx.x >> 5) * 64 + (ln & 3) * 2);
#pragma unroll
    for (int i = 0; i < 4; i++) {
      xw[4 * i] = __ldg(xp + i * 8); xw[4 * i + 1] = __ldg(xp + 16 * 256 + i * 8);
      xw[4 * i + 2] = __ldg(xp + i * 8 + 4); xw[4 * i + 3] = __ldg(xp + 16 * 256 + i * 8 + 4);
    }
  } else if (threadIdx.x == 256) {
    for (int i = 0; i < NGRAN; i++) { mbar_init(bars + BAR_FULL + 8 * i, 1); mbar_init(bars + BAR_EMPTY + 8 * i, 8); }
    for (int i = 0; i < 4; i++) mbar_init(bars + BAR_HRECV + 8 * i, 1);
    for (int i = 0; i < 2; i++) mbar_init(bars + BAR_HREADY + 8 * i, 4);
    asm volatile("fence.mbarrier_init.release.cluster;" ::: "memory");
  }
  __syncthreads();
  asm volatile("barrier.cluster.arrive.release.aligned;" ::: "memory");

  if (threadIdx.x >= 256) {
    asm volatile("setmaxnreg.dec.sync.aligned.u32 40;");
    const int warp = threadIdx.x >> 5, lane = threadIdx.x & 31;
    const int j = blockIdx.x & 7, b = j & 1;
    if (warp == 8) {
      ProdRing r{0u, 0u};
      const int cb0 = 224 * j + 32 * b, hb0 = 224 * j + 192 * (b ^ 1);
      const int jp = j ^ 1, cbp = 224 * jp + 32 * (b ^ 1), hbp = 224 * jp + 192 * b;
#pragma unroll 1
      for (uint32_t L = 0; L < 2; L++) {
        r.pos = 0;
        PSTOP_AT(L == 0 ? 0 : 3);
#pragma unroll 1
        for (int kb = 0; kb < 8; kb++) {
          const uint32_t g0 = prod_acquire<3>(sbase, r);
          if (elect_one()) {
            mbar_expect_tx(bars + BAR_FULL + 8 * g0, 24576);
            tma_3d(sbase + g0 * GRAN, &m_qkv, bars + BAR_FULL + 8 * g0, 64 * j, 64 * kb, 0);
          }
        }
        PSTOP_AT(10 * L + 1);
#pragma unroll 1
        for (int i = 0; i < 4; i++) {
          const uint32_t g0 = prod_acquire<2>(sbase, r);
          if (elect_one()) {
            mbar_expect_tx(bars + BAR_FULL + 8 * g0, 16384);
            tma_2d(sbase + g0 * GRAN, &m_wo, bars + BAR_FULL + 8 * g0, 64 * j, 128 * i);
          }
        }
        PSTOP_AT(10 * L + 2);
#pragma unroll 1
        for (int kb = 0; kb < 8; kb++) {
          const uint32_t g0 = prod_acquire<4>(sbase, r);
          if (elect_one()) {
            mbar_expect_tx(bars + BAR_FULL + 8 * g0, 32768);
            tma_4d(sbase + g0 * GRAN, &m_gu2, bars + BAR_FULL + 8 * g0, cb0, 64 * ((j + kb) & 7), 0, 0);
          }
        }
#pragma unroll 1
        for (int kb = 0; kb < 8; kb++) {
          const uint32_t g0 = prod_acquire<3>(sbase, r);
          if (elect_one()) {
            mbar_expect_tx(bars + BAR_FULL + 8 * g0, 24576);
            tma_4d(sbase + g0 * GRAN, &m_gu1, bars + BAR_FULL + 8 * g0, cb0 + 128, 64 * ((j + kb) & 7), 0, 0);
            tma_3d(sbase + g0 * GRAN + 16384, &m_guh, bars + BAR_FULL + 8 * g0, hb0, 64 * ((j + kb) & 7), 0);
          }
        }
        static_for<0, 16>([&](auto I) {
          constexpr int i = I.value, g0 = st_g0(ST_DN + i);
          prod_acquire_static<ST_DN + i>(sbase, L);
          if (elect_one()) {
            const uint32_t dst = sbase + g0 * GRAN, fb = bars + BAR_FULL + 8 * g0;
            const int n0 = 256 * b + 64 * dn_q(i);
            mbar_expect_tx(fb, 14336);
            if constexpr (dn_kh(i) == 0) {
              tma_2d(dst, &m_wd112, fb, n0, dn_par(i) ? cbp : cb0);
            } else {
              tma_2d(dst, &m_wd80, fb, n0, (dn_par(i) ? cbp : cb0) + 112);
              tma_2d(dst + 10240, &m_wd32, fb, n0, dn_par(i) ? hbp : hb0);
            }
          }
        });
        r.par ^= flip_mask(ST_DN, NSTAGE);
      }
    } else if (warp == 9) {
#define PF_DELAY 0
      { const uint32_t t0 = (uint32_t)clock(); while ((uint32_t)clock() - t0 < PF_DELAY) {} }
      const int cta = blockIdx.x;
      if (lane == 0) l2_prefetch(w_o + cta * 4096, 4096);
      if (lane == 1) l2_prefetch(w_g + cta * 14336, 14336);
      if (lane == 2) l2_prefetch(w_u + cta * 14336, 14336);
      if (lane == 3) l2_prefetch(w_d + cta * 14336, 14336);
    }
    __syncwarp();
    asm volatile("barrier.cluster.wait.acquire.aligned; // producer" ::: "memory");
    asm volatile("barrier.cluster.arrive.release.aligned;\nbarrier.cluster.wait.acquire.aligned; // producer" ::: "memory");
  } else {
    asm volatile("setmaxnreg.inc.sync.aligned.u32 232;");
    TS(0);
    TG(61);

    uint4 xraw[4];
    {
      float v[32];
#pragma unroll
      for (int i = 0; i < 16; i++) { v[2 * i] = bf_lo(xw[i]); v[2 * i + 1] = bf_hi(xw[i]); }
      owner_ln_publish(sbase, v, 0u, 1u, xraw);
      asm volatile("barrier.cluster.wait.acquire.aligned; // consumer" ::: "memory");
    }
    STOP_AT(0);
    TS(1);

#pragma unroll 1
    for (uint32_t L = 0; L < 2; L++) {
      const uint32_t tag = L ^ 1;
      {
        PHASE_VARS;
        uint4 qf[4], kf[4], vf[4], pp[4];
        const int blk = 16 * g + c;
        const int pb = blk > 0 ? blk - 1 : 0;
        const uint4* halo_src = g_arena + (pb & 15) * ARENA + AR_HALO + (((((L * 2 + (pb >> 4)) * 8 + j) * 2 + (w & 1)) * 4) * 32) + lane;
        {
          float acc[96];
          uint4 A[3][4];
          const uint4* xs = g_arena + c * ARENA + AR_XN + ((slab) * 32) * 32 + lane;
          bar_wg(1 + g);
          cold_delay(L);
          load_pk<4>(A[0], xs);
          ensure_pk<4>(A[0], xs, tag);
          TS(2 + 20 * L);
          load_pk<4>(A[1], xs + 128);
          static_for<0, 8>([&](auto I) {
            constexpr int kb = I.value;
            cons_acquire<kb>(sbase, L);
            wg_fence();
            static_for<0, 4>([&](auto K) { constexpr int k = K.value; wgmma_n192<kb == 0 && k == 0, 0>(acc, A[kb % 3][k], st_desc<kb, 2048, 8192, 1024, 1>(k)); });
            wg_commit();
            if constexpr (kb > 0) {
              wg_wait<1>();
              keep4(A[(kb + 2) % 3]);
              cons_release<kb - 1>(sbase, lane);
            }
            if constexpr (kb + 1 < 8) ensure_pk<4>(A[(kb + 1) % 3], xs + (kb + 1) * 128, tag);
            if constexpr (kb + 2 < 8) load_pk<4>(A[(kb + 2) % 3], xs + (kb + 2) * 128);
            if constexpr (kb == 2) {
              uint4* xr = g_arena + c * ARENA + AR_XRAW + ((j) * 32 + 4 * warp) * 32 + lane;
#pragma unroll
              for (int i = 0; i < 4; i++) st_ll(xr + i * 32, xraw[i]);
            }
          });
          wg_wait<0>();
          TS(3 + 20 * L);
          fence_acc(acc);
          keep4(A[1]);
          cons_release<7>(sbase, lane);
#pragma unroll
          for (int h = 0; h < 4; h++) {
            kf[h].y = pack2(acc[32 + 8 * h + 2], acc[32 + 8 * h + 3]); kf[h].w = pack2(acc[32 + 8 * h + 6], acc[32 + 8 * h + 7]);
            vf[h].y = movm(pack2(acc[64 + 8 * h + 2], acc[64 + 8 * h + 3])); vf[h].w = movm(pack2(acc[64 + 8 * h + 6], acc[64 + 8 * h + 7]));
            pp[h] = make_uint4(kf[h].y, kf[h].w, vf[h].y, vf[h].w);
          }
          if (w >= 2 && blk < 31) {
            uint4* hd = g_arena + c * ARENA + AR_HALO + (((((L * 2 + g) * 8 + j) * 2 + (w & 1)) * 4) * 32) + lane;
#pragma unroll
            for (int h = 0; h < 4; h++) { uint4 t = pp[h]; t.x |= 1u; st_ll(hd + h * 32, t); }
          }
#pragma unroll
          for (int h = 0; h < 4; h++) sts128(areg + (28 + h) * 2048 + t128 * 16, pp[h]);
          if (w < 2 && blk > 0) { cold_delay(L); load_pk<4>(pp, halo_src); }
#pragma unroll
          for (int h = 0; h < 4; h++) {
            kf[h].x = pack2(acc[32 + 8 * h], acc[32 + 8 * h + 1]); kf[h].z = pack2(acc[32 + 8 * h + 4], acc[32 + 8 * h + 5]);
            vf[h].x = movm(pack2(acc[64 + 8 * h], acc[64 + 8 * h + 1])); vf[h].z = movm(pack2(acc[64 + 8 * h + 4], acc[64 + 8 * h + 5]));
          }
#pragma unroll
          for (int h = 0; h < 4; h++) qf[h] = pack8(&acc[8 * h]);
        }
        bar_wg(1 + g);
        const bool first = (w < 2) && (blk == 0);
        if (w >= 2) {
#pragma unroll
          for (int h = 0; h < 4; h++) pp[h] = lds128(areg + (28 + h) * 2048 + (t128 - 64) * 16);
        }
        bar_wg(1 + g);
        if (w < 2 && blk > 0) {
          ensure_pk<4>(pp, halo_src, 1u);
          uint4* hz = const_cast<uint4*>(halo_src);
#pragma unroll
          for (int h = 0; h < 4; h++) st_ll(hz + h * 32, make_uint4(0, 0, 0, 0));
        }
        TS(4 + 20 * L);
        const bool n0 = 2 * qc <= qr, n1 = 2 * qc + 1 <= qr;
        const uint32_t msk = (n0 ? 0xffffu : 0u) | (n1 ? 0xffff0000u : 0u);
        const float sc = 0.25f * 1.4426950408889634f;
        const float NEG = -1e30f;
        uint4* od = g_arena + c * ARENA + AR_O + ((slab) * 32 + 4 * j) * 32 + lane;
        float l0[4], l1[4], h0[4], h1[4], ml[4], mh[4];
#pragma unroll
        for (int h = 0; h < 4; h++) {
          float sp[4], s0[4], s1[4];
          mma16816_z(sp, qf[h], pp[h].x, pp[h].y);
          mma16816_z(s0, qf[h], kf[h].x, kf[h].z);
          mma16816_z(s1, qf[h], kf[h].y, kf[h].w);
          if (first) { sp[0] = NEG; sp[1] = NEG; }
          l0[h] = n0 ? s0[0] : sp[0]; l1[h] = n1 ? s0[1] : sp[1];
          h0[h] = n0 ? s1[2] : s0[2]; h1[h] = n1 ? s1[3] : s0[3];
          ml[h] = fmaxf(l0[h], l1[h]); mh[h] = fmaxf(h0[h], h1[h]);
        }
#pragma unroll
        for (int h = 0; h < 4; h++) { ml[h] = fmaxf(ml[h], __shfl_xor_sync(0xffffffffu, ml[h], 1)); mh[h] = fmaxf(mh[h], __shfl_xor_sync(0xffffffffu, mh[h], 1)); }
#pragma unroll
        for (int h = 0; h < 4; h++) { ml[h] = fmaxf(ml[h], __shfl_xor_sync(0xffffffffu, ml[h], 2)); mh[h] = fmaxf(mh[h], __shfl_xor_sync(0xffffffffu, mh[h], 2)); }
        float sl[4], sh[4];
#pragma unroll
        for (int h = 0; h < 4; h++) {
          const float bl = -ml[h] * sc, bh = -mh[h] * sc;
          l0[h] = ex2(fmaf(l0[h], sc, bl)); l1[h] = ex2(fmaf(l1[h], sc, bl));
          h0[h] = ex2(fmaf(h0[h], sc, bh)); h1[h] = ex2(fmaf(h1[h], sc, bh));
          sl[h] = l0[h] + l1[h]; sh[h] = h0[h] + h1[h];
        }
#pragma unroll
        for (int h = 0; h < 4; h++) { sl[h] += __shfl_xor_sync(0xffffffffu, sl[h], 1); sh[h] += __shfl_xor_sync(0xffffffffu, sh[h], 1); }
#pragma unroll
        for (int h = 0; h < 4; h++) { sl[h] += __shfl_xor_sync(0xffffffffu, sl[h], 2); sh[h] += __shfl_xor_sync(0xffffffffu, sh[h], 2); }
#pragma unroll
        for (int h = 0; h < 4; h++) {
          const float il = rcp(sl[h]), ih = rcp(sh[h]);
          const uint32_t pl = pack2(l0[h] * il, l1[h] * il), ph = pack2(h0[h] * ih, h1[h] * ih);
          const uint4 P = make_uint4(pl & msk, ph & ~msk, 0u, ph & msk);
          float o0[4], o1[4];
          mma16816_z(o0, P, vf[h].x, vf[h].y);
          mma16816_z(o1, P, vf[h].z, vf[h].w);
          mma1688(o0, pl & ~msk, 0u, pp[h].z);
          mma1688(o1, pl & ~msk, 0u, pp[h].w);
          st_ll(od + h * 32, make_uint4(set_tag(pack2(o0[0], o0[1]), tag), pack2(o0[2], o0[3]), pack2(o1[0], o1[1]), pack2(o1[2], o1[3])));
        }
      }
      TS(5 + 20 * L);
      if (L == 0) { STOP_AT(1); } else { STOP_AT(11); }
      uint4 x1own[4];
      {
        PHASE_VARS;
        float acc[32];
        uint4 A[32], xr[4];
        const uint4* os = g_arena + c * ARENA + AR_O + ((slab) * 32) * 32 + lane;
        uint4* xp = g_arena + c * ARENA + AR_XRAW + ((slab) * 32 + 4 * j) * 32 + lane;
        load_pk<4>(xr, xp);
        cold_delay(L);
        load_pk<4>(A, os);
        ensure_pk<4>(A, os, tag);
        TS(6 + 20 * L);
        load_pk<28>(A + 4, os + 128);
        static_for<0, 8>([&](auto I) {
          constexpr int kb = I.value;
          if constexpr ((kb & 1) == 0) cons_acquire<ST_WO + kb / 2>(sbase, L);
          if constexpr (kb > 0) ensure_pk<4>(A + 4 * kb, os + kb * 128, tag);
          wg_fence();
          static_for<0, 4>([&](auto K) {
            constexpr int k = K.value;
            wgmma_n64<kb == 0 && k == 0, 0>(acc, A[4 * kb + k], st_desc<ST_WO + kb / 2, 2048, 8192, 1024, 1>(4 * (kb & 1) + k));
          });
          wg_commit();
          if constexpr ((kb & 1) == 0 && kb > 0) { wg_wait<1>(); cons_release<ST_WO + kb / 2 - 1>(sbase, lane); }
        });
        wg_wait<0>();
        TS(7 + 20 * L);
        fence_acc(acc);
#pragma unroll
        for (int k = 0; k < 32; k++) keep(A[k]);
        cons_release<ST_WO + 3>(sbase, lane);
        ensure_pk<4>(xr, xp, 1u);
#pragma unroll
        for (int i = 0; i < 4; i++) {
          acc[8 * i + 0] += bf_lo(xr[i].x); acc[8 * i + 1] += bf_hi(xr[i].x); acc[8 * i + 2] += bf_lo(xr[i].y); acc[8 * i + 3] += bf_hi(xr[i].y);
          acc[8 * i + 4] += bf_lo(xr[i].z); acc[8 * i + 5] += bf_hi(xr[i].z); acc[8 * i + 6] += bf_lo(xr[i].w); acc[8 * i + 7] += bf_hi(xr[i].w);
        }
        uint4 st = local_stats(acc);
        st.x = set_tag(st.x, tag);
        if (qc == 0) st_ll(g_arena + c * ARENA + AR_STATS + (slab * 8 + j) * 8 + qr, st);
#pragma unroll
        for (int i = 0; i < 4; i++) {
          x1own[i] = pack8(&acc[8 * i]);
          x1own[i].x = set_tag(x1own[i].x, 0u);
          st_ll(xp + i * 32, x1own[i]);
        }
      }
      TS(8 + 20 * L);
      if (L == 0) { STOP_AT(2); } else { STOP_AT(12); }
      uint4 hs[14];
      {
        PHASE_VARS;
        float acc[128];
        uint4 A[3][4];
        const uint4* xs = g_arena + c * ARENA + AR_XRAW + ((slab) * 32) * 32 + lane;
        const uint4* sp = g_arena + c * ARENA + AR_STATS + (slab * 8 + 2 * qc) * 8 + qr;
        const uint32_t sm = areg + t128 * 16;
        uint32_t rl2, rh2, bl2, bh2;
        float cl, ch;
        auto xsrc = [&](int p) { return xs + ((j + p) & 7) * 128; };
        {
          uint4 p[2];
#pragma unroll
          for (int k = 0; k < 4; k++) A[0][k] = x1own[k];
          cold_delay(L);
          p[0] = ld_ll(sp); p[1] = ld_ll(sp + 8);
          load_pk<4>(A[1], xsrc(1));
          for (uint32_t n = 0; !ok_pk<2>(p, tag) && n < SPIN_LIMIT; n++) { p[0] = ld_ll(sp); p[1] = ld_ll(sp + 8); }
          TS(9 + 20 * L);
          float ml, rl, mh, rh;
          combine_stats(p[0], p[1], ml, rl, mh, rh);
          rl2 = pack2(rl, rl); rh2 = pack2(rh, rh);
          const float rlb = bf_lo(rl2), rhb = bf_lo(rh2);
          bl2 = pack2(-ml * rlb, -ml * rlb); bh2 = pack2(-mh * rhb, -mh * rhb);
          cl = rl / rlb; cl *= cl; ch = rh / rhb; ch *= ch;
        }
        auto normalise = [&](uint4 (&xb)[4], int kb) {
#pragma unroll
          for (int k = 0; k < 4; k++) {
            xb[k].x = hfma2(xb[k].x, rl2, bl2); xb[k].y = hfma2(xb[k].y, rh2, bh2);
            xb[k].z = hfma2(xb[k].z, rl2, bl2); xb[k].w = hfma2(xb[k].w, rh2, bh2);
            sts128(sm + (kb * 4 + k) * 2048, xb[k]);
          }
        };
        normalise(A[0], 0);
        static_for<0, 8>([&](auto I) {
          constexpr int kb = I.value;
          cons_acquire<ST_G1 + kb>(sbase, L);
          wg_fence();
          static_for<0, 4>([&](auto K) { constexpr int k = K.value; wgmma_n256<kb == 0 && k == 0, 0>(acc, A[kb % 3][k], st_desc<ST_G1 + kb, 2048, 8192, 1024, 1>(k)); });
          wg_commit();
          if constexpr (kb > 0) {
            wg_wait<1>();
            keep4(A[(kb + 2) % 3]);
            cons_release<ST_G1 + kb - 1>(sbase, lane);
          }
          if constexpr (kb + 1 < 8) ensure_pk<4>(A[(kb + 1) % 3], xsrc(kb + 1), 0u);
          if constexpr (kb + 2 < 8) load_pk<4>(A[(kb + 2) % 3], xsrc(kb + 2));
          if constexpr (kb + 1 < 8) normalise(A[(kb + 1) % 3], kb + 1);
        });
        wg_wait<0>();
        TS(10 + 20 * L);
        fence_acc(acc);
        keep4(A[1]);
        cons_release<ST_G1 + 7>(sbase, lane);
        uint4 B[2][4];
#pragma unroll
        for (int k = 0; k < 4; k++) B[0][k] = lds128(sm + k * 2048);
#pragma unroll
        for (int s = 0; s < 8; s++) hs[s] = glu8<32>(&acc[64 * (s >> 2) + 8 * (s & 3)], cl, ch);
        float acc2[96];
        const uint32_t hdst = mapa(sm, cbit ^ 1);
        const uint32_t hbar1 = mapa(bars + BAR_HRECV + 16 * g, cbit ^ 1);
        if (t128 == 0) { mbar_expect_tx(bars + BAR_HRECV + 16 * g, 8 * 2048); mbar_expect_tx(bars + BAR_HRECV + 16 * g + 8, 6 * 2048); }
        static_for<0, 8>([&](auto I) {
          constexpr int kb = I.value;
          cons_acquire<ST_G2 + kb>(sbase, L);
          wg_fence();
          static_for<0, 4>([&](auto K) {
            constexpr int k = K.value;
            wgmma_n128<kb == 0 && k == 0, 0>(acc2, B[kb & 1][k], st_desc<ST_G2 + kb, 2048, 8192, 1024, 1>(k));
            wgmma_n64<kb == 0 && k == 0, 64>(acc2, B[kb & 1][k], st_desc<ST_G2 + kb, 1024, 4096, 512, 2>(k) + (16384 >> 4));
          });
          wg_commit();
          if constexpr (kb > 0) {
            wg_wait<1>();
            keep4(B[(kb + 1) & 1]);
            cons_release<ST_G2 + kb - 1>(sbase, lane);
          }
          if constexpr (kb + 1 < 8) {
#pragma unroll
            for (int k = 0; k < 4; k++) B[(kb + 1) & 1][k] = lds128(sm + ((kb + 1) * 4 + k) * 2048);
          }
          if constexpr (kb == 3) {
            __syncwarp();
            if (lane == 0) mbar_arrive_remote(mapa(bars + BAR_HREADY + 8 * g, cbit ^ 1));
          }
          if constexpr (kb >= 4) {
            if constexpr (kb == 4) mbar_wait(bars + BAR_HREADY + 8 * g, L);
            st_async128(hdst + (2 * kb - 8) * 2048, hs[2 * kb - 8], hbar1);
            st_async128(hdst + (2 * kb - 7) * 2048, hs[2 * kb - 7], hbar1);
          }
        });
        wg_wait<0>();
        TS(11 + 20 * L);
        fence_acc(acc2);
        keep4(B[1]);
        cons_release<ST_G2 + 7>(sbase, lane);
#pragma unroll
        for (int s = 0; s < 4; s++) hs[8 + s] = glu8<32>(&acc2[8 * s], cl, ch);
#pragma unroll
        for (int s = 0; s < 2; s++) hs[12 + s] = glu8<16>(&acc2[64 + 8 * s], cl, ch);
      }
      {
        PHASE_VARS;
        TS(12 + 20 * L);
        const uint32_t hdst = mapa(areg + t128 * 16, cbit ^ 1);
        const uint32_t hbar2 = mapa(bars + BAR_HRECV + 16 * g + 8, cbit ^ 1);
        uint4* pd = g_arena + c * ARENA + AR_PART + (((slab * 2 + cbit) * 4 + ca) * 16) * 32 + lane;
        const uint4* ps = g_arena + c * ARENA + AR_PART + (((j * 2 + g) * 4) * 16 + 4 * w) * 32 + lane;
        auto fetch_partials = [&]() {
#pragma unroll
          for (int src = 0; src < 4; src++)
#pragma unroll
            for (int k = 0; k < 4; k++) cp_async16(areg + t128 * 16 + (14 + 4 * src + k) * 2048, ps + src * (16 * 32) + k * 32);
        };
        uint4 hb[7];
        float a0[32], a1[32], a2[32], a3[32];
        auto publish = [&](float (&a)[32], int q, int s0, int s1) {
#pragma unroll
          for (int s = s0; s < s1; s++) {
            uint4 o = pack8(&a[8 * s]);
            o.x = set_tag(o.x, tag);
            st_ll(pd + (4 * q + s) * 32, o);
          }
        };
        static_for<0, 16>([&](auto I) {
          constexpr int i = I.value, q = dn_q(i), par = dn_par(i), kh = dn_kh(i);
          auto mm = [&](auto K) {
            constexpr int k = decltype(K)::value;
            constexpr bool init = (k == 0 && par == 0 && kh == 0);
            constexpr uint64_t db = st_desc<ST_DN + i, 2048, 8192, 1024, 1>(k);
            if constexpr (q == 0) { if constexpr (par) wgmma_n64<init, 0>(a0, hb[k], db); else wgmma_n64<init, 0>(a0, hs[7 * kh + k], db); }
            if constexpr (q == 1) { if constexpr (par) wgmma_n64<init, 0>(a1, hb[k], db); else wgmma_n64<init, 0>(a1, hs[7 * kh + k], db); }
            if constexpr (q == 2) { if constexpr (par) wgmma_n64<init, 0>(a2, hb[k], db); else wgmma_n64<init, 0>(a2, hs[7 * kh + k], db); }
            if constexpr (q == 3) { if constexpr (par) wgmma_n64<init, 0>(a3, hb[k], db); else wgmma_n64<init, 0>(a3, hs[7 * kh + k], db); }
          };
          cons_acquire<ST_DN + i>(sbase, L);
          wg_fence();
          mm(IC<0>{}); mm(IC<1>{}); mm(IC<2>{}); mm(IC<3>{}); mm(IC<4>{}); mm(IC<5>{}); mm(IC<6>{});
          wg_commit();
          if constexpr (i > 0) { wg_wait<1>(); cons_release<ST_DN + i - 1>(sbase, lane); }
          if constexpr (i < 3) {
            st_async128(hdst + (8 + 2 * i) * 2048, hs[8 + 2 * i], hbar2);
            st_async128(hdst + (9 + 2 * i) * 2048, hs[9 + 2 * i], hbar2);
          }
          constexpr int n = i + 1;
          if constexpr (n < 16 && dn_par(n) && n != 4 && n != 7) {
            if constexpr (n == 2) { mbar_wait(bars + BAR_HRECV + 16 * g, L); TS(13 + 20 * L); }
            if constexpr (n == 6) { mbar_wait(bars + BAR_HRECV + 16 * g + 8, L); TS(14 + 20 * L); }
#pragma unroll
            for (int k = 0; k < 7; k++) { if constexpr (n != 2) keep(hb[k]); hb[k] = lds128(areg + t128 * 16 + (7 * dn_kh(n) + k) * 2048); }
          }
          if constexpr (i == 7) { fence_acc(a0); publish(a0, 0, 0, 4); }
          if constexpr (i == 8) { fence_acc(a1); publish(a1, 1, 0, 2); }
          if constexpr (i == 9) publish(a1, 1, 2, 4);
          if constexpr (i == 12) { fence_acc(a2); publish(a2, 2, 0, 2); }
          if constexpr (i == 13) publish(a2, 2, 2, 4);
          if constexpr (i == 10) { if (w == 0) fetch_partials(); }
          if constexpr (i == 12) { if (w == 1) fetch_partials(); }
        });
        wg_wait<0>();
        TS(15 + 20 * L);
        fence_acc(a3);
#pragma unroll
        for (int k = 0; k < 7; k++) { keep(hb[k]); keep(hs[7 + k]); }
        cons_release<NSTAGE - 1>(sbase, lane);
        publish(a3, 3, 0, 4);
        if (w >= 2) fetch_partials();
      }
      {
        PHASE_VARS;
        const uint4* xq = g_arena + c * ARENA + AR_XRAW + ((j) * 32 + 4 * warp) * 32 + lane;
        const uint4* ps = g_arena + c * ARENA + AR_PART + (((j * 2 + g) * 4) * 16 + 4 * w) * 32 + lane;
        uint4 xr[4], P[4][4];
        float v[32];
        load_pk<4>(xr, xq);
        cp_wait_all();
#pragma unroll
        for (int k = 0; k < 16; k++) P[k >> 2][k & 3] = lds128(areg + t128 * 16 + (14 + k) * 2048);
        for (uint32_t n = 0; !ok_pk<16>(&P[0][0], tag) && n < SPIN_LIMIT; n++) {
#pragma unroll
          for (int src = 0; src < 4; src++) load_pk<4>(P[src], ps + src * (16 * 32));
        }
        TS(16 + 20 * L);
        ensure_pk<4>(xr, xq, 0u);
#pragma unroll
        for (int i = 0; i < 4; i++) {
          v[8 * i + 0] = bf_lo(xr[i].x); v[8 * i + 1] = bf_hi(xr[i].x); v[8 * i + 2] = bf_lo(xr[i].y); v[8 * i + 3] = bf_hi(xr[i].y);
          v[8 * i + 4] = bf_lo(xr[i].z); v[8 * i + 5] = bf_hi(xr[i].z); v[8 * i + 6] = bf_lo(xr[i].w); v[8 * i + 7] = bf_hi(xr[i].w);
          float d[8] = {0, 0, 0, 0, 0, 0, 0, 0};
#pragma unroll
          for (int src = 0; src < 4; src++) {
            const uint4 p = P[src][i];
            d[0] += bf_lo(p.x); d[1] += bf_hi(p.x); d[2] += bf_lo(p.y); d[3] += bf_hi(p.y);
            d[4] += bf_lo(p.z); d[5] += bf_hi(p.z); d[6] += bf_lo(p.w); d[7] += bf_hi(p.w);
          }
#pragma unroll
          for (int k = 0; k < 8; k++) v[8 * i + k] += d[k];
        }
        if (L == 0) {
          owner_ln_publish(sbase, v, 1u, 0u, xraw);
        } else {
#pragma unroll
          for (int i = 0; i < 4; i++) xraw[i] = make_uint4(0, 0, 0, 0);
          uint32_t* op = reinterpret_cast<uint32_t*>(out + (size_t)(slab_row0(c, j >> 2, j & 3) + 2 * qr) * 512 + warp * 64 + qc * 2);
#pragma unroll
          for (int i = 0; i < 4; i++) {
            op[i * 8] = pack2(v[8 * i], v[8 * i + 1]);
            op[16 * 256 + i * 8] = pack2(v[8 * i + 2], v[8 * i + 3]);
            op[i * 8 + 4] = pack2(v[8 * i + 4], v[8 * i + 5]);
            op[16 * 256 + i * 8 + 4] = pack2(v[8 * i + 6], v[8 * i + 7]);
          }
        }
      }
      TS(17 + 20 * L);
      if (L == 0) { STOP_AT(3); }
    }
    TG(62);
    asm volatile("barrier.cluster.arrive.release.aligned;\nbarrier.cluster.wait.acquire.aligned; // consumer" ::: "memory");
    TG(63);
  }
}

typedef CUresult (*EncodeFn)(CUtensorMap*, CUtensorMapDataType, cuuint32_t, void*, const cuuint64_t*, const cuuint64_t*,
                             const cuuint32_t*, const cuuint32_t*, CUtensorMapInterleave, CUtensorMapSwizzle,
                             CUtensorMapL2promotion, CUtensorMapFloatOOBfill);

void encode(EncodeFn fn, CUtensorMap* m, int rank, const void* base, const cuuint64_t* dims, const cuuint64_t* strides,
            const cuuint32_t* box, CUtensorMapSwizzle sw) {
  cuuint32_t es[5] = {1, 1, 1, 1, 1};
  fn(m, CU_TENSOR_MAP_DATA_TYPE_BFLOAT16, (cuuint32_t)rank, const_cast<void*>(base), dims, strides, box, es,
     CU_TENSOR_MAP_INTERLEAVE_NONE, sw, CU_TENSOR_MAP_L2_PROMOTION_L2_128B, CU_TENSOR_MAP_FLOAT_OOB_FILL_NONE);
}

}

extern "C" void kernel_launch(void* const* d_in, const int* in_sizes, int n_in, void* d_out, int out_size) {
  (void)in_sizes; (void)n_in; (void)out_size;
  const __nv_bfloat16* x = (const __nv_bfloat16*)d_in[0];
  const char* wqkv = (const char*)d_in[1];
  const char* wo = (const char*)d_in[2];
  const char* wg = (const char*)d_in[4];
  const char* wu = (const char*)d_in[5];
  const char* wd = (const char*)d_in[6];

  static EncodeFn fn = nullptr;
  if (!fn) {
    void* p = nullptr;
    cudaDriverEntryPointQueryResult st;
    cudaGetDriverEntryPoint("cuTensorMapEncodeTiled", &p, cudaEnableDefault, &st);
    fn = (EncodeFn)p;
    cudaFuncSetAttribute(fused_kernel, cudaFuncAttributeMaxDynamicSharedMemorySize, SMEM_BYTES);
  }
  CUtensorMap m_qkv, m_wo, m_gu2, m_gu1, m_guh, m_wd112, m_wd80, m_wd32;
  {
    cuuint64_t dims[3] = {512, 512, 3}, str[2] = {3072, 1024};
    cuuint32_t box[3] = {64, 64, 3};
    encode(fn, &m_qkv, 3, wqkv, dims, str, box, CU_TENSOR_MAP_SWIZZLE_128B);
  }
  {
    cuuint64_t dims[2] = {512, 512}, str[1] = {1024};
    cuuint32_t box[2] = {64, 128};
    encode(fn, &m_wo, 2, wo, dims, str, box, CU_TENSOR_MAP_SWIZZLE_128B);
  }
  {
    const char* lo = wg < wu ? wg : wu;
    cuuint64_t diff = (cuuint64_t)(wg < wu ? wu - wg : wg - wu);
    cuuint64_t dims[4] = {1792, 512, 2, 2}, str[3] = {3584, diff, 128};
    cuuint32_t box2[4] = {64, 64, 2, 2}, box1[4] = {64, 64, 2, 1}, boxh[3] = {32, 64, 2};
    encode(fn, &m_gu2, 4, lo, dims, str, box2, CU_TENSOR_MAP_SWIZZLE_128B);
    encode(fn, &m_gu1, 4, lo, dims, str, box1, CU_TENSOR_MAP_SWIZZLE_128B);
    encode(fn, &m_guh, 3, lo, dims, str, boxh, CU_TENSOR_MAP_SWIZZLE_64B);
  }
  {
    cuuint64_t dims[2] = {512, 1792}, str[1] = {1024};
    cuuint32_t b112[2] = {64, 112}, b80[2] = {64, 80}, b32[2] = {64, 32};
    encode(fn, &m_wd112, 2, wd, dims, str, b112, CU_TENSOR_MAP_SWIZZLE_128B);
    encode(fn, &m_wd80, 2, wd, dims, str, b80, CU_TENSOR_MAP_SWIZZLE_128B);
    encode(fn, &m_wd32, 2, wd, dims, str, b32, CU_TENSOR_MAP_SWIZZLE_128B);
  }
  cudaLaunchConfig_t cfg = {};
  cfg.gridDim = dim3(128);
  cfg.blockDim = dim3(NTHREADS);
  cfg.dynamicSmemBytes = SMEM_BYTES;
  cfg.stream = cudaStreamPerThread;
  cudaLaunchAttribute at[1];
  at[0].id = cudaLaunchAttributeClusterDimension;
  at[0].val.clusterDim.x = 2; at[0].val.clusterDim.y = 1; at[0].val.clusterDim.z = 1;
  cfg.attrs = at; cfg.numAttrs = 1;
  cudaLaunchKernelEx(&cfg, fused_kernel, m_qkv, m_wo, m_gu2, m_gu1, m_guh, m_wd112, m_wd80, m_wd32, x, (__nv_bfloat16*)d_out, wo, wg, wu, wd
  );
}
```

```cpp
#include <cuda_runtime.h>
#include <cuda_bf16.h>
#include <cuda.h>
#include <stdint.h>

namespace {

constexpr int NTHREADS = 384;
constexpr int GRAN = 8192;
constexpr int NGRAN = 12;
constexpr int SM_AREG = NGRAN * GRAN;
constexpr int SM_MISC = SM_AREG + 131072;
constexpr int SM_TSTAT = SM_MISC + 256;
constexpr int SMEM_BYTES = SM_TSTAT + 1024;
constexpr int BAR_FULL = 0, BAR_EMPTY = 96, BAR_HRECV = 192, BAR_HREADY = 224;

constexpr int AR_XN = 0, AR_XRAW = 8192, AR_O = 16384, AR_STATS = 24576, AR_HALO = 25088, AR_PART = 33280, ARENA = 66048;
__device__ __align__(1024) uint4 g_arena[16 * ARENA];

#define TS(n)
#define TG(n)
#define OPAQUE(x) asm volatile("" : "+r"(x))
#define PHASE_VARS                                                                                   \
  int tid_ = threadIdx.x, bid_ = blockIdx.x;                                                         \
  OPAQUE(tid_); OPAQUE(bid_);                                                                        \
  const int lane = tid_ & 31, warp = tid_ >> 5, g = warp >> 2, w = warp & 3, t128 = tid_ & 127;      \
  const int qr = lane >> 2, qc = lane & 3, slab = warp;                                              \
  const int c = bid_ >> 3, j = bid_ & 7, ca = j >> 1, cbit = j & 1;                                  \
  const uint32_t areg = sbase + SM_AREG + g * 65536;                                                 \
  (void)g; (void)j; (void)w; (void)t128; (void)qr; (void)qc; (void)slab; (void)c; (void)ca; (void)cbit; (void)areg; (void)lane
#define STOP_AT(n)
#define PSTOP_AT(n)

__device__ __forceinline__ uint32_t smem_u32(const void* p) { return (uint32_t)__cvta_generic_to_shared(p); }
__device__ __forceinline__ void mbar_init(uint32_t bar, uint32_t cnt) {
  asm volatile("mbarrier.init.shared::cta.b64 [%0], %1;" ::"r"(bar), "r"(cnt) : "memory");
}
__device__ __forceinline__ void mbar_expect_tx(uint32_t bar, uint32_t bytes) {
  asm volatile("mbarrier.arrive.expect_tx.shared::cta.b64 _, [%0], %1;" ::"r"(bar), "r"(bytes) : "memory");
}
__device__ __forceinline__ void mbar_arrive(uint32_t bar) {
  asm volatile("mbarrier.arrive.shared::cta.b64 _, [%0];" ::"r"(bar) : "memory");
}
__device__ __forceinline__ void mbar_arrive_remote(uint32_t cluster_addr) {
  asm volatile("mbarrier.arrive.relaxed.cluster.shared::cluster.b64 _, [%0];" ::"r"(cluster_addr) : "memory");
}
__device__ __forceinline__ bool mbar_try(uint32_t bar, uint32_t parity) {
  uint32_t ok;
  asm volatile("{\n.reg .pred p;\nmbarrier.try_wait.parity.shared::cta.b64 p, [%1], %2;\nselp.u32 %0, 1, 0, p;\n}"
               : "=r"(ok) : "r"(bar), "r"(parity) : "memory");
  return ok != 0;
}
constexpr uint32_t SPIN_LIMIT = 1u << 16;
constexpr uint32_t SMEM_ORIGIN = 1024;
__device__ __forceinline__ void mbar_wait(uint32_t bar, uint32_t parity) {
  for (uint32_t n = 0; !mbar_try(bar, parity) && n < SPIN_LIMIT; n++) {}
}
__device__ __forceinline__ uint32_t mapa(uint32_t addr, uint32_t rank) {
  uint32_t r;
  asm volatile("mapa.shared::cluster.u32 %0, %1, %2;" : "=r"(r) : "r"(addr), "r"(rank));
  return r;
}

__device__ __forceinline__ void tma_2d(uint32_t dst, const CUtensorMap* m, uint32_t bar, int c0, int c1) {
  asm volatile("cp.async.bulk.tensor.2d.shared::cluster.global.mbarrier::complete_tx::bytes [%0], [%1, {%3, %4}], [%2];"
               ::"r"(dst), "l"(m), "r"(bar), "r"(c0), "r"(c1) : "memory");
}
__device__ __forceinline__ void tma_3d(uint32_t dst, const CUtensorMap* m, uint32_t bar, int c0, int c1, int c2) {
  asm volatile("cp.async.bulk.tensor.3d.shared::cluster.global.mbarrier::complete_tx::bytes [%0], [%1, {%3, %4, %5}], [%2];"
               ::"r"(dst), "l"(m), "r"(bar), "r"(c0), "r"(c1), "r"(c2) : "memory");
}
__device__ __forceinline__ void tma_4d(uint32_t dst, const CUtensorMap* m, uint32_t bar, int c0, int c1, int c2, int c3) {
  asm volatile("cp.async.bulk.tensor.4d.shared::cluster.global.mbarrier::complete_tx::bytes [%0], [%1, {%3, %4, %5, %6}], [%2];"
               ::"r"(dst), "l"(m), "r"(bar), "r"(c0), "r"(c1), "r"(c2), "r"(c3) : "memory");
}

__device__ __forceinline__ uint4 ld_ll(const uint4* p) {
  uint4 v;
  asm volatile("ld.relaxed.gpu.global.v4.u32 {%0,%1,%2,%3}, [%4];" : "=r"(v.x), "=r"(v.y), "=r"(v.z), "=r"(v.w) : "l"(p) : "memory");
  return v;
}
__device__ __forceinline__ void st_ll(uint4* p, uint4 v) {
  asm volatile("st.relaxed.gpu.global.v4.u32 [%0], {%1,%2,%3,%4};" ::"l"(p), "r"(v.x), "r"(v.y), "r"(v.z), "r"(v.w) : "memory");
}
__device__ __forceinline__ uint4 lds128(uint32_t a) {
  uint4 v;
  asm volatile("ld.shared.v4.u32 {%0,%1,%2,%3}, [%4];" : "=r"(v.x), "=r"(v.y), "=r"(v.z), "=r"(v.w) : "r"(a) : "memory");
  return v;
}
__device__ __forceinline__ void sts128(uint32_t a, uint4 v) {
  asm volatile("st.shared.v4.u32 [%0], {%1,%2,%3,%4};" ::"r"(a), "r"(v.x), "r"(v.y), "r"(v.z), "r"(v.w) : "memory");
}
__device__ __forceinline__ void st_async128(uint32_t cluster_addr, uint4 v, uint32_t cluster_bar) {
  asm volatile("st.async.weak.shared::cluster.mbarrier::complete_tx::bytes.v4.b32 [%0], {%1,%2,%3,%4}, [%5];"
               ::"r"(cluster_addr), "r"(v.x), "r"(v.y), "r"(v.z), "r"(v.w), "r"(cluster_bar) : "memory");
}
__device__ __forceinline__ uint32_t pack2(float lo, float hi) {
  uint32_t r;
  asm("cvt.rn.bf16x2.f32 %0, %1, %2;" : "=r"(r) : "f"(hi), "f"(lo));
  return r;
}
__device__ __forceinline__ float bf_lo(uint32_t w) { return __uint_as_float(w << 16); }
__device__ __forceinline__ float bf_hi(uint32_t w) { return __uint_as_float(w & 0xffff0000u); }
__device__ __forceinline__ uint32_t set_tag(uint32_t w, uint32_t tag) { return (w & ~1u) | tag; }
__device__ __forceinline__ uint32_t movm(uint32_t a) {
  uint32_t d;
  asm("movmatrix.sync.aligned.m8n8.trans.b16 %0, %1;" : "=r"(d) : "r"(a));
  return d;
}
__device__ __forceinline__ void mma1688(float (&d)[4], uint32_t a0, uint32_t a1, uint32_t b0) {
  asm("mma.sync.aligned.m16n8k8.row.col.f32.bf16.bf16.f32 {%0,%1,%2,%3}, {%4,%5}, {%6}, {%0,%1,%2,%3};"
      : "+f"(d[0]), "+f"(d[1]), "+f"(d[2]), "+f"(d[3])
      : "r"(a0), "r"(a1), "r"(b0));
}
__device__ __forceinline__ void mma16816_z(float (&d)[4], const uint4& a, uint32_t b0, uint32_t b1) {
  asm("mma.sync.aligned.m16n8k16.row.col.f32.bf16.bf16.f32 {%0,%1,%2,%3}, {%4,%5,%6,%7}, {%8,%9}, {%10,%10,%10,%10};"
      : "=f"(d[0]), "=f"(d[1]), "=f"(d[2]), "=f"(d[3])
      : "r"(a.x), "r"(a.y), "r"(a.z), "r"(a.w), "r"(b0), "r"(b1), "f"(0.f));
}
__device__ __forceinline__ float ex2(float x) {
  float y;
  asm("ex2.approx.ftz.f32 %0, %1;" : "=f"(y) : "f"(x));
  return y;
}
__device__ __forceinline__ float rcp(float x) {
  float y;
  asm("rcp.approx.ftz.f32 %0, %1;" : "=f"(y) : "f"(x));
  return y;
}
__device__ __forceinline__ void cp_async16(uint32_t dst, const void* src) {
  asm volatile("cp.async.cg.shared.global [%0], [%1], 16;" ::"r"(dst), "l"(src) : "memory");
}
__device__ __forceinline__ void cp_wait_all() { asm volatile("cp.async.wait_all;" ::: "memory"); }
template <int N> __device__ __forceinline__ void cp_wait() { asm volatile("cp.async.wait_group %0;" ::"n"(N) : "memory"); }
__device__ __forceinline__ void bar_wg(int id) { asm volatile("bar.sync %0, 128;" ::"r"(id) : "memory"); }
#define COLD_DELAY 900
__device__ __forceinline__ void cold_delay(uint32_t L) {
  if (L == 0) {
    const uint32_t t0 = (uint32_t)clock();
    while ((uint32_t)clock() - t0 < COLD_DELAY) {}
  }
}
__device__ __forceinline__ void wg_fence() { asm volatile("wgmma.fence.sync.aligned;" ::: "memory"); }
__device__ __forceinline__ void wg_commit() { asm volatile("wgmma.commit_group.sync.aligned;" ::: "memory"); }
template <int N> __device__ __forceinline__ void wg_wait() { asm volatile("wgmma.wait_group.sync.aligned %0;" ::"n"(N) : "memory"); }
__device__ __forceinline__ void keep(const uint4& a) { asm volatile("" ::"r"(a.x), "r"(a.y), "r"(a.z), "r"(a.w) : "memory"); }
template <int T> __device__ __forceinline__ void zero_acc(float (&d)[T]) {
#pragma unroll
  for (int i = 0; i < T; i++) d[i] = 0.f;
}
template <int T> __device__ __forceinline__ void fence_acc(float (&d)[T]) {
#pragma unroll
  for (int i = 0; i < T; i++) asm volatile("" : "+f"(d[i])::"memory");
}

template <int O, int T> __device__ __forceinline__ void wgmma_rs_n64(float (&d)[T], const uint4& a, uint64_t db) {
  asm volatile("{\n.reg .pred p;\nsetp.ne.b32 p, 1, 0;\n"
    "wgmma.mma_async.sync.aligned.m64n64k16.f32.bf16.bf16 "
    "{%0, %1, %2, %3, %4, %5, %6, %7, %8, %9, %10, %11, %12, %13, %14, %15, "
    "%16, %17, %18, %19, %20, %21, %22, %23, %24, %25, %26, %27, %28, %29, %30, %31}, "
    "{%32, %33, %34, %35}, %36, p, 1, 1, 1;\n}\n"
    : "+f"(d[O + 0]), "+f"(d[O + 1]), "+f"(d[O + 2]), "+f"(d[O + 3]), "+f"(d[O + 4]), "+f"(d[O + 5]), "+f"(d[O + 6]), "+f"(d[O + 7]),
      "+f"(d[O + 8]), "+f"(d[O + 9]), "+f"(d[O + 10]), "+f"(d[O + 11]), "+f"(d[O + 12]), "+f"(d[O + 13]), "+f"(d[O + 14]), "+f"(d[O + 15]),
      "+f"(d[O + 16]), "+f"(d[O + 17]), "+f"(d[O + 18]), "+f"(d[O + 19]), "+f"(d[O + 20]), "+f"(d[O + 21]), "+f"(d[O + 22]), "+f"(d[O + 23]),
      "+f"(d[O + 24]), "+f"(d[O + 25]), "+f"(d[O + 26]), "+f"(d[O + 27]), "+f"(d[O + 28]), "+f"(d[O + 29]), "+f"(d[O + 30]), "+f"(d[O + 31])
    : "r"(a.x), "r"(a.y), "r"(a.z), "r"(a.w), "l"(db));
}
template <int O, int T> __device__ __forceinline__ void wgmma_rs_n64_init(float (&d)[T], const uint4& a, uint64_t db) {
  asm volatile("{\n.reg .pred p;\nsetp.ne.b32 p, 0, 0;\n"
    "wgmma.mma_async.sync.aligned.m64n64k16.f32.bf16.bf16 "
    "{%0, %1, %2, %3, %4, %5, %6, %7, %8, %9, %10, %11, %12, %13, %14, %15, "
    "%16, %17, %18, %19, %20, %21, %22, %23, %24, %25, %26, %27, %28, %29, %30, %31}, "
    "{%32, %33, %34, %35}, %36, p, 1, 1, 1;\n}\n"
    : "=f"(d[O + 0]), "=f"(d[O + 1]), "=f"(d[O + 2]), "=f"(d[O + 3]), "=f"(d[O + 4]), "=f"(d[O + 5]), "=f"(d[O + 6]), "=f"(d[O + 7]),
      "=f"(d[O + 8]), "=f"(d[O + 9]), "=f"(d[O + 10]), "=f"(d[O + 11]), "=f"(d[O + 12]), "=f"(d[O + 13]), "=f"(d[O + 14]), "=f"(d[O + 15]),
      "=f"(d[O + 16]), "=f"(d[O + 17]), "=f"(d[O + 18]), "=f"(d[O + 19]), "=f"(d[O + 20]), "=f"(d[O + 21]), "=f"(d[O + 22]), "=f"(d[O + 23]),
      "=f"(d[O + 24]), "=f"(d[O + 25]), "=f"(d[O + 26]), "=f"(d[O + 27]), "=f"(d[O + 28]), "=f"(d[O + 29]), "=f"(d[O + 30]), "=f"(d[O + 31])
    : "r"(a.x), "r"(a.y), "r"(a.z), "r"(a.w), "l"(db));
}
template <bool INIT, int O, int T> __device__ __forceinline__ void wgmma_n64(float (&d)[T], const uint4& a, uint64_t db) {
  if constexpr (INIT) wgmma_rs_n64_init<O>(d, a, db); else wgmma_rs_n64<O>(d, a, db);
}
template <int O, int T> __device__ __forceinline__ void wgmma_rs_n128(float (&d)[T], const uint4& a, uint64_t db) {
  asm volatile("{\n.reg .pred p;\nsetp.ne.b32 p, 1, 0;\n"
    "wgmma.mma_async.sync.aligned.m64n128k16.f32.bf16.bf16 "
    "{%0, %1, %2, %3, %4, %5, %6, %7, %8, %9, %10, %11, %12, %13, %14, %15, "
    "%16, %17, %18, %19, %20, %21, %22, %23, %24, %25, %26, %27, %28, %29, %30, %31, "
    "%32, %33, %34, %35, %36, %37, %38, %39, %40, %41, %42, %43, %44, %45, %46, %47, "
    "%48, %49, %50, %51, %52, %53, %54, %55, %56, %57, %58, %59, %60, %61, %62, %63}, "
    "{%64, %65, %66, %67}, %68, p, 1, 1, 1;\n}\n"
    : "+f"(d[O + 0]), "+f"(d[O + 1]), "+f"(d[O + 2]), "+f"(d[O + 3]), "+f"(d[O + 4]), "+f"(d[O + 5]), "+f"(d[O + 6]), "+f"(d[O + 7]),
      "+f"(d[O + 8]), "+f"(d[O + 9]), "+f"(d[O + 10]), "+f"(d[O + 11]), "+f"(d[O + 12]), "+f"(d[O + 13]), "+f"(d[O + 14]), "+f"(d[O + 15]),
      "+f"(d[O + 16]), "+f"(d[O + 17]), "+f"(d[O + 18]), "+f"(d[O + 19]), "+f"(d[O + 20]), "+f"(d[O + 21]), "+f"(d[O + 22]), "+f"(d[O + 23]),
      "+f"(d[O + 24]), "+f"(d[O + 25]), "+f"(d[O + 26]), "+f"(d[O + 27]), "+f"(d[O + 28]), "+f"(d[O + 29]), "+f"(d[O + 30]), "+f"(d[O + 31]),
      "+f"(d[O + 32]), "+f"(d[O + 33]), "+f"(d[O + 34]), "+f"(d[O + 35]), "+f"(d[O + 36]), "+f"(d[O + 37]), "+f"(d[O + 38]), "+f"(d[O + 39]),
      "+f"(d[O + 40]), "+f"(d[O + 41]), "+f"(d[O + 42]), "+f"(d[O + 43]), "+f"(d[O + 44]), "+f"(d[O + 45]), "+f"(d[O + 46]), "+f"(d[O + 47]),
      "+f"(d[O + 48]), "+f"(d[O + 49]), "+f"(d[O + 50]), "+f"(d[O + 51]), "+f"(d[O + 52]), "+f"(d[O + 53]), "+f"(d[O + 54]), "+f"(d[O + 55]),
      "+f"(d[O + 56]), "+f"(d[O + 57]), "+f"(d[O + 58]), "+f"(d[O + 59]), "+f"(d[O + 60]), "+f"(d[O + 61]), "+f"(d[O + 62]), "+f"(d[O + 63])
    : "r"(a.x), "r"(a.y), "r"(a.z), "r"(a.w), "l"(db));
}
template <int O, int T> __device__ __forceinline__ void wgmma_rs_n128_init(float (&d)[T], const uint4& a, uint64_t db) {
  asm volatile("{\n.reg .pred p;\nsetp.ne.b32 p, 0, 0;\n"
    "wgmma.mma_async.sync.aligned.m64n128k16.f32.bf16.bf16 "
    "{%0, %1, %2, %3, %4, %5, %6, %7, %8, %9, %10, %11, %12, %13, %14, %15, "
    "%16, %17, %18, %19, %20, %21, %22, %23, %24, %25, %26, %27, %28, %29, %30, %31, "
    "%32, %33, %34, %35, %36, %37, %38, %39, %40, %41, %42, %43, %44, %45, %46, %47, "
    "%48, %49, %50, %51, %52, %53, %54, %55, %56, %57, %58, %59, %60, %61, %62, %63}, "
    "{%64, %65, %66, %67}, %68, p, 1, 1, 1;\n}\n"
    : "=f"(d[O + 0]), "=f"(d[O + 1]), "=f"(d[O + 2]), "=f"(d[O + 3]), "=f"(d[O + 4]), "=f"(d[O + 5]), "=f"(d[O + 6]), "=f"(d[O + 7]),
      "=f"(d[O + 8]), "=f"(d[O + 9]), "=f"(d[O + 10]), "=f"(d[O + 11]), "=f"(d[O + 12]), "=f"(d[O + 13]), "=f"(d[O + 14]), "=f"(d[O + 15]),
      "=f"(d[O + 16]), "=f"(d[O + 17]), "=f"(d[O + 18]), "=f"(d[O + 19]), "=f"(d[O + 20]), "=f"(d[O + 21]), "=f"(d[O + 22]), "=f"(d[O + 23]),
      "=f"(d[O + 24]), "=f"(d[O + 25]), "=f"(d[O + 26]), "=f"(d[O + 27]), "=f"(d[O + 28]), "=f"(d[O + 29]), "=f"(d[O + 30]), "=f"(d[O + 31]),
      "=f"(d[O + 32]), "=f"(d[O + 33]), "=f"(d[O + 34]), "=f"(d[O + 35]), "=f"(d[O + 36]), "=f"(d[O + 37]), "=f"(d[O + 38]), "=f"(d[O + 39]),
      "=f"(d[O + 40]), "=f"(d[O + 41]), "=f"(d[O + 42]), "=f"(d[O + 43]), "=f"(d[O + 44]), "=f"(d[O + 45]), "=f"(d[O + 46]), "=f"(d[O + 47]),
      "=f"(d[O + 48]), "=f"(d[O + 49]), "=f"(d[O + 50]), "=f"(d[O + 51]), "=f"(d[O + 52]), "=f"(d[O + 53]), "=f"(d[O + 54]), "=f"(d[O + 55]),
      "=f"(d[O + 56]), "=f"(d[O + 57]), "=f"(d[O + 58]), "=f"(d[O + 59]), "=f"(d[O + 60]), "=f"(d[O + 61]), "=f"(d[O + 62]), "=f"(d[O + 63])
    : "r"(a.x), "r"(a.y), "r"(a.z), "r"(a.w), "l"(db));
}
template <bool INIT, int O, int T> __device__ __forceinline__ void wgmma_n128(float (&d)[T], const uint4& a, uint64_t db) {
  if constexpr (INIT) wgmma_rs_n128_init<O>(d, a, db); else wgmma_rs_n128<O>(d, a, db);
}
template <int O, int T> __device__ __forceinline__ void wgmma_rs_n192(float (&d)[T], const uint4& a, uint64_t db) {
  asm volatile("{\n.reg .pred p;\nsetp.ne.b32 p, 1, 0;\n"
    "wgmma.mma_async.sync.aligned.m64n192k16.f32.bf16.bf16 "
    "{%0, %1, %2, %3, %4, %5, %6, %7, %8, %9, %10, %11, %12, %13, %14, %15, "
    "%16, %17, %18, %19, %20, %21, %22, %23, %24, %25, %26, %27, %28, %29, %30, %31, "
    "%32, %33, %34, %35, %36, %37, %38, %39, %40, %41, %42, %43, %44, %45, %46, %47, "
    "%48, %49, %50, %51, %52, %53, %54, %55, %56, %57, %58, %59, %60, %61, %62, %63, "
    "%64, %65, %66, %67, %68, %69, %70, %71, %72, %73, %74, %75, %76, %77, %78, %79, "
    "%80, %81, %82, %83, %84, %85, %86, %87, %88, %89, %90, %91, %92, %93, %94, %95}, "
    "{%96, %97, %98, %99}, %100, p, 1, 1, 1;\n}\n"
    : "+f"(d[O + 0]), "+f"(d[O + 1]), "+f"(d[O + 2]), "+f"(d[O + 3]), "+f"(d[O + 4]), "+f"(d[O + 5]), "+f"(d[O + 6]), "+f"(d[O + 7]),
      "+f"(d[O + 8]), "+f"(d[O + 9]), "+f"(d[O + 10]), "+f"(d[O + 11]), "+f"(d[O + 12]), "+f"(d[O + 13]), "+f"(d[O + 14]), "+f"(d[O + 15]),
      "+f"(d[O + 16]), "+f"(d[O + 17]), "+f"(d[O + 18]), "+f"(d[O + 19]), "+f"(d[O + 20]), "+f"(d[O + 21]), "+f"(d[O + 22]), "+f"(d[O + 23]),
      "+f"(d[O + 24]), "+f"(d[O + 25]), "+f"(d[O + 26]), "+f"(d[O + 27]), "+f"(d[O + 28]), "+f"(d[O + 29]), "+f"(d[O + 30]), "+f"(d[O + 31]),
      "+f"(d[O + 32]), "+f"(d[O + 33]), "+f"(d[O + 34]), "+f"(d[O + 35]), "+f"(d[O + 36]), "+f"(d[O + 37]), "+f"(d[O + 38]), "+f"(d[O + 39]),
      "+f"(d[O + 40]), "+f"(d[O + 41]), "+f"(d[O + 42]), "+f"(d[O + 43]), "+f"(d[O + 44]), "+f"(d[O + 45]), "+f"(d[O + 46]), "+f"(d[O + 47]),
      "+f"(d[O + 48]), "+f"(d[O + 49]), "+f"(d[O + 50]), "+f"(d[O + 51]), "+f"(d[O + 52]), "+f"(d[O + 53]), "+f"(d[O + 54]), "+f"(d[O + 55]),
      "+f"(d[O + 56]), "+f"(d[O + 57]), "+f"(d[O + 58]), "+f"(d[O + 59]), "+f"(d[O + 60]), "+f"(d[O + 61]), "+f"(d[O + 62]), "+f"(d[O + 63]),
      "+f"(d[O + 64]), "+f"(d[O + 65]), "+f"(d[O + 66]), "+f"(d[O + 67]), "+f"(d[O + 68]), "+f"(d[O + 69]), "+f"(d[O + 70]), "+f"(d[O + 71]),
      "+f"(d[O + 72]), "+f"(d[O + 73]), "+f"(d[O + 74]), "+f"(d[O + 75]), "+f"(d[O + 76]), "+f"(d[O + 77]), "+f"(d[O + 78]), "+f"(d[O + 79]),
      "+f"(d[O + 80]), "+f"(d[O + 81]), "+f"(d[O + 82]), "+f"(d[O + 83]), "+f"(d[O + 84]), "+f"(d[O + 85]), "+f"(d[O + 86]), "+f"(d[O + 87]),
      "+f"(d[O + 88]), "+f"(d[O + 89]), "+f"(d[O + 90]), "+f"(d[O + 91]), "+f"(d[O + 92]), "+f"(d[O + 93]), "+f"(d[O + 94]), "+f"(d[O + 95])
    : "r"(a.x), "r"(a.y), "r"(a.z), "r"(a.w), "l"(db));
}
template <int O, int T> __device__ __forceinline__ void wgmma_rs_n192_init(float (&d)[T], const uint4& a, uint64_t db) {
  asm volatile("{\n.reg .pred p;\nsetp.ne.b32 p, 0, 0;\n"
    "wgmma.mma_async.sync.aligned.m64n192k16.f32.bf16.bf16 "
    "{%0, %1, %2, %3, %4, %5, %6, %7, %8, %9, %10, %11, %12, %13, %14, %15, "
    "%16, %17, %18, %19, %20, %21, %22, %23, %24, %25, %26, %27, %28, %29, %30, %31, "
    "%32, %33, %34, %35, %36, %37, %38, %39, %40, %41, %42, %43, %44, %45, %46, %47, "
    "%48, %49, %50, %51, %52, %53, %54, %55, %56, %57, %58, %59, %60, %61, %62, %63, "
    "%64, %65, %66, %67, %68, %69, %70, %71, %72, %73, %74, %75, %76, %77, %78, %79, "
    "%80, %81, %82, %83, %84, %85, %86, %87, %88, %89, %90, %91, %92, %93, %94, %95}, "
    "{%96, %97, %98, %99}, %100, p, 1, 1, 1;\n}\n"
    : "=f"(d[O + 0]), "=f"(d[O + 1]), "=f"(d[O + 2]), "=f"(d[O + 3]), "=f"(d[O + 4]), "=f"(d[O + 5]), "=f"(d[O + 6]), "=f"(d[O + 7]),
      "=f"(d[O + 8]), "=f"(d[O + 9]), "=f"(d[O + 10]), "=f"(d[O + 11]), "=f"(d[O + 12]), "=f"(d[O + 13]), "=f"(d[O + 14]), "=f"(d[O + 15]),
      "=f"(d[O + 16]), "=f"(d[O + 17]), "=f"(d[O + 18]), "=f"(d[O + 19]), "=f"(d[O + 20]), "=f"(d[O + 21]), "=f"(d[O + 22]), "=f"(d[O + 23]),
      "=f"(d[O + 24]), "=f"(d[O + 25]), "=f"(d[O + 26]), "=f"(d[O + 27]), "=f"(d[O + 28]), "=f"(d[O + 29]), "=f"(d[O + 30]), "=f"(d[O + 31]),
      "=f"(d[O + 32]), "=f"(d[O + 33]), "=f"(d[O + 34]), "=f"(d[O + 35]), "=f"(d[O + 36]), "=f"(d[O + 37]), "=f"(d[O + 38]), "=f"(d[O + 39]),
      "=f"(d[O + 40]), "=f"(d[O + 41]), "=f"(d[O + 42]), "=f"(d[O + 43]), "=f"(d[O + 44]), "=f"(d[O + 45]), "=f"(d[O + 46]), "=f"(d[O + 47]),
      "=f"(d[O + 48]), "=f"(d[O + 49]), "=f"(d[O + 50]), "=f"(d[O + 51]), "=f"(d[O + 52]), "=f"(d[O + 53]), "=f"(d[O + 54]), "=f"(d[O + 55]),
      "=f"(d[O + 56]), "=f"(d[O + 57]), "=f"(d[O + 58]), "=f"(d[O + 59]), "=f"(d[O + 60]), "=f"(d[O + 61]), "=f"(d[O + 62]), "=f"(d[O + 63]),
      "=f"(d[O + 64]), "=f"(d[O + 65]), "=f"(d[O + 66]), "=f"(d[O + 67]), "=f"(d[O + 68]), "=f"(d[O + 69]), "=f"(d[O + 70]), "=f"(d[O + 71]),
      "=f"(d[O + 72]), "=f"(d[O + 73]), "=f"(d[O + 74]), "=f"(d[O + 75]), "=f"(d[O + 76]), "=f"(d[O + 77]), "=f"(d[O + 78]), "=f"(d[O + 79]),
      "=f"(d[O + 80]), "=f"(d[O + 81]), "=f"(d[O + 82]), "=f"(d[O + 83]), "=f"(d[O + 84]), "=f"(d[O + 85]), "=f"(d[O + 86]), "=f"(d[O + 87]),
      "=f"(d[O + 88]), "=f"(d[O + 89]), "=f"(d[O + 90]), "=f"(d[O + 91]), "=f"(d[O + 92]), "=f"(d[O + 93]), "=f"(d[O + 94]), "=f"(d[O + 95])
    : "r"(a.x), "r"(a.y), "r"(a.z), "r"(a.w), "l"(db));
}
template <bool INIT, int O, int T> __device__ __forceinline__ void wgmma_n192(float (&d)[T], const uint4& a, uint64_t db) {
  if constexpr (INIT) wgmma_rs_n192_init<O>(d, a, db); else wgmma_rs_n192<O>(d, a, db);
}
template <int O, int T> __device__ __forceinline__ void wgmma_rs_n256(float (&d)[T], const uint4& a, uint64_t db) {
  asm volatile("{\n.reg .pred p;\nsetp.ne.b32 p, 1, 0;\n"
    "wgmma.mma_async.sync.aligned.m64n256k16.f32.bf16.bf16 "
    "{%0, %1, %2, %3, %4, %5, %6, %7, %8, %9, %10, %11, %12, %13, %14, %15, "
    "%16, %17, %18, %19, %20, %21, %22, %23, %24, %25, %26, %27, %28, %29, %30, %31, "
    "%32, %33, %34, %35, %36, %37, %38, %39, %40, %41, %42, %43, %44, %45, %46, %47, "
    "%48, %49, %50, %51, %52, %53, %54, %55, %56, %57, %58, %59, %60, %61, %62, %63, "
    "%64, %65, %66, %67, %68, %69, %70, %71, %72, %73, %74, %75, %76, %77, %78, %79, "
    "%80, %81, %82, %83, %84, %85, %86, %87, %88, %89, %90, %91, %92, %93, %94, %95, "
    "%96, %97, %98, %99, %100, %101, %102, %103, %104, %105, %106, %107, %108, %109, %110, %111, "
    "%112, %113, %114, %115, %116, %117, %118, %119, %120, %121, %122, %123, %124, %125, %126, %127}, "
    "{%128, %129, %130, %131}, %132, p, 1, 1, 1;\n}\n"
    : "+f"(d[O + 0]), "+f"(d[O + 1]), "+f"(d[O + 2]), "+f"(d[O + 3]), "+f"(d[O + 4]), "+f"(d[O + 5]), "+f"(d[O + 6]), "+f"(d[O + 7]),
      "+f"(d[O + 8]), "+f"(d[O + 9]), "+f"(d[O + 10]), "+f"(d[O + 11]), "+f"(d[O + 12]), "+f"(d[O + 13]), "+f"(d[O + 14]), "+f"(d[O + 15]),
      "+f"(d[O + 16]), "+f"(d[O + 17]), "+f"(d[O + 18]), "+f"(d[O + 19]), "+f"(d[O + 20]), "+f"(d[O + 21]), "+f"(d[O + 22]), "+f"(d[O + 23]),
      "+f"(d[O + 24]), "+f"(d[O + 25]), "+f"(d[O + 26]), "+f"(d[O + 27]), "+f"(d[O + 28]), "+f"(d[O + 29]), "+f"(d[O + 30]), "+f"(d[O + 31]),
      "+f"(d[O + 32]), "+f"(d[O + 33]), "+f"(d[O + 34]), "+f"(d[O + 35]), "+f"(d[O + 36]), "+f"(d[O + 37]), "+f"(d[O + 38]), "+f"(d[O + 39]),
      "+f"(d[O + 40]), "+f"(d[O + 41]), "+f"(d[O + 42]), "+f"(d[O + 43]), "+f"(d[O + 44]), "+f"(d[O + 45]), "+f"(d[O + 46]), "+f"(d[O + 47]),
      "+f"(d[O + 48]), "+f"(d[O + 49]), "+f"(d[O + 50]), "+f"(d[O + 51]), "+f"(d[O + 52]), "+f"(d[O + 53]), "+f"(d[O + 54]), "+f"(d[O + 55]),
      "+f"(d[O + 56]), "+f"(d[O + 57]), "+f"(d[O + 58]), "+f"(d[O + 59]), "+f"(d[O + 60]), "+f"(d[O + 61]), "+f"(d[O + 62]), "+f"(d[O + 63]),
      "+f"(d[O + 64]), "+f"(d[O + 65]), "+f"(d[O + 66]), "+f"(d[O + 67]), "+f"(d[O + 68]), "+f"(d[O + 69]), "+f"(d[O + 70]), "+f"(d[O + 71]),
      "+f"(d[O + 72]), "+f"(d[O + 73]), "+f"(d[O + 74]), "+f"(d[O + 75]), "+f"(d[O + 76]), "+f"(d[O + 77]), "+f"(d[O + 78]), "+f"(d[O + 79]),
      "+f"(d[O + 80]), "+f"(d[O + 81]), "+f"(d[O + 82]), "+f"(d[O + 83]), "+f"(d[O + 84]), "+f"(d[O + 85]), "+f"(d[O + 86]), "+f"(d[O + 87]),
      "+f"(d[O + 88]), "+f"(d[O + 89]), "+f"(d[O + 90]), "+f"(d[O + 91]), "+f"(d[O + 92]), "+f"(d[O + 93]), "+f"(d[O + 94]), "+f"(d[O + 95]),
      "+f"(d[O + 96]), "+f"(d[O + 97]), "+f"(d[O + 98]), "+f"(d[O + 99]), "+f"(d[O + 100]), "+f"(d[O + 101]), "+f"(d[O + 102]), "+f"(d[O + 103]),
      "+f"(d[O + 104]), "+f"(d[O + 105]), "+f"(d[O + 106]), "+f"(d[O + 107]), "+f"(d[O + 108]), "+f"(d[O + 109]), "+f"(d[O + 110]), "+f"(d[O + 111]),
      "+f"(d[O + 112]), "+f"(d[O + 113]), "+f"(d[O + 114]), "+f"(d[O + 115]), "+f"(d[O + 116]), "+f"(d[O + 117]), "+f"(d[O + 118]), "+f"(d[O + 119]),
      "+f"(d[O + 120]), "+f"(d[O + 121]), "+f"(d[O + 122]), "+f"(d[O + 123]), "+f"(d[O + 124]), "+f"(d[O + 125]), "+f"(d[O + 126]), "+f"(d[O + 127])
    : "r"(a.x), "r"(a.y), "r"(a.z), "r"(a.w), "l"(db));
}
template <int O, int T> __device__ __forceinline__ void wgmma_rs_n256_init(float (&d)[T], const uint4& a, uint64_t db) {
  asm volatile("{\n.reg .pred p;\nsetp.ne.b32 p, 0, 0;\n"
    "wgmma.mma_async.sync.aligned.m64n256k16.f32.bf16.bf16 "
    "{%0, %1, %2, %3, %4, %5, %6, %7, %8, %9, %10, %11, %12, %13, %14, %15, "
    "%16, %17, %18, %19, %20, %21, %22, %23, %24, %25, %26, %27, %28, %29, %30, %31, "
    "%32, %33, %34, %35, %36, %37, %38, %39, %40, %41, %42, %43, %44, %45, %46, %47, "
    "%48, %49, %50, %51, %52, %53, %54, %55, %56, %57, %58, %59, %60, %61, %62, %63, "
    "%64, %65, %66, %67, %68, %69, %70, %71, %72, %73, %74, %75, %76, %77, %78, %79, "
    "%80, %81, %82, %83, %84, %85, %86, %87, %88, %89, %90, %91, %92, %93, %94, %95, "
    "%96, %97, %98, %99, %100, %101, %102, %103, %104, %105, %106, %107, %108, %109, %110, %111, "
    "%112, %113, %114, %115, %116, %117, %118, %119, %120, %121, %122, %123, %124, %125, %126, %127}, "
    "{%128, %129, %130, %131}, %132, p, 1, 1, 1;\n}\n"
    : "=f"(d[O + 0]), "=f"(d[O + 1]), "=f"(d[O + 2]), "=f"(d[O + 3]), "=f"(d[O + 4]), "=f"(d[O + 5]), "=f"(d[O + 6]), "=f"(d[O + 7]),
      "=f"(d[O + 8]), "=f"(d[O + 9]), "=f"(d[O + 10]), "=f"(d[O + 11]), "=f"(d[O + 12]), "=f"(d[O + 13]), "=f"(d[O + 14]), "=f"(d[O + 15]),
      "=f"(d[O + 16]), "=f"(d[O + 17]), "=f"(d[O + 18]), "=f"(d[O + 19]), "=f"(d[O + 20]), "=f"(d[O + 21]), "=f"(d[O + 22]), "=f"(d[O + 23]),
      "=f"(d[O + 24]), "=f"(d[O + 25]), "=f"(d[O + 26]), "=f"(d[O + 27]), "=f"(d[O + 28]), "=f"(d[O + 29]), "=f"(d[O + 30]), "=f"(d[O + 31]),
      "=f"(d[O + 32]), "=f"(d[O + 33]), "=f"(d[O + 34]), "=f"(d[O + 35]), "=f"(d[O + 36]), "=f"(d[O + 37]), "=f"(d[O + 38]), "=f"(d[O + 39]),
      "=f"(d[O + 40]), "=f"(d[O + 41]), "=f"(d[O + 42]), "=f"(d[O + 43]), "=f"(d[O + 44]), "=f"(d[O + 45]), "=f"(d[O + 46]), "=f"(d[O + 47]),
      "=f"(d[O + 48]), "=f"(d[O + 49]), "=f"(d[O + 50]), "=f"(d[O + 51]), "=f"(d[O + 52]), "=f"(d[O + 53]), "=f"(d[O + 54]), "=f"(d[O + 55]),
      "=f"(d[O + 56]), "=f"(d[O + 57]), "=f"(d[O + 58]), "=f"(d[O + 59]), "=f"(d[O + 60]), "=f"(d[O + 61]), "=f"(d[O + 62]), "=f"(d[O + 63]),
      "=f"(d[O + 64]), "=f"(d[O + 65]), "=f"(d[O + 66]), "=f"(d[O + 67]), "=f"(d[O + 68]), "=f"(d[O + 69]), "=f"(d[O + 70]), "=f"(d[O + 71]),
      "=f"(d[O + 72]), "=f"(d[O + 73]), "=f"(d[O + 74]), "=f"(d[O + 75]), "=f"(d[O + 76]), "=f"(d[O + 77]), "=f"(d[O + 78]), "=f"(d[O + 79]),
      "=f"(d[O + 80]), "=f"(d[O + 81]), "=f"(d[O + 82]), "=f"(d[O + 83]), "=f"(d[O + 84]), "=f"(d[O + 85]), "=f"(d[O + 86]), "=f"(d[O + 87]),
      "=f"(d[O + 88]), "=f"(d[O + 89]), "=f"(d[O + 90]), "=f"(d[O + 91]), "=f"(d[O + 92]), "=f"(d[O + 93]), "=f"(d[O + 94]), "=f"(d[O + 95]),
      "=f"(d[O + 96]), "=f"(d[O + 97]), "=f"(d[O + 98]), "=f"(d[O + 99]), "=f"(d[O + 100]), "=f"(d[O + 101]), "=f"(d[O + 102]), "=f"(d[O + 103]),
      "=f"(d[O + 104]), "=f"(d[O + 105]), "=f"(d[O + 106]), "=f"(d[O + 107]), "=f"(d[O + 108]), "=f"(d[O + 109]), "=f"(d[O + 110]), "=f"(d[O + 111]),
      "=f"(d[O + 112]), "=f"(d[O + 113]), "=f"(d[O + 114]), "=f"(d[O + 115]), "=f"(d[O + 116]), "=f"(d[O + 117]), "=f"(d[O + 118]), "=f"(d[O + 119]),
      "=f"(d[O + 120]), "=f"(d[O + 121]), "=f"(d[O + 122]), "=f"(d[O + 123]), "=f"(d[O + 124]), "=f"(d[O + 125]), "=f"(d[O + 126]), "=f"(d[O + 127])
    : "r"(a.x), "r"(a.y), "r"(a.z), "r"(a.w), "l"(db));
}
template <bool INIT, int O, int T> __device__ __forceinline__ void wgmma_n256(float (&d)[T], const uint4& a, uint64_t db) {
  if constexpr (INIT) wgmma_rs_n256_init<O>(d, a, db); else wgmma_rs_n256<O>(d, a, db);
}

template <int N> __device__ __forceinline__ void load_pk(uint4* a, const uint4* p) {
#pragma unroll
  for (int i = 0; i < N; i++) a[i] = ld_ll(p + i * 32);
}
__device__ __forceinline__ uint32_t xor_or(uint32_t a, uint32_t b, uint32_t t) {
  uint32_t r;
  asm("lop3.b32 %0, %1, %2, %3, 0x7E;" : "=r"(r) : "r"(a), "r"(b), "r"(t));
  return r;
}
template <int N> __device__ __forceinline__ bool ok_pk(const uint4* a, uint32_t tag) {
  static_assert(N % 2 == 0, "");
  uint32_t x = xor_or(a[0].x, a[1].x, tag);
#pragma unroll
  for (int i = 2; i < N; i += 2) x |= xor_or(a[i].x, a[i + 1].x, tag);
  return __all_sync(0xffffffffu, (x & 1u) == 0u);
}
template <int N> __device__ __forceinline__ void ensure_pk(uint4* a, const uint4* p, uint32_t tag) {
  if (ok_pk<N>(a, tag)) return;
  uint32_t n = 0;
  do { load_pk<N>(a, p); } while (!ok_pk<N>(a, tag) && ++n < SPIN_LIMIT);
}

constexpr int NSTAGE = 44;
constexpr int ST_WO = 8, ST_G1 = 12, ST_G2 = 20, ST_DN = 28;
__host__ __device__ constexpr int st_len(int s) { return s < ST_WO ? 3 : s < ST_G1 ? 2 : s < ST_G2 ? 4 : s < ST_DN ? 3 : 2; }
__host__ __device__ constexpr int st_g0(int s) {
  int pos = 0, g0 = 0;
  for (int i = 0; i <= s; i++) {
    if (pos + st_len(i) > NGRAN) pos = 0;
    g0 = pos;
    pos += st_len(i);
  }
  return g0;
}
__host__ __device__ constexpr int cnt_first(int g, int s) {
  int n = 0;
  for (int i = 0; i < s; i++) n += (st_g0(i) == g);
  return n;
}
__host__ __device__ constexpr int cnt_cover(int g, int s) {
  int n = 0;
  for (int i = 0; i < s; i++) n += (g >= st_g0(i) && g < st_g0(i) + st_len(i));
  return n;
}
__host__ __device__ constexpr uint32_t flip_mask(int s0, int s1) {
  uint32_t m = 0;
  for (int i = s0; i < s1; i++) m ^= ((1u << st_len(i)) - 1u) << st_g0(i);
  return m;
}
__host__ __device__ constexpr int dn_q(int i) { return i < 3 ? 0 : i < 6 ? 1 : i == 6 ? 0 : i == 7 ? 1 : i < 12 ? 2 : 3; }
__host__ __device__ constexpr int dn_par(int i) { return i < 8 ? (i == 2 || i == 4 || i >= 6) : (i & 1); }
__host__ __device__ constexpr int dn_kh(int i) { return i < 8 ? (i == 1 || i >= 5) : ((i & 3) >= 2); }
template <int I> struct IC { static constexpr int value = I; };
template <int B, int E, typename F> __device__ __forceinline__ void static_for(F&& f) {
  if constexpr (B < E) { f(IC<B>{}); static_for<B + 1, E>(f); }
}
template <int S> __device__ __forceinline__ void cons_acquire(uint32_t sbase, uint32_t L) {
  constexpr int g0 = st_g0(S);
  constexpr uint32_t p0 = cnt_first(g0, S) & 1, odd = cnt_first(g0, NSTAGE) & 1;
  mbar_wait(sbase + SM_MISC + BAR_FULL + 8 * g0, p0 ^ (L & odd));
}
template <int S> __device__ __forceinline__ void cons_release(uint32_t sbase, int lane) {
  if (lane < st_len(S)) mbar_arrive(sbase + SM_MISC + BAR_EMPTY + 8 * st_g0(S) + 8 * lane);
}
__device__ __forceinline__ bool elect_one() {
  uint32_t p;
  asm volatile("{\n.reg .pred P;\nelect.sync _|P, 0xffffffff;\nselp.u32 %0, 1, 0, P;\n}" : "=r"(p));
  return p != 0;
}
struct ProdRing { uint32_t pos, par; };
template <int N> __device__ __forceinline__ uint32_t prod_acquire(uint32_t sbase, ProdRing& r) {
  if (r.pos + N > NGRAN) r.pos = 0;
  const uint32_t g0 = r.pos;
#pragma unroll
  for (uint32_t i = 0; i < N; i++) mbar_wait(sbase + SM_MISC + BAR_EMPTY + 8 * (g0 + i), ((r.par >> (g0 + i)) & 1u) ^ 1u);
  r.par ^= ((1u << N) - 1u) << g0;
  r.pos = g0 + N;
  return g0;
}
template <int S> __device__ __forceinline__ void prod_acquire_static(uint32_t sbase, uint32_t L) {
  constexpr int g0 = st_g0(S);
  static_for<0, st_len(S)>([&](auto I) {
    constexpr int g = g0 + I.value;
    constexpr uint32_t p0 = cnt_cover(g, S) & 1, odd = cnt_cover(g, NSTAGE) & 1;
    mbar_wait(sbase + SM_MISC + BAR_EMPTY + 8 * g, p0 ^ (L & odd) ^ 1u);
  });
}
template <int S, int KSTEP_BYTES, int LBO, int SBO, int SWZ> __device__ __forceinline__ constexpr uint64_t st_desc(int k) {
  return (uint64_t)((SMEM_ORIGIN + st_g0(S) * GRAN + k * KSTEP_BYTES) >> 4) | ((uint64_t)(LBO >> 4) << 16) |
         ((uint64_t)(SBO >> 4) << 32) | ((uint64_t)SWZ << 62);
}

__device__ __forceinline__ void combine_stats(const uint4& p0, const uint4& p1, float& mean_lo, float& rstd_lo, float& mean_hi, float& rstd_hi) {
  float m0 = __uint_as_float(p0.x), q0 = __uint_as_float(p0.y), m0h = __uint_as_float(p0.z), q0h = __uint_as_float(p0.w);
  float m1 = __uint_as_float(p1.x), q1 = __uint_as_float(p1.y), m1h = __uint_as_float(p1.z), q1h = __uint_as_float(p1.w);
  float s = m0 + m1, sh = m0h + m1h;
  s += __shfl_xor_sync(0xffffffffu, s, 1); sh += __shfl_xor_sync(0xffffffffu, sh, 1);
  s += __shfl_xor_sync(0xffffffffu, s, 2); sh += __shfl_xor_sync(0xffffffffu, sh, 2);
  mean_lo = s * 0.125f; mean_hi = sh * 0.125f;
  float d0 = m0 - mean_lo, d1 = m1 - mean_lo, d0h = m0h - mean_hi, d1h = m1h - mean_hi;
  float t = q0 + q1 + 64.f * (d0 * d0 + d1 * d1), th = q0h + q1h + 64.f * (d0h * d0h + d1h * d1h);
  t += __shfl_xor_sync(0xffffffffu, t, 1); th += __shfl_xor_sync(0xffffffffu, th, 1);
  t += __shfl_xor_sync(0xffffffffu, t, 2); th += __shfl_xor_sync(0xffffffffu, th, 2);
  rstd_lo = rsqrtf(t * (1.f / 512.f) + 1e-5f);
  rstd_hi = rsqrtf(th * (1.f / 512.f) + 1e-5f);
}
__device__ __forceinline__ uint4 local_stats(const float (&v)[32]) {
  float s = 0.f, sh = 0.f;
#pragma unroll
  for (int i = 0; i < 4; i++) {
    s += (v[8 * i + 0] + v[8 * i + 1]) + (v[8 * i + 4] + v[8 * i + 5]);
    sh += (v[8 * i + 2] + v[8 * i + 3]) + (v[8 * i + 6] + v[8 * i + 7]);
  }
  s += __shfl_xor_sync(0xffffffffu, s, 1); sh += __shfl_xor_sync(0xffffffffu, sh, 1);
  s += __shfl_xor_sync(0xffffffffu, s, 2); sh += __shfl_xor_sync(0xffffffffu, sh, 2);
  float m = s * (1.f / 64.f), mh = sh * (1.f / 64.f);
  float q = 0.f, qh = 0.f;
#pragma unroll
  for (int i = 0; i < 4; i++) {
    float a = v[8 * i + 0] - m, b = v[8 * i + 1] - m, c = v[8 * i + 4] - m, d = v[8 * i + 5] - m;
    q += (a * a + b * b) + (c * c + d * d);
    float e = v[8 * i + 2] - mh, f = v[8 * i + 3] - mh, g = v[8 * i + 6] - mh, h = v[8 * i + 7] - mh;
    qh += (e * e + f * f) + (g * g + h * h);
  }
  q += __shfl_xor_sync(0xffffffffu, q, 1); qh += __shfl_xor_sync(0xffffffffu, qh, 1);
  q += __shfl_xor_sync(0xffffffffu, q, 2); qh += __shfl_xor_sync(0xffffffffu, qh, 2);
  return make_uint4(__float_as_uint(m), __float_as_uint(q), __float_as_uint(mh), __float_as_uint(qh));
}

__device__ __forceinline__ int slab_row0(int c, int g, int w) { return 1024 * g + 64 * c + 32 * (w >> 1) + (w & 1); }

__device__ __forceinline__ void owner_ln_publish(uint32_t sbase, const float (&v)[32], uint32_t tphase, uint32_t tag_xn, uint4 (&xraw)[4]) {
  PHASE_VARS;
  TS(40 + 4 * tphase);
  uint4 st = local_stats(v);
  if (qc == 0) sts128(sbase + SM_TSTAT + warp * 128 + qr * 16, st);
  uint4* xn = g_arena + c * ARENA + AR_XN + ((j) * 32 + 4 * warp) * 32 + lane;
  TS(41 + 4 * tphase);
  asm volatile("bar.sync 3, 256;" ::: "memory");
  TS(42 + 4 * tphase);
  const uint32_t rd = sbase + SM_TSTAT + qc * 256 + qr * 16;
  uint4 p0 = lds128(rd), p1 = lds128(rd + 128);
  float ml, rl, mh, rh;
  combine_stats(p0, p1, ml, rl, mh, rh);
  const float bl = -ml * rl, bh = -mh * rh;
#pragma unroll
  for (int i = 0; i < 4; i++) {
    uint4 o;
    o.x = set_tag(pack2(fmaf(v[8 * i + 0], rl, bl), fmaf(v[8 * i + 1], rl, bl)), tag_xn);
    o.y = pack2(fmaf(v[8 * i + 2], rh, bh), fmaf(v[8 * i + 3], rh, bh));
    o.z = pack2(fmaf(v[8 * i + 4], rl, bl), fmaf(v[8 * i + 5], rl, bl));
    o.w = pack2(fmaf(v[8 * i + 6], rh, bh), fmaf(v[8 * i + 7], rh, bh));
    st_ll(xn + i * 32, o);
  }
#pragma unroll
  for (int i = 0; i < 4; i++) {
    xraw[i].x = set_tag(pack2(v[8 * i + 0], v[8 * i + 1]), 1u);
    xraw[i].y = pack2(v[8 * i + 2], v[8 * i + 3]);
    xraw[i].z = pack2(v[8 * i + 4], v[8 * i + 5]);
    xraw[i].w = pack2(v[8 * i + 6], v[8 * i + 7]);
  }
}

__device__ __forceinline__ uint4 pack8(const float* a) {
  return make_uint4(pack2(a[0], a[1]), pack2(a[2], a[3]), pack2(a[4], a[5]), pack2(a[6], a[7]));
}
template <int U> __device__ __forceinline__ uint4 glu8(const float* g, float cl, float ch) {
  return make_uint4(pack2(g[0] * cl * g[U], g[1] * cl * g[U + 1]), pack2(g[2] * ch * g[U + 2], g[3] * ch * g[U + 3]),
                    pack2(g[4] * cl * g[U + 4], g[5] * cl * g[U + 5]), pack2(g[6] * ch * g[U + 6], g[7] * ch * g[U + 7]));
}
__device__ __forceinline__ uint32_t hfma2(uint32_t a, uint32_t b, uint32_t c) {
  uint32_t d;
  asm("fma.rn.bf16x2 %0, %1, %2, %3;" : "=r"(d) : "r"(a), "r"(b), "r"(c));
  return d;
}
__device__ __forceinline__ void keep4(const uint4 (&a)[4]) { keep(a[0]); keep(a[1]); keep(a[2]); keep(a[3]); }

#define STAGGER 0

__global__ void __launch_bounds__(NTHREADS, 1)
fused_kernel(const __grid_constant__ CUtensorMap m_qkv, const __grid_constant__ CUtensorMap m_wo,
             const __grid_constant__ CUtensorMap m_gu2, const __grid_constant__ CUtensorMap m_gu1,
             const __grid_constant__ CUtensorMap m_guh, const __grid_constant__ CUtensorMap m_wd112,
             const __grid_constant__ CUtensorMap m_wd80, const __grid_constant__ CUtensorMap m_wd32,
             const __nv_bfloat16* __restrict__ x_in,
             __nv_bfloat16* __restrict__ out
) {
  extern __shared__ __align__(1024) unsigned char smem_raw[];
  const uint32_t sbase = smem_u32(smem_raw);
  const uint32_t bars = sbase + SM_MISC;
  if ((sbase & 0xFFFFFFu) != SMEM_ORIGIN) return;
  TG(60);

  uint32_t xw[16];
  if (threadIdx.x < 256) {
    const int cc = blockIdx.x >> 3, jj = blockIdx.x & 7, ln = threadIdx.x & 31;
    const uint32_t* xp = reinterpret_cast<const uint32_t*>(x_in + (size_t)(slab_row0(cc, jj >> 2, jj & 3) + 2 * (ln >> 2)) * 512 + (threadIdx.x >> 5) * 64 + (ln & 3) * 2);
#pragma unroll
    for (int i = 0; i < 4; i++) {
      xw[4 * i] = __ldg(xp + i * 8); xw[4 * i + 1] = __ldg(xp + 16 * 256 + i * 8);
      xw[4 * i + 2] = __ldg(xp + i * 8 + 4); xw[4 * i + 3] = __ldg(xp + 16 * 256 + i * 8 + 4);
    }
  } else if (threadIdx.x == 256) {
    for (int i = 0; i < NGRAN; i++) { mbar_init(bars + BAR_FULL + 8 * i, 1); mbar_init(bars + BAR_EMPTY + 8 * i, 8); }
    for (int i = 0; i < 4; i++) mbar_init(bars + BAR_HRECV + 8 * i, 1);
    for (int i = 0; i < 2; i++) mbar_init(bars + BAR_HREADY + 8 * i, 4);
    asm volatile("fence.mbarrier_init.release.cluster;" ::: "memory");
  }
  __syncthreads();
  asm volatile("barrier.cluster.arrive.release.aligned;" ::: "memory");

  if (threadIdx.x >= 256) {
    asm volatile("setmaxnreg.dec.sync.aligned.u32 40;");
    const int warp = threadIdx.x >> 5;
    const int j = blockIdx.x & 7, b = j & 1;
    if (warp == 8) {
      ProdRing r{0u, 0u};
      const int cb0 = 224 * j + 32 * b, hb0 = 224 * j + 192 * (b ^ 1);
      const int jp = j ^ 1, cbp = 224 * jp + 32 * (b ^ 1), hbp = 224 * jp + 192 * b;
#pragma unroll 1
      for (uint32_t L = 0; L < 2; L++) {
        r.pos = 0;
        PSTOP_AT(L == 0 ? 0 : 3);
#pragma unroll 1
        for (int kb = 0; kb < 8; kb++) {
          const uint32_t g0 = prod_acquire<3>(sbase, r);
          if (elect_one()) {
            mbar_expect_tx(bars + BAR_FULL + 8 * g0, 24576);
            tma_3d(sbase + g0 * GRAN, &m_qkv, bars + BAR_FULL + 8 * g0, 64 * j, 64 * kb, 0);
          }
        }
        PSTOP_AT(10 * L + 1);
#pragma unroll 1
        for (int i = 0; i < 4; i++) {
          const uint32_t g0 = prod_acquire<2>(sbase, r);
          if (elect_one()) {
            mbar_expect_tx(bars + BAR_FULL + 8 * g0, 16384);
            tma_2d(sbase + g0 * GRAN, &m_wo, bars + BAR_FULL + 8 * g0, 64 * j, 128 * i);
          }
        }
        PSTOP_AT(10 * L + 2);
#pragma unroll 1
        for (int kb = 0; kb < 8; kb++) {
          const uint32_t g0 = prod_acquire<4>(sbase, r);
          if (elect_one()) {
            mbar_expect_tx(bars + BAR_FULL + 8 * g0, 32768);
            tma_4d(sbase + g0 * GRAN, &m_gu2, bars + BAR_FULL + 8 * g0, cb0, 64 * ((j + kb) & 7), 0, 0);
          }
        }
#pragma unroll 1
        for (int kb = 0; kb < 8; kb++) {
          const uint32_t g0 = prod_acquire<3>(sbase, r);
          if (elect_one()) {
            mbar_expect_tx(bars + BAR_FULL + 8 * g0, 24576);
            tma_4d(sbase + g0 * GRAN, &m_gu1, bars + BAR_FULL + 8 * g0, cb0 + 128, 64 * ((j + kb) & 7), 0, 0);
            tma_3d(sbase + g0 * GRAN + 16384, &m_guh, bars + BAR_FULL + 8 * g0, hb0, 64 * ((j + kb) & 7), 0);
          }
        }
        static_for<0, 16>([&](auto I) {
          constexpr int i = I.value, g0 = st_g0(ST_DN + i);
          prod_acquire_static<ST_DN + i>(sbase, L);
          if (elect_one()) {
            const uint32_t dst = sbase + g0 * GRAN, fb = bars + BAR_FULL + 8 * g0;
            const int n0 = 256 * b + 64 * dn_q(i);
            mbar_expect_tx(fb, 14336);
            if constexpr (dn_kh(i) == 0) {
              tma_2d(dst, &m_wd112, fb, n0, dn_par(i) ? cbp : cb0);
            } else {
              tma_2d(dst, &m_wd80, fb, n0, (dn_par(i) ? cbp : cb0) + 112);
              tma_2d(dst + 10240, &m_wd32, fb, n0, dn_par(i) ? hbp : hb0);
            }
          }
        });
        r.par ^= flip_mask(ST_DN, NSTAGE);
      }
    }
    __syncwarp();
    asm volatile("barrier.cluster.wait.acquire.aligned; // producer" ::: "memory");
    asm volatile("barrier.cluster.arrive.release.aligned;\nbarrier.cluster.wait.acquire.aligned; // producer" ::: "memory");
  } else {
    asm volatile("setmaxnreg.inc.sync.aligned.u32 232;");
    TS(0);
    TG(61);

    uint4 xraw[4];
    {
      float v[32];
#pragma unroll
      for (int i = 0; i < 16; i++) { v[2 * i] = bf_lo(xw[i]); v[2 * i + 1] = bf_hi(xw[i]); }
      owner_ln_publish(sbase, v, 0u, 1u, xraw);
      asm volatile("barrier.cluster.wait.acquire.aligned; // consumer" ::: "memory");
    }
    STOP_AT(0);
    TS(1);

#pragma unroll 1
    for (uint32_t L = 0; L < 2; L++) {
      const uint32_t tag = L ^ 1;
      {
        PHASE_VARS;
        uint4 qf[4], kf[4], vf[4], pp[4];
        const int blk = 16 * g + c;
        const int pb = blk > 0 ? blk - 1 : 0;
        const uint4* halo_src = g_arena + (pb & 15) * ARENA + AR_HALO + (((((L * 2 + (pb >> 4)) * 8 + j) * 2 + (w & 1)) * 4) * 32) + lane;
        {
          float acc[96];
          uint4 A[3][4];
          const uint4* xs = g_arena + c * ARENA + AR_XN + ((slab) * 32) * 32 + lane;
          bar_wg(1 + g);
          cold_delay(L);
          load_pk<4>(A[0], xs);
          ensure_pk<4>(A[0], xs, tag);
          TS(2 + 20 * L);
          load_pk<4>(A[1], xs + 128);
          static_for<0, 8>([&](auto I) {
            constexpr int kb = I.value;
            cons_acquire<kb>(sbase, L);
            wg_fence();
            static_for<0, 4>([&](auto K) { constexpr int k = K.value; wgmma_n192<kb == 0 && k == 0, 0>(acc, A[kb % 3][k], st_desc<kb, 2048, 8192, 1024, 1>(k)); });
            wg_commit();
            if constexpr (kb > 0) {
              wg_wait<1>();
              keep4(A[(kb + 2) % 3]);
              cons_release<kb - 1>(sbase, lane);
            }
            if constexpr (kb + 1 < 8) ensure_pk<4>(A[(kb + 1) % 3], xs + (kb + 1) * 128, tag);
            if constexpr (kb + 2 < 8) load_pk<4>(A[(kb + 2) % 3], xs + (kb + 2) * 128);
            if constexpr (kb == 2) {
              uint4* xr = g_arena + c * ARENA + AR_XRAW + ((j) * 32 + 4 * warp) * 32 + lane;
#pragma unroll
              for (int i = 0; i < 4; i++) st_ll(xr + i * 32, xraw[i]);
            }
          });
          wg_wait<0>();
          TS(3 + 20 * L);
          fence_acc(acc);
          keep4(A[1]);
          cons_release<7>(sbase, lane);
#pragma unroll
          for (int h = 0; h < 4; h++) {
            kf[h].y = pack2(acc[32 + 8 * h + 2], acc[32 + 8 * h + 3]); kf[h].w = pack2(acc[32 + 8 * h + 6], acc[32 + 8 * h + 7]);
            vf[h].y = movm(pack2(acc[64 + 8 * h + 2], acc[64 + 8 * h + 3])); vf[h].w = movm(pack2(acc[64 + 8 * h + 6], acc[64 + 8 * h + 7]));
            pp[h] = make_uint4(kf[h].y, kf[h].w, vf[h].y, vf[h].w);
          }
          if (w >= 2 && blk < 31) {
            uint4* hd = g_arena + c * ARENA + AR_HALO + (((((L * 2 + g) * 8 + j) * 2 + (w & 1)) * 4) * 32) + lane;
#pragma unroll
            for (int h = 0; h < 4; h++) { uint4 t = pp[h]; t.x |= 1u; st_ll(hd + h * 32, t); }
          }
#pragma unroll
          for (int h = 0; h < 4; h++) sts128(areg + (28 + h) * 2048 + t128 * 16, pp[h]);
#pragma unroll
          for (int h = 0; h < 4; h++) {
            kf[h].x = pack2(acc[32 + 8 * h], acc[32 + 8 * h + 1]); kf[h].z = pack2(acc[32 + 8 * h + 4], acc[32 + 8 * h + 5]);
            vf[h].x = movm(pack2(acc[64 + 8 * h], acc[64 + 8 * h + 1])); vf[h].z = movm(pack2(acc[64 + 8 * h + 4], acc[64 + 8 * h + 5]));
          }
#pragma unroll
          for (int h = 0; h < 4; h++) qf[h] = pack8(&acc[8 * h]);
        }
        bar_wg(1 + g);
        const bool first = (w < 2) && (blk == 0);
        if (w >= 2) {
#pragma unroll
          for (int h = 0; h < 4; h++) pp[h] = lds128(areg + (28 + h) * 2048 + (t128 - 64) * 16);
        }
        bar_wg(1 + g);
        if (w < 2 && blk > 0) {
          cold_delay(L);
          load_pk<4>(pp, halo_src);
          ensure_pk<4>(pp, halo_src, 1u);
          uint4* hz = const_cast<uint4*>(halo_src);
#pragma unroll
          for (int h = 0; h < 4; h++) st_ll(hz + h * 32, make_uint4(0, 0, 0, 0));
        }
        TS(4 + 20 * L);
        const bool n0 = 2 * qc <= qr, n1 = 2 * qc + 1 <= qr;
        const uint32_t msk = (n0 ? 0xffffu : 0u) | (n1 ? 0xffff0000u : 0u);
        const float sc = 0.25f * 1.4426950408889634f;
        const float NEG = -1e30f;
        uint4* od = g_arena + c * ARENA + AR_O + ((slab) * 32 + 4 * j) * 32 + lane;
        float l0[4], l1[4], h0[4], h1[4], ml[4], mh[4];
#pragma unroll
        for (int h = 0; h < 4; h++) {
          float sp[4], s0[4], s1[4];
          mma16816_z(sp, qf[h], pp[h].x, pp[h].y);
          mma16816_z(s0, qf[h], kf[h].x, kf[h].z);
          mma16816_z(s1, qf[h], kf[h].y, kf[h].w);
          if (first) { sp[0] = NEG; sp[1] = NEG; }
          l0[h] = n0 ? s0[0] : sp[0]; l1[h] = n1 ? s0[1] : sp[1];
          h0[h] = n0 ? s1[2] : s0[2]; h1[h] = n1 ? s1[3] : s0[3];
          ml[h] = fmaxf(l0[h], l1[h]); mh[h] = fmaxf(h0[h], h1[h]);
        }
#pragma unroll
        for (int h = 0; h < 4; h++) { ml[h] = fmaxf(ml[h], __shfl_xor_sync(0xffffffffu, ml[h], 1)); mh[h] = fmaxf(mh[h], __shfl_xor_sync(0xffffffffu, mh[h], 1)); }
#pragma unroll
        for (int h = 0; h < 4; h++) { ml[h] = fmaxf(ml[h], __shfl_xor_sync(0xffffffffu, ml[h], 2)); mh[h] = fmaxf(mh[h], __shfl_xor_sync(0xffffffffu, mh[h], 2)); }
        float sl[4], sh[4];
#pragma unroll
        for (int h = 0; h < 4; h++) {
          const float bl = -ml[h] * sc, bh = -mh[h] * sc;
          l0[h] = ex2(fmaf(l0[h], sc, bl)); l1[h] = ex2(fmaf(l1[h], sc, bl));
          h0[h] = ex2(fmaf(h0[h], sc, bh)); h1[h] = ex2(fmaf(h1[h], sc, bh));
          sl[h] = l0[h] + l1[h]; sh[h] = h0[h] + h1[h];
        }
#pragma unroll
        for (int h = 0; h < 4; h++) { sl[h] += __shfl_xor_sync(0xffffffffu, sl[h], 1); sh[h] += __shfl_xor_sync(0xffffffffu, sh[h], 1); }
#pragma unroll
        for (int h = 0; h < 4; h++) { sl[h] += __shfl_xor_sync(0xffffffffu, sl[h], 2); sh[h] += __shfl_xor_sync(0xffffffffu, sh[h], 2); }
#pragma unroll
        for (int h = 0; h < 4; h++) {
          const float il = rcp(sl[h]), ih = rcp(sh[h]);
          const uint32_t pl = pack2(l0[h] * il, l1[h] * il), ph = pack2(h0[h] * ih, h1[h] * ih);
          const uint4 P = make_uint4(pl & msk, ph & ~msk, 0u, ph & msk);
          float o0[4], o1[4];
          mma16816_z(o0, P, vf[h].x, vf[h].y);
          mma16816_z(o1, P, vf[h].z, vf[h].w);
          mma1688(o0, pl & ~msk, 0u, pp[h].z);
          mma1688(o1, pl & ~msk, 0u, pp[h].w);
          st_ll(od + h * 32, make_uint4(set_tag(pack2(o0[0], o0[1]), tag), pack2(o0[2], o0[3]), pack2(o1[0], o1[1]), pack2(o1[2], o1[3])));
        }
      }
      TS(5 + 20 * L);
      if (L == 0) { STOP_AT(1); } else { STOP_AT(11); }
      uint4 x1own[4];
      {
        PHASE_VARS;
        float acc[32];
        uint4 A[32], xr[4];
        const uint4* os = g_arena + c * ARENA + AR_O + ((slab) * 32) * 32 + lane;
        uint4* xp = g_arena + c * ARENA + AR_XRAW + ((slab) * 32 + 4 * j) * 32 + lane;
        load_pk<4>(xr, xp);
        cold_delay(L);
        load_pk<4>(A, os);
        ensure_pk<4>(A, os, tag);
        TS(6 + 20 * L);
        load_pk<28>(A + 4, os + 128);
        static_for<0, 8>([&](auto I) {
          constexpr int kb = I.value;
          if constexpr ((kb & 1) == 0) cons_acquire<ST_WO + kb / 2>(sbase, L);
          if constexpr (kb > 0) ensure_pk<4>(A + 4 * kb, os + kb * 128, tag);
          wg_fence();
          static_for<0, 4>([&](auto K) {
            constexpr int k = K.value;
            wgmma_n64<kb == 0 && k == 0, 0>(acc, A[4 * kb + k], st_desc<ST_WO + kb / 2, 2048, 8192, 1024, 1>(4 * (kb & 1) + k));
          });
          wg_commit();
          if constexpr ((kb & 1) == 0 && kb > 0) { wg_wait<1>(); cons_release<ST_WO + kb / 2 - 1>(sbase, lane); }
        });
        wg_wait<0>();
        TS(7 + 20 * L);
        fence_acc(acc);
#pragma unroll
        for (int k = 0; k < 32; k++) keep(A[k]);
        cons_release<ST_WO + 3>(sbase, lane);
        ensure_pk<4>(xr, xp, 1u);
#pragma unroll
        for (int i = 0; i < 4; i++) {
          acc[8 * i + 0] += bf_lo(xr[i].x); acc[8 * i + 1] += bf_hi(xr[i].x); acc[8 * i + 2] += bf_lo(xr[i].y); acc[8 * i + 3] += bf_hi(xr[i].y);
          acc[8 * i + 4] += bf_lo(xr[i].z); acc[8 * i + 5] += bf_hi(xr[i].z); acc[8 * i + 6] += bf_lo(xr[i].w); acc[8 * i + 7] += bf_hi(xr[i].w);
        }
        uint4 st = local_stats(acc);
        st.x = set_tag(st.x, tag);
        if (qc == 0) st_ll(g_arena + c * ARENA + AR_STATS + (slab * 8 + j) * 8 + qr, st);
#pragma unroll
        for (int i = 0; i < 4; i++) {
          x1own[i] = pack8(&acc[8 * i]);
          x1own[i].x = set_tag(x1own[i].x, 0u);
          st_ll(xp + i * 32, x1own[i]);
        }
      }
      TS(8 + 20 * L);
      if (L == 0) { STOP_AT(2); } else { STOP_AT(12); }
      uint4 hs[14];
      {
        PHASE_VARS;
        float acc[128];
        uint4 A[3][4];
        const uint4* xs = g_arena + c * ARENA + AR_XRAW + ((slab) * 32) * 32 + lane;
        const uint4* sp = g_arena + c * ARENA + AR_STATS + (slab * 8 + 2 * qc) * 8 + qr;
        const uint32_t sm = areg + t128 * 16;
        uint32_t rl2, rh2, bl2, bh2;
        float cl, ch;
        auto xsrc = [&](int p) { return xs + ((j + p) & 7) * 128; };
        {
          uint4 p[2];
#pragma unroll
          for (int k = 0; k < 4; k++) A[0][k] = x1own[k];
          cold_delay(L);
          p[0] = ld_ll(sp); p[1] = ld_ll(sp + 8);
          load_pk<4>(A[1], xsrc(1));
          for (uint32_t n = 0; !ok_pk<2>(p, tag) && n < SPIN_LIMIT; n++) { p[0] = ld_ll(sp); p[1] = ld_ll(sp + 8); }
          TS(9 + 20 * L);
          float ml, rl, mh, rh;
          combine_stats(p[0], p[1], ml, rl, mh, rh);
          rl2 = pack2(rl, rl); rh2 = pack2(rh, rh);
          const float rlb = bf_lo(rl2), rhb = bf_lo(rh2);
          bl2 = pack2(-ml * rlb, -ml * rlb); bh2 = pack2(-mh * rhb, -mh * rhb);
          cl = rl / rlb; cl *= cl; ch = rh / rhb; ch *= ch;
        }
        auto normalise = [&](uint4 (&xb)[4], int kb) {
#pragma unroll
          for (int k = 0; k < 4; k++) {
            xb[k].x = hfma2(xb[k].x, rl2, bl2); xb[k].y = hfma2(xb[k].y, rh2, bh2);
            xb[k].z = hfma2(xb[k].z, rl2, bl2); xb[k].w = hfma2(xb[k].w, rh2, bh2);
            sts128(sm + (kb * 4 + k) * 2048, xb[k]);
          }
        };
        normalise(A[0], 0);
        static_for<0, 8>([&](auto I) {
          constexpr int kb = I.value;
          cons_acquire<ST_G1 + kb>(sbase, L);
          wg_fence();
          static_for<0, 4>([&](auto K) { constexpr int k = K.value; wgmma_n256<kb == 0 && k == 0, 0>(acc, A[kb % 3][k], st_desc<ST_G1 + kb, 2048, 8192, 1024, 1>(k)); });
          wg_commit();
          if constexpr (kb > 0) {
            wg_wait<1>();
            keep4(A[(kb + 2) % 3]);
            cons_release<ST_G1 + kb - 1>(sbase, lane);
          }
          if constexpr (kb + 1 < 8) ensure_pk<4>(A[(kb + 1) % 3], xsrc(kb + 1), 0u);
          if constexpr (kb + 2 < 8) load_pk<4>(A[(kb + 2) % 3], xsrc(kb + 2));
          if constexpr (kb + 1 < 8) normalise(A[(kb + 1) % 3], kb + 1);
        });
        wg_wait<0>();
        TS(10 + 20 * L);
        fence_acc(acc);
        keep4(A[1]);
        cons_release<ST_G1 + 7>(sbase, lane);
        uint4 B[2][4];
#pragma unroll
        for (int k = 0; k < 4; k++) B[0][k] = lds128(sm + k * 2048);
#pragma unroll
        for (int s = 0; s < 8; s++) hs[s] = glu8<32>(&acc[64 * (s >> 2) + 8 * (s & 3)], cl, ch);
        float acc2[96];
        const uint32_t hdst = mapa(sm, cbit ^ 1);
        const uint32_t hbar1 = mapa(bars + BAR_HRECV + 16 * g, cbit ^ 1);
        if (t128 == 0) { mbar_expect_tx(bars + BAR_HRECV + 16 * g, 8 * 2048); mbar_expect_tx(bars + BAR_HRECV + 16 * g + 8, 6 * 2048); }
        static_for<0, 8>([&](auto I) {
          constexpr int kb = I.value;
          cons_acquire<ST_G2 + kb>(sbase, L);
          wg_fence();
          static_for<0, 4>([&](auto K) {
            constexpr int k = K.value;
            wgmma_n128<kb == 0 && k == 0, 0>(acc2, B[kb & 1][k], st_desc<ST_G2 + kb, 2048, 8192, 1024, 1>(k));
            wgmma_n64<kb == 0 && k == 0, 64>(acc2, B[kb & 1][k], st_desc<ST_G2 + kb, 1024, 4096, 512, 2>(k) + (16384 >> 4));
          });
          wg_commit();
          if constexpr (kb > 0) {
            wg_wait<1>();
            keep4(B[(kb + 1) & 1]);
            cons_release<ST_G2 + kb - 1>(sbase, lane);
          }
          if constexpr (kb + 1 < 8) {
#pragma unroll
            for (int k = 0; k < 4; k++) B[(kb + 1) & 1][k] = lds128(sm + ((kb + 1) * 4 + k) * 2048);
          }
          if constexpr (kb == 3) {
            __syncwarp();
            if (lane == 0) mbar_arrive_remote(mapa(bars + BAR_HREADY + 8 * g, cbit ^ 1));
          }
          if constexpr (kb >= 4) {
            if constexpr (kb == 4) mbar_wait(bars + BAR_HREADY + 8 * g, L);
            st_async128(hdst + (2 * kb - 8) * 2048, hs[2 * kb - 8], hbar1);
            st_async128(hdst + (2 * kb - 7) * 2048, hs[2 * kb - 7], hbar1);
          }
        });
        wg_wait<0>();
        TS(11 + 20 * L);
        fence_acc(acc2);
        keep4(B[1]);
        cons_release<ST_G2 + 7>(sbase, lane);
#pragma unroll
        for (int s = 0; s < 4; s++) hs[8 + s] = glu8<32>(&acc2[8 * s], cl, ch);
#pragma unroll
        for (int s = 0; s < 2; s++) hs[12 + s] = glu8<16>(&acc2[64 + 8 * s], cl, ch);
      }
      {
        PHASE_VARS;
        TS(12 + 20 * L);
        const uint32_t hdst = mapa(areg + t128 * 16, cbit ^ 1);
        const uint32_t hbar2 = mapa(bars + BAR_HRECV + 16 * g + 8, cbit ^ 1);
        uint4* pd = g_arena + c * ARENA + AR_PART + (((slab * 2 + cbit) * 4 + ca) * 16) * 32 + lane;
        const uint4* ps = g_arena + c * ARENA + AR_PART + (((j * 2 + g) * 4) * 16 + 4 * w) * 32 + lane;
        auto fetch_partials = [&]() {
#pragma unroll
          for (int src = 0; src < 4; src++)
#pragma unroll
            for (int k = 0; k < 4; k++) cp_async16(areg + t128 * 16 + (14 + 4 * src + k) * 2048, ps + src * (16 * 32) + k * 32);
        };
        uint4 hb[7];
        float a0[32], a1[32], a2[32], a3[32];
        auto publish = [&](float (&a)[32], int q, int s0, int s1) {
#pragma unroll
          for (int s = s0; s < s1; s++) {
            uint4 o = pack8(&a[8 * s]);
            o.x = set_tag(o.x, tag);
            st_ll(pd + (4 * q + s) * 32, o);
          }
        };
        static_for<0, 16>([&](auto I) {
          constexpr int i = I.value, q = dn_q(i), par = dn_par(i), kh = dn_kh(i);
          auto mm = [&](auto K) {
            constexpr int k = decltype(K)::value;
            constexpr bool init = (k == 0 && par == 0 && kh == 0);
            constexpr uint64_t db = st_desc<ST_DN + i, 2048, 8192, 1024, 1>(k);
            if constexpr (q == 0) { if constexpr (par) wgmma_n64<init, 0>(a0, hb[k], db); else wgmma_n64<init, 0>(a0, hs[7 * kh + k], db); }
            if constexpr (q == 1) { if constexpr (par) wgmma_n64<init, 0>(a1, hb[k], db); else wgmma_n64<init, 0>(a1, hs[7 * kh + k], db); }
            if constexpr (q == 2) { if constexpr (par) wgmma_n64<init, 0>(a2, hb[k], db); else wgmma_n64<init, 0>(a2, hs[7 * kh + k], db); }
            if constexpr (q == 3) { if constexpr (par) wgmma_n64<init, 0>(a3, hb[k], db); else wgmma_n64<init, 0>(a3, hs[7 * kh + k], db); }
          };
          cons_acquire<ST_DN + i>(sbase, L);
          wg_fence();
          mm(IC<0>{}); mm(IC<1>{}); mm(IC<2>{}); mm(IC<3>{}); mm(IC<4>{}); mm(IC<5>{}); mm(IC<6>{});
          wg_commit();
          if constexpr (i > 0) { wg_wait<1>(); cons_release<ST_DN + i - 1>(sbase, lane); }
          if constexpr (i < 3) {
            st_async128(hdst + (8 + 2 * i) * 2048, hs[8 + 2 * i], hbar2);
            st_async128(hdst + (9 + 2 * i) * 2048, hs[9 + 2 * i], hbar2);
          }
          constexpr int n = i + 1;
          if constexpr (n < 16 && dn_par(n) && n != 4 && n != 7) {
            if constexpr (n == 2) { mbar_wait(bars + BAR_HRECV + 16 * g, L); TS(13 + 20 * L); }
            if constexpr (n == 6) { mbar_wait(bars + BAR_HRECV + 16 * g + 8, L); TS(14 + 20 * L); }
#pragma unroll
            for (int k = 0; k < 7; k++) { if constexpr (n != 2) keep(hb[k]); hb[k] = lds128(areg + t128 * 16 + (7 * dn_kh(n) + k) * 2048); }
          }
          if constexpr (i == 7) { fence_acc(a0); publish(a0, 0, 0, 4); }
          if constexpr (i == 8) { fence_acc(a1); publish(a1, 1, 0, 2); }
          if constexpr (i == 9) publish(a1, 1, 2, 4);
          if constexpr (i == 12) { fence_acc(a2); publish(a2, 2, 0, 2); }
          if constexpr (i == 13) publish(a2, 2, 2, 4);
          if constexpr (i == 10) { if (w == 0) fetch_partials(); }
          if constexpr (i == 12) { if (w == 1) fetch_partials(); }
        });
        wg_wait<0>();
        TS(15 + 20 * L);
        fence_acc(a3);
#pragma unroll
        for (int k = 0; k < 7; k++) { keep(hb[k]); keep(hs[7 + k]); }
        cons_release<NSTAGE - 1>(sbase, lane);
        publish(a3, 3, 0, 4);
        if (w >= 2) { cold_delay(L); fetch_partials(); }
      }
      {
        PHASE_VARS;
        const uint4* xq = g_arena + c * ARENA + AR_XRAW + ((j) * 32 + 4 * warp) * 32 + lane;
        const uint4* ps = g_arena + c * ARENA + AR_PART + (((j * 2 + g) * 4) * 16 + 4 * w) * 32 + lane;
        uint4 xr[4], P[4][4];
        float v[32];
        load_pk<4>(xr, xq);
        cp_wait_all();
#pragma unroll
        for (int k = 0; k < 16; k++) P[k >> 2][k & 3] = lds128(areg + t128 * 16 + (14 + k) * 2048);
        for (uint32_t n = 0; !ok_pk<16>(&P[0][0], tag) && n < SPIN_LIMIT; n++) {
#pragma unroll
          for (int src = 0; src < 4; src++) load_pk<4>(P[src], ps + src * (16 * 32));
        }
        TS(16 + 20 * L);
        ensure_pk<4>(xr, xq, 0u);
#pragma unroll
        for (int i = 0; i < 4; i++) {
          v[8 * i + 0] = bf_lo(xr[i].x); v[8 * i + 1] = bf_hi(xr[i].x); v[8 * i + 2] = bf_lo(xr[i].y); v[8 * i + 3] = bf_hi(xr[i].y);
          v[8 * i + 4] = bf_lo(xr[i].z); v[8 * i + 5] = bf_hi(xr[i].z); v[8 * i + 6] = bf_lo(xr[i].w); v[8 * i + 7] = bf_hi(xr[i].w);
          float d[8] = {0, 0, 0, 0, 0, 0, 0, 0};
#pragma unroll
          for (int src = 0; src < 4; src++) {
            const uint4 p = P[src][i];
            d[0] += bf_lo(p.x); d[1] += bf_hi(p.x); d[2] += bf_lo(p.y); d[3] += bf_hi(p.y);
            d[4] += bf_lo(p.z); d[5] += bf_hi(p.z); d[6] += bf_lo(p.w); d[7] += bf_hi(p.w);
          }
#pragma unroll
          for (int k = 0; k < 8; k++) v[8 * i + k] += d[k];
        }
        if (L == 0) {
          owner_ln_publish(sbase, v, 1u, 0u, xraw);
        } else {
#pragma unroll
          for (int i = 0; i < 4; i++) xraw[i] = make_uint4(0, 0, 0, 0);
          uint32_t* op = reinterpret_cast<uint32_t*>(out + (size_t)(slab_row0(c, j >> 2, j & 3) + 2 * qr) * 512 + warp * 64 + qc * 2);
#pragma unroll
          for (int i = 0; i < 4; i++) {
            op[i * 8] = pack2(v[8 * i], v[8 * i + 1]);
            op[16 * 256 + i * 8] = pack2(v[8 * i + 2], v[8 * i + 3]);
            op[i * 8 + 4] = pack2(v[8 * i + 4], v[8 * i + 5]);
            op[16 * 256 + i * 8 + 4] = pack2(v[8 * i + 6], v[8 * i + 7]);
          }
        }
      }
      TS(17 + 20 * L);
      if (L == 0) { STOP_AT(3); }
    }
    TG(62);
    asm volatile("barrier.cluster.arrive.release.aligned;\nbarrier.cluster.wait.acquire.aligned; // consumer" ::: "memory");
    TG(63);
  }
}

typedef CUresult (*EncodeFn)(CUtensorMap*, CUtensorMapDataType, cuuint32_t, void*, const cuuint64_t*, const cuuint64_t*,
                             const cuuint32_t*, const cuuint32_t*, CUtensorMapInterleave, CUtensorMapSwizzle,
                             CUtensorMapL2promotion, CUtensorMapFloatOOBfill);

void encode(EncodeFn fn, CUtensorMap* m, int rank, const void* base, const cuuint64_t* dims, const cuuint64_t* strides,
            const cuuint32_t* box, CUtensorMapSwizzle sw) {
  cuuint32_t es[5] = {1, 1, 1, 1, 1};
  fn(m, CU_TENSOR_MAP_DATA_TYPE_BFLOAT16, (cuuint32_t)rank, const_cast<void*>(base), dims, strides, box, es,
     CU_TENSOR_MAP_INTERLEAVE_NONE, sw, CU_TENSOR_MAP_L2_PROMOTION_L2_128B, CU_TENSOR_MAP_FLOAT_OOB_FILL_NONE);
}

}

extern "C" void kernel_launch(void* const* d_in, const int* in_sizes, int n_in, void* d_out, int out_size) {
  (void)in_sizes; (void)n_in; (void)out_size;
  const __nv_bfloat16* x = (const __nv_bfloat16*)d_in[0];
  const char* wqkv = (const char*)d_in[1];
  const char* wo = (const char*)d_in[2];
  const char* wg = (const char*)d_in[4];
  const char* wu = (const char*)d_in[5];
  const char* wd = (const char*)d_in[6];

  static EncodeFn fn = nullptr;
  if (!fn) {
    void* p = nullptr;
    cudaDriverEntryPointQueryResult st;
    cudaGetDriverEntryPoint("cuTensorMapEncodeTiled", &p, cudaEnableDefault, &st);
    fn = (EncodeFn)p;
    cudaFuncSetAttribute(fused_kernel, cudaFuncAttributeMaxDynamicSharedMemorySize, SMEM_BYTES);
  }
  CUtensorMap m_qkv, m_wo, m_gu2, m_gu1, m_guh, m_wd112, m_wd80, m_wd32;
  {
    cuuint64_t dims[3] = {512, 512, 3}, str[2] = {3072, 1024};
    cuuint32_t box[3] = {64, 64, 3};
    encode(fn, &m_qkv, 3, wqkv, dims, str, box, CU_TENSOR_MAP_SWIZZLE_128B);
  }
  {
    cuuint64_t dims[2] = {512, 512}, str[1] = {1024};
    cuuint32_t box[2] = {64, 128};
    encode(fn, &m_wo, 2, wo, dims, str, box, CU_TENSOR_MAP_SWIZZLE_128B);
  }
  {
    const char* lo = wg < wu ? wg : wu;
    cuuint64_t diff = (cuuint64_t)(wg < wu ? wu - wg : wg - wu);
    cuuint64_t dims[4] = {1792, 512, 2, 2}, str[3] = {3584, diff, 128};
    cuuint32_t box2[4] = {64, 64, 2, 2}, box1[4] = {64, 64, 2, 1}, boxh[3] = {32, 64, 2};
    encode(fn, &m_gu2, 4, lo, dims, str, box2, CU_TENSOR_MAP_SWIZZLE_128B);
    encode(fn, &m_gu1, 4, lo, dims, str, box1, CU_TENSOR_MAP_SWIZZLE_128B);
    encode(fn, &m_guh, 3, lo, dims, str, boxh, CU_TENSOR_MAP_SWIZZLE_64B);
  }
  {
    cuuint64_t dims[2] = {512, 1792}, str[1] = {1024};
    cuuint32_t b112[2] = {64, 112}, b80[2] = {64, 80}, b32[2] = {64, 32};
    encode(fn, &m_wd112, 2, wd, dims, str, b112, CU_TENSOR_MAP_SWIZZLE_128B);
    encode(fn, &m_wd80, 2, wd, dims, str, b80, CU_TENSOR_MAP_SWIZZLE_128B);
    encode(fn, &m_wd32, 2, wd, dims, str, b32, CU_TENSOR_MAP_SWIZZLE_128B);
  }
  cudaLaunchConfig_t cfg = {};
  cfg.gridDim = dim3(128);
  cfg.blockDim = dim3(NTHREADS);
  cfg.dynamicSmemBytes = SMEM_BYTES;
  cfg.stream = cudaStreamPerThread;
  cudaLaunchAttribute at[1];
  at[0].id = cudaLaunchAttributeClusterDimension;
  at[0].val.clusterDim.x = 2; at[0].val.clusterDim.y = 1; at[0].val.clusterDim.z = 1;
  cfg.attrs = at; cfg.numAttrs = 1;
  cudaLaunchKernelEx(&cfg, fused_kernel, m_qkv, m_wo, m_gu2, m_gu1, m_guh, m_wd112, m_wd80, m_wd32, x, (__nv_bfloat16*)d_out
  );
}
```

```cpp
#include <cuda_runtime.h>
#include <cuda_bf16.h>
#include <cuda.h>
#include <stdint.h>

namespace {

constexpr int NTHREADS = 384;
constexpr int GRAN = 8192;
constexpr int NGRAN = 12;
constexpr int SM_AREG = NGRAN * GRAN;
constexpr int SM_MISC = SM_AREG + 131072;
constexpr int SM_TSTAT = SM_MISC + 256;
constexpr int SMEM_BYTES = SM_TSTAT + 1024;
constexpr int BAR_FULL = 0, BAR_EMPTY = 96, BAR_HRECV = 192, BAR_HREADY = 224;

constexpr int AR_XN = 0, AR_XRAW = 8192, AR_O = 16384, AR_STATS = 24576, AR_HALO = 25088, AR_PART = 33280, ARENA = 66048;
__device__ __align__(1024) uint4 g_arena[16 * ARENA];

#define TS(n)
#define TG(n)
#define OPAQUE(x) asm volatile("" : "+r"(x))
#define PHASE_VARS                                                                                   \
  int tid_ = threadIdx.x, bid_ = blockIdx.x;                                                         \
  OPAQUE(tid_); OPAQUE(bid_);                                                                        \
  const int lane = tid_ & 31, warp = tid_ >> 5, g = warp >> 2, w = warp & 3, t128 = tid_ & 127;      \
  const int qr = lane >> 2, qc = lane & 3, slab = warp;                                              \
  const int c = bid_ >> 3, j = bid_ & 7, ca = j >> 1, cbit = j & 1;                                  \
  const uint32_t areg = sbase + SM_AREG + g * 65536;                                                 \
  (void)g; (void)j; (void)w; (void)t128; (void)qr; (void)qc; (void)slab; (void)c; (void)ca; (void)cbit; (void)areg; (void)lane
#define STOP_AT(n)
#define PSTOP_AT(n)

__device__ __forceinline__ uint32_t smem_u32(const void* p) { return (uint32_t)__cvta_generic_to_shared(p); }
__device__ __forceinline__ void mbar_init(uint32_t bar, uint32_t cnt) {
  asm volatile("mbarrier.init.shared::cta.b64 [%0], %1;" ::"r"(bar), "r"(cnt) : "memory");
}
__device__ __forceinline__ void mbar_expect_tx(uint32_t bar, uint32_t bytes) {
  asm volatile("mbarrier.arrive.expect_tx.shared::cta.b64 _, [%0], %1;" ::"r"(bar), "r"(bytes) : "memory");
}
__device__ __forceinline__ void mbar_arrive(uint32_t bar) {
  asm volatile("mbarrier.arrive.shared::cta.b64 _, [%0];" ::"r"(bar) : "memory");
}
__device__ __forceinline__ void mbar_arrive_remote(uint32_t cluster_addr) {
  asm volatile("mbarrier.arrive.relaxed.cluster.shared::cluster.b64 _, [%0];" ::"r"(cluster_addr) : "memory");
}
__device__ __forceinline__ bool mbar_try(uint32_t bar, uint32_t parity) {
  uint32_t ok;
  asm volatile("{\n.reg .pred p;\nmbarrier.try_wait.parity.shared::cta.b64 p, [%1], %2;\nselp.u32 %0, 1, 0, p;\n}"
               : "=r"(ok) : "r"(bar), "r"(parity) : "memory");
  return ok != 0;
}
constexpr uint32_t SPIN_LIMIT = 1u << 16;
constexpr uint32_t SMEM_ORIGIN = 1024;
__device__ __forceinline__ void mbar_wait(uint32_t bar, uint32_t parity) {
  for (uint32_t n = 0; !mbar_try(bar, parity) && n < SPIN_LIMIT; n++) {}
}
__device__ __forceinline__ uint32_t mapa(uint32_t addr, uint32_t rank) {
  uint32_t r;
  asm volatile("mapa.shared::cluster.u32 %0, %1, %2;" : "=r"(r) : "r"(addr), "r"(rank));
  return r;
}

__device__ __forceinline__ void tma_2d(uint32_t dst, const CUtensorMap* m, uint32_t bar, int c0, int c1) {
  asm volatile("cp.async.bulk.tensor.2d.shared::cluster.global.mbarrier::complete_tx::bytes [%0], [%1, {%3, %4}], [%2];"
               ::"r"(dst), "l"(m), "r"(bar), "r"(c0), "r"(c1) : "memory");
}
__device__ __forceinline__ void tma_3d(uint32_t dst, const CUtensorMap* m, uint32_t bar, int c0, int c1, int c2) {
  asm volatile("cp.async.bulk.tensor.3d.shared::cluster.global.mbarrier::complete_tx::bytes [%0], [%1, {%3, %4, %5}], [%2];"
               ::"r"(dst), "l"(m), "r"(bar), "r"(c0), "r"(c1), "r"(c2) : "memory");
}
__device__ __forceinline__ void tma_4d(uint32_t dst, const CUtensorMap* m, uint32_t bar, int c0, int c1, int c2, int c3) {
  asm volatile("cp.async.bulk.tensor.4d.shared::cluster.global.mbarrier::complete_tx::bytes [%0], [%1, {%3, %4, %5, %6}], [%2];"
               ::"r"(dst), "l"(m), "r"(bar), "r"(c0), "r"(c1), "r"(c2), "r"(c3) : "memory");
}

__device__ __forceinline__ uint4 ld_ll(const uint4* p) {
  uint4 v;
  asm volatile("ld.relaxed.gpu.global.v4.u32 {%0,%1,%2,%3}, [%4];" : "=r"(v.x), "=r"(v.y), "=r"(v.z), "=r"(v.w) : "l"(p) : "memory");
  return v;
}
__device__ __forceinline__ uint4 ld_try(const uint4* p) {
  uint4 v;
  asm volatile("ld.global.cg.v4.u32 {%0,%1,%2,%3}, [%4];" : "=r"(v.x), "=r"(v.y), "=r"(v.z), "=r"(v.w) : "l"(p) : "memory");
  return v;
}
__device__ __forceinline__ void st_ll(uint4* p, uint4 v) {
  asm volatile("st.relaxed.gpu.global.v4.u32 [%0], {%1,%2,%3,%4};" ::"l"(p), "r"(v.x), "r"(v.y), "r"(v.z), "r"(v.w) : "memory");
}
__device__ __forceinline__ uint4 lds128(uint32_t a) {
  uint4 v;
  asm volatile("ld.shared.v4.u32 {%0,%1,%2,%3}, [%4];" : "=r"(v.x), "=r"(v.y), "=r"(v.z), "=r"(v.w) : "r"(a) : "memory");
  return v;
}
__device__ __forceinline__ void sts128(uint32_t a, uint4 v) {
  asm volatile("st.shared.v4.u32 [%0], {%1,%2,%3,%4};" ::"r"(a), "r"(v.x), "r"(v.y), "r"(v.z), "r"(v.w) : "memory");
}
__device__ __forceinline__ void st_async128(uint32_t cluster_addr, uint4 v, uint32_t cluster_bar) {
  asm volatile("st.async.weak.shared::cluster.mbarrier::complete_tx::bytes.v4.b32 [%0], {%1,%2,%3,%4}, [%5];"
               ::"r"(cluster_addr), "r"(v.x), "r"(v.y), "r"(v.z), "r"(v.w), "r"(cluster_bar) : "memory");
}
__device__ __forceinline__ uint32_t pack2(float lo, float hi) {
  uint32_t r;
  asm("cvt.rn.bf16x2.f32 %0, %1, %2;" : "=r"(r) : "f"(hi), "f"(lo));
  return r;
}
__device__ __forceinline__ float bf_lo(uint32_t w) { return __uint_as_float(w << 16); }
__device__ __forceinline__ float bf_hi(uint32_t w) { return __uint_as_float(w & 0xffff0000u); }
__device__ __forceinline__ uint32_t set_tag(uint32_t w, uint32_t tag) { return (w & ~1u) | tag; }
__device__ __forceinline__ uint32_t movm(uint32_t a) {
  uint32_t d;
  asm("movmatrix.sync.aligned.m8n8.trans.b16 %0, %1;" : "=r"(d) : "r"(a));
  return d;
}
__device__ __forceinline__ void mma1688(float (&d)[4], uint32_t a0, uint32_t a1, uint32_t b0) {
  asm("mma.sync.aligned.m16n8k8.row.col.f32.bf16.bf16.f32 {%0,%1,%2,%3}, {%4,%5}, {%6}, {%0,%1,%2,%3};"
      : "+f"(d[0]), "+f"(d[1]), "+f"(d[2]), "+f"(d[3])
      : "r"(a0), "r"(a1), "r"(b0));
}
__device__ __forceinline__ void mma16816_z(float (&d)[4], const uint4& a, uint32_t b0, uint32_t b1) {
  asm("mma.sync.aligned.m16n8k16.row.col.f32.bf16.bf16.f32 {%0,%1,%2,%3}, {%4,%5,%6,%7}, {%8,%9}, {%10,%10,%10,%10};"
      : "=f"(d[0]), "=f"(d[1]), "=f"(d[2]), "=f"(d[3])
      : "r"(a.x), "r"(a.y), "r"(a.z), "r"(a.w), "r"(b0), "r"(b1), "f"(0.f));
}
__device__ __forceinline__ float ex2(float x) {
  float y;
  asm("ex2.approx.ftz.f32 %0, %1;" : "=f"(y) : "f"(x));
  return y;
}
__device__ __forceinline__ float rcp(float x) {
  float y;
  asm("rcp.approx.ftz.f32 %0, %1;" : "=f"(y) : "f"(x));
  return y;
}
__device__ __forceinline__ void cp_async16(uint32_t dst, const void* src) {
  asm volatile("cp.async.cg.shared.global [%0], [%1], 16;" ::"r"(dst), "l"(src) : "memory");
}
__device__ __forceinline__ void cp_wait_all() { asm volatile("cp.async.wait_all;" ::: "memory"); }
template <int N> __device__ __forceinline__ void cp_wait() { asm volatile("cp.async.wait_group %0;" ::"n"(N) : "memory"); }
__device__ __forceinline__ void bar_wg(int id) { asm volatile("bar.sync %0, 128;" ::"r"(id) : "memory"); }
#define COLD_DELAY 900
__device__ __forceinline__ void cold_delay(uint32_t L) {
  if (L == 0) {
    const uint32_t t0 = (uint32_t)clock();
    while ((uint32_t)clock() - t0 < COLD_DELAY) {}
  }
}
__device__ __forceinline__ void wg_fence() { asm volatile("wgmma.fence.sync.aligned;" ::: "memory"); }
__device__ __forceinline__ void wg_commit() { asm volatile("wgmma.commit_group.sync.aligned;" ::: "memory"); }
template <int N> __device__ __forceinline__ void wg_wait() { asm volatile("wgmma.wait_group.sync.aligned %0;" ::"n"(N) : "memory"); }
__device__ __forceinline__ void keep(const uint4& a) { asm volatile("" ::"r"(a.x), "r"(a.y), "r"(a.z), "r"(a.w) : "memory"); }
template <int T> __device__ __forceinline__ void zero_acc(float (&d)[T]) {
#pragma unroll
  for (int i = 0; i < T; i++) d[i] = 0.f;
}
template <int T> __device__ __forceinline__ void fence_acc(float (&d)[T]) {
#pragma unroll
  for (int i = 0; i < T; i++) asm volatile("" : "+f"(d[i])::"memory");
}

template <int O, int T> __device__ __forceinline__ void wgmma_rs_n64(float (&d)[T], const uint4& a, uint64_t db) {
  asm volatile("{\n.reg .pred p;\nsetp.ne.b32 p, 1, 0;\n"
    "wgmma.mma_async.sync.aligned.m64n64k16.f32.bf16.bf16 "
    "{%0, %1, %2, %3, %4, %5, %6, %7, %8, %9, %10, %11, %12, %13, %14, %15, "
    "%16, %17, %18, %19, %20, %21, %22, %23, %24, %25, %26, %27, %28, %29, %30, %31}, "
    "{%32, %33, %34, %35}, %36, p, 1, 1, 1;\n}\n"
    : "+f"(d[O + 0]), "+f"(d[O + 1]), "+f"(d[O + 2]), "+f"(d[O + 3]), "+f"(d[O + 4]), "+f"(d[O + 5]), "+f"(d[O + 6]), "+f"(d[O + 7]),
      "+f"(d[O + 8]), "+f"(d[O + 9]), "+f"(d[O + 10]), "+f"(d[O + 11]), "+f"(d[O + 12]), "+f"(d[O + 13]), "+f"(d[O + 14]), "+f"(d[O + 15]),
      "+f"(d[O + 16]), "+f"(d[O + 17]), "+f"(d[O + 18]), "+f"(d[O + 19]), "+f"(d[O + 20]), "+f"(d[O + 21]), "+f"(d[O + 22]), "+f"(d[O + 23]),
      "+f"(d[O + 24]), "+f"(d[O + 25]), "+f"(d[O + 26]), "+f"(d[O + 27]), "+f"(d[O + 28]), "+f"(d[O + 29]), "+f"(d[O + 30]), "+f"(d[O + 31])
    : "r"(a.x), "r"(a.y), "r"(a.z), "r"(a.w), "l"(db));
}
template <int O, int T> __device__ __forceinline__ void wgmma_rs_n64_init(float (&d)[T], const uint4& a, uint64_t db) {
  asm volatile("{\n.reg .pred p;\nsetp.ne.b32 p, 0, 0;\n"
    "wgmma.mma_async.sync.aligned.m64n64k16.f32.bf16.bf16 "
    "{%0, %1, %2, %3, %4, %5, %6, %7, %8, %9, %10, %11, %12, %13, %14, %15, "
    "%16, %17, %18, %19, %20, %21, %22, %23, %24, %25, %26, %27, %28, %29, %30, %31}, "
    "{%32, %33, %34, %35}, %36, p, 1, 1, 1;\n}\n"
    : "=f"(d[O + 0]), "=f"(d[O + 1]), "=f"(d[O + 2]), "=f"(d[O + 3]), "=f"(d[O + 4]), "=f"(d[O + 5]), "=f"(d[O + 6]), "=f"(d[O + 7]),
      "=f"(d[O + 8]), "=f"(d[O + 9]), "=f"(d[O + 10]), "=f"(d[O + 11]), "=f"(d[O + 12]), "=f"(d[O + 13]), "=f"(d[O + 14]), "=f"(d[O + 15]),
      "=f"(d[O + 16]), "=f"(d[O + 17]), "=f"(d[O + 18]), "=f"(d[O + 19]), "=f"(d[O + 20]), "=f"(d[O + 21]), "=f"(d[O + 22]), "=f"(d[O + 23]),
      "=f"(d[O + 24]), "=f"(d[O + 25]), "=f"(d[O + 26]), "=f"(d[O + 27]), "=f"(d[O + 28]), "=f"(d[O + 29]), "=f"(d[O + 30]), "=f"(d[O + 31])
    : "r"(a.x), "r"(a.y), "r"(a.z), "r"(a.w), "l"(db));
}
template <bool INIT, int O, int T> __device__ __forceinline__ void wgmma_n64(float (&d)[T], const uint4& a, uint64_t db) {
  if constexpr (INIT) wgmma_rs_n64_init<O>(d, a, db); else wgmma_rs_n64<O>(d, a, db);
}
template <int O, int T> __device__ __forceinline__ void wgmma_rs_n128(float (&d)[T], const uint4& a, uint64_t db) {
  asm volatile("{\n.reg .pred p;\nsetp.ne.b32 p, 1, 0;\n"
    "wgmma.mma_async.sync.aligned.m64n128k16.f32.bf16.bf16 "
    "{%0, %1, %2, %3, %4, %5, %6, %7, %8, %9, %10, %11, %12, %13, %14, %15, "
    "%16, %17, %18, %19, %20, %21, %22, %23, %24, %25, %26, %27, %28, %29, %30, %31, "
    "%32, %33, %34, %35, %36, %37, %38, %39, %40, %41, %42, %43, %44, %45, %46, %47, "
    "%48, %49, %50, %51, %52, %53, %54, %55, %56, %57, %58, %59, %60, %61, %62, %63}, "
    "{%64, %65, %66, %67}, %68, p, 1, 1, 1;\n}\n"
    : "+f"(d[O + 0]), "+f"(d[O + 1]), "+f"(d[O + 2]), "+f"(d[O + 3]), "+f"(d[O + 4]), "+f"(d[O + 5]), "+f"(d[O + 6]), "+f"(d[O + 7]),
      "+f"(d[O + 8]), "+f"(d[O + 9]), "+f"(d[O + 10]), "+f"(d[O + 11]), "+f"(d[O + 12]), "+f"(d[O + 13]), "+f"(d[O + 14]), "+f"(d[O + 15]),
      "+f"(d[O + 16]), "+f"(d[O + 17]), "+f"(d[O + 18]), "+f"(d[O + 19]), "+f"(d[O + 20]), "+f"(d[O + 21]), "+f"(d[O + 22]), "+f"(d[O + 23]),
      "+f"(d[O + 24]), "+f"(d[O + 25]), "+f"(d[O + 26]), "+f"(d[O + 27]), "+f"(d[O + 28]), "+f"(d[O + 29]), "+f"(d[O + 30]), "+f"(d[O + 31]),
      "+f"(d[O + 32]), "+f"(d[O + 33]), "+f"(d[O + 34]), "+f"(d[O + 35]), "+f"(d[O + 36]), "+f"(d[O + 37]), "+f"(d[O + 38]), "+f"(d[O + 39]),
      "+f"(d[O + 40]), "+f"(d[O + 41]), "+f"(d[O + 42]), "+f"(d[O + 43]), "+f"(d[O + 44]), "+f"(d[O + 45]), "+f"(d[O + 46]), "+f"(d[O + 47]),
      "+f"(d[O + 48]), "+f"(d[O + 49]), "+f"(d[O + 50]), "+f"(d[O + 51]), "+f"(d[O + 52]), "+f"(d[O + 53]), "+f"(d[O + 54]), "+f"(d[O + 55]),
      "+f"(d[O + 56]), "+f"(d[O + 57]), "+f"(d[O + 58]), "+f"(d[O + 59]), "+f"(d[O + 60]), "+f"(d[O + 61]), "+f"(d[O + 62]), "+f"(d[O + 63])
    : "r"(a.x), "r"(a.y), "r"(a.z), "r"(a.w), "l"(db));
}
template <int O, int T> __device__ __forceinline__ void wgmma_rs_n128_init(float (&d)[T], const uint4& a, uint64_t db) {
  asm volatile("{\n.reg .pred p;\nsetp.ne.b32 p, 0, 0;\n"
    "wgmma.mma_async.sync.aligned.m64n128k16.f32.bf16.bf16 "
    "{%0, %1, %2, %3, %4, %5, %6, %7, %8, %9, %10, %11, %12, %13, %14, %15, "
    "%16, %17, %18, %19, %20, %21, %22, %23, %24, %25, %26, %27, %28, %29, %30, %31, "
    "%32, %33, %34, %35, %36, %37, %38, %39, %40, %41, %42, %43, %44, %45, %46, %47, "
    "%48, %49, %50, %51, %52, %53, %54, %55, %56, %57, %58, %59, %60, %61, %62, %63}, "
    "{%64, %65, %66, %67}, %68, p, 1, 1, 1;\n}\n"
    : "=f"(d[O + 0]), "=f"(d[O + 1]), "=f"(d[O + 2]), "=f"(d[O + 3]), "=f"(d[O + 4]), "=f"(d[O + 5]), "=f"(d[O + 6]), "=f"(d[O + 7]),
      "=f"(d[O + 8]), "=f"(d[O + 9]), "=f"(d[O + 10]), "=f"(d[O + 11]), "=f"(d[O + 12]), "=f"(d[O + 13]), "=f"(d[O + 14]), "=f"(d[O + 15]),
      "=f"(d[O + 16]), "=f"(d[O + 17]), "=f"(d[O + 18]), "=f"(d[O + 19]), "=f"(d[O + 20]), "=f"(d[O + 21]), "=f"(d[O + 22]), "=f"(d[O + 23]),
      "=f"(d[O + 24]), "=f"(d[O + 25]), "=f"(d[O + 26]), "=f"(d[O + 27]), "=f"(d[O + 28]), "=f"(d[O + 29]), "=f"(d[O + 30]), "=f"(d[O + 31]),
      "=f"(d[O + 32]), "=f"(d[O + 33]), "=f"(d[O + 34]), "=f"(d[O + 35]), "=f"(d[O + 36]), "=f"(d[O + 37]), "=f"(d[O + 38]), "=f"(d[O + 39]),
      "=f"(d[O + 40]), "=f"(d[O + 41]), "=f"(d[O + 42]), "=f"(d[O + 43]), "=f"(d[O + 44]), "=f"(d[O + 45]), "=f"(d[O + 46]), "=f"(d[O + 47]),
      "=f"(d[O + 48]), "=f"(d[O + 49]), "=f"(d[O + 50]), "=f"(d[O + 51]), "=f"(d[O + 52]), "=f"(d[O + 53]), "=f"(d[O + 54]), "=f"(d[O + 55]),
      "=f"(d[O + 56]), "=f"(d[O + 57]), "=f"(d[O + 58]), "=f"(d[O + 59]), "=f"(d[O + 60]), "=f"(d[O + 61]), "=f"(d[O + 62]), "=f"(d[O + 63])
    : "r"(a.x), "r"(a.y), "r"(a.z), "r"(a.w), "l"(db));
}
template <bool INIT, int O, int T> __device__ __forceinline__ void wgmma_n128(float (&d)[T], const uint4& a, uint64_t db) {
  if constexpr (INIT) wgmma_rs_n128_init<O>(d, a, db); else wgmma_rs_n128<O>(d, a, db);
}
template <int O, int T> __device__ __forceinline__ void wgmma_rs_n192(float (&d)[T], const uint4& a, uint64_t db) {
  asm volatile("{\n.reg .pred p;\nsetp.ne.b32 p, 1, 0;\n"
    "wgmma.mma_async.sync.aligned.m64n192k16.f32.bf16.bf16 "
    "{%0, %1, %2, %3, %4, %5, %6, %7, %8, %9, %10, %11, %12, %13, %14, %15, "
    "%16, %17, %18, %19, %20, %21, %22, %23, %24, %25, %26, %27, %28, %29, %30, %31, "
    "%32, %33, %34, %35, %36, %37, %38, %39, %40, %41, %42, %43, %44, %45, %46, %47, "
    "%48, %49, %50, %51, %52, %53, %54, %55, %56, %57, %58, %59, %60, %61, %62, %63, "
    "%64, %65, %66, %67, %68, %69, %70, %71, %72, %73, %74, %75, %76, %77, %78, %79, "
    "%80, %81, %82, %83, %84, %85, %86, %87, %88, %89, %90, %91, %92, %93, %94, %95}, "
    "{%96, %97, %98, %99}, %100, p, 1, 1, 1;\n}\n"
    : "+f"(d[O + 0]), "+f"(d[O + 1]), "+f"(d[O + 2]), "+f"(d[O + 3]), "+f"(d[O + 4]), "+f"(d[O + 5]), "+f"(d[O + 6]), "+f"(d[O + 7]),
      "+f"(d[O + 8]), "+f"(d[O + 9]), "+f"(d[O + 10]), "+f"(d[O + 11]), "+f"(d[O + 12]), "+f"(d[O + 13]), "+f"(d[O + 14]), "+f"(d[O + 15]),
      "+f"(d[O + 16]), "+f"(d[O + 17]), "+f"(d[O + 18]), "+f"(d[O + 19]), "+f"(d[O + 20]), "+f"(d[O + 21]), "+f"(d[O + 22]), "+f"(d[O + 23]),
      "+f"(d[O + 24]), "+f"(d[O + 25]), "+f"(d[O + 26]), "+f"(d[O + 27]), "+f"(d[O + 28]), "+f"(d[O + 29]), "+f"(d[O + 30]), "+f"(d[O + 31]),
      "+f"(d[O + 32]), "+f"(d[O + 33]), "+f"(d[O + 34]), "+f"(d[O + 35]), "+f"(d[O + 36]), "+f"(d[O + 37]), "+f"(d[O + 38]), "+f"(d[O + 39]),
      "+f"(d[O + 40]), "+f"(d[O + 41]), "+f"(d[O + 42]), "+f"(d[O + 43]), "+f"(d[O + 44]), "+f"(d[O + 45]), "+f"(d[O + 46]), "+f"(d[O + 47]),
      "+f"(d[O + 48]), "+f"(d[O + 49]), "+f"(d[O + 50]), "+f"(d[O + 51]), "+f"(d[O + 52]), "+f"(d[O + 53]), "+f"(d[O + 54]), "+f"(d[O + 55]),
      "+f"(d[O + 56]), "+f"(d[O + 57]), "+f"(d[O + 58]), "+f"(d[O + 59]), "+f"(d[O + 60]), "+f"(d[O + 61]), "+f"(d[O + 62]), "+f"(d[O + 63]),
      "+f"(d[O + 64]), "+f"(d[O + 65]), "+f"(d[O + 66]), "+f"(d[O + 67]), "+f"(d[O + 68]), "+f"(d[O + 69]), "+f"(d[O + 70]), "+f"(d[O + 71]),
      "+f"(d[O + 72]), "+f"(d[O + 73]), "+f"(d[O + 74]), "+f"(d[O + 75]), "+f"(d[O + 76]), "+f"(d[O + 77]), "+f"(d[O + 78]), "+f"(d[O + 79]),
      "+f"(d[O + 80]), "+f"(d[O + 81]), "+f"(d[O + 82]), "+f"(d[O + 83]), "+f"(d[O + 84]), "+f"(d[O + 85]), "+f"(d[O + 86]), "+f"(d[O + 87]),
      "+f"(d[O + 88]), "+f"(d[O + 89]), "+f"(d[O + 90]), "+f"(d[O + 91]), "+f"(d[O + 92]), "+f"(d[O + 93]), "+f"(d[O + 94]), "+f"(d[O + 95])
    : "r"(a.x), "r"(a.y), "r"(a.z), "r"(a.w), "l"(db));
}
template <int O, int T> __device__ __forceinline__ void wgmma_rs_n192_init(float (&d)[T], const uint4& a, uint64_t db) {
  asm volatile("{\n.reg .pred p;\nsetp.ne.b32 p, 0, 0;\n"
    "wgmma.mma_async.sync.aligned.m64n192k16.f32.bf16.bf16 "
    "{%0, %1, %2, %3, %4, %5, %6, %7, %8, %9, %10, %11, %12, %13, %14, %15, "
    "%16, %17, %18, %19, %20, %21, %22, %23, %24, %25, %26, %27, %28, %29, %30, %31, "
    "%32, %33, %34, %35, %36, %37, %38, %39, %40, %41, %42, %43, %44, %45, %46, %47, "
    "%48, %49, %50, %51, %52, %53, %54, %55, %56, %57, %58, %59, %60, %61, %62, %63, "
    "%64, %65, %66, %67, %68, %69, %70, %71, %72, %73, %74, %75, %76, %77, %78, %79, "
    "%80, %81, %82, %83, %84, %85, %86, %87, %88, %89, %90, %91, %92, %93, %94, %95}, "
    "{%96, %97, %98, %99}, %100, p, 1, 1, 1;\n}\n"
    : "=f"(d[O + 0]), "=f"(d[O + 1]), "=f"(d[O + 2]), "=f"(d[O + 3]), "=f"(d[O + 4]), "=f"(d[O + 5]), "=f"(d[O + 6]), "=f"(d[O + 7]),
      "=f"(d[O + 8]), "=f"(d[O + 9]), "=f"(d[O + 10]), "=f"(d[O + 11]), "=f"(d[O + 12]), "=f"(d[O + 13]), "=f"(d[O + 14]), "=f"(d[O + 15]),
      "=f"(d[O + 16]), "=f"(d[O + 17]), "=f"(d[O + 18]), "=f"(d[O + 19]), "=f"(d[O + 20]), "=f"(d[O + 21]), "=f"(d[O + 22]), "=f"(d[O + 23]),
      "=f"(d[O + 24]), "=f"(d[O + 25]), "=f"(d[O + 26]), "=f"(d[O + 27]), "=f"(d[O + 28]), "=f"(d[O + 29]), "=f"(d[O + 30]), "=f"(d[O + 31]),
      "=f"(d[O + 32]), "=f"(d[O + 33]), "=f"(d[O + 34]), "=f"(d[O + 35]), "=f"(d[O + 36]), "=f"(d[O + 37]), "=f"(d[O + 38]), "=f"(d[O + 39]),
      "=f"(d[O + 40]), "=f"(d[O + 41]), "=f"(d[O + 42]), "=f"(d[O + 43]), "=f"(d[O + 44]), "=f"(d[O + 45]), "=f"(d[O + 46]), "=f"(d[O + 47]),
      "=f"(d[O + 48]), "=f"(d[O + 49]), "=f"(d[O + 50]), "=f"(d[O + 51]), "=f"(d[O + 52]), "=f"(d[O + 53]), "=f"(d[O + 54]), "=f"(d[O + 55]),
      "=f"(d[O + 56]), "=f"(d[O + 57]), "=f"(d[O + 58]), "=f"(d[O + 59]), "=f"(d[O + 60]), "=f"(d[O + 61]), "=f"(d[O + 62]), "=f"(d[O + 63]),
      "=f"(d[O + 64]), "=f"(d[O + 65]), "=f"(d[O + 66]), "=f"(d[O + 67]), "=f"(d[O + 68]), "=f"(d[O + 69]), "=f"(d[O + 70]), "=f"(d[O + 71]),
      "=f"(d[O + 72]), "=f"(d[O + 73]), "=f"(d[O + 74]), "=f"(d[O + 75]), "=f"(d[O + 76]), "=f"(d[O + 77]), "=f"(d[O + 78]), "=f"(d[O + 79]),
      "=f"(d[O + 80]), "=f"(d[O + 81]), "=f"(d[O + 82]), "=f"(d[O + 83]), "=f"(d[O + 84]), "=f"(d[O + 85]), "=f"(d[O + 86]), "=f"(d[O + 87]),
      "=f"(d[O + 88]), "=f"(d[O + 89]), "=f"(d[O + 90]), "=f"(d[O + 91]), "=f"(d[O + 92]), "=f"(d[O + 93]), "=f"(d[O + 94]), "=f"(d[O + 95])
    : "r"(a.x), "r"(a.y), "r"(a.z), "r"(a.w), "l"(db));
}
template <bool INIT, int O, int T> __device__ __forceinline__ void wgmma_n192(float (&d)[T], const uint4& a, uint64_t db) {
  if constexpr (INIT) wgmma_rs_n192_init<O>(d, a, db); else wgmma_rs_n192<O>(d, a, db);
}
template <int O, int T> __device__ __forceinline__ void wgmma_rs_n256(float (&d)[T], const uint4& a, uint64_t db) {
  asm volatile("{\n.reg .pred p;\nsetp.ne.b32 p, 1, 0;\n"
    "wgmma.mma_async.sync.aligned.m64n256k16.f32.bf16.bf16 "
    "{%0, %1, %2, %3, %4, %5, %6, %7, %8, %9, %10, %11, %12, %13, %14, %15, "
    "%16, %17, %18, %19, %20, %21, %22, %23, %24, %25, %26, %27, %28, %29, %30, %31, "
    "%32, %33, %34, %35, %36, %37, %38, %39, %40, %41, %42, %43, %44, %45, %46, %47, "
    "%48, %49, %50, %51, %52, %53, %54, %55, %56, %57, %58, %59, %60, %61, %62, %63, "
    "%64, %65, %66, %67, %68, %69, %70, %71, %72, %73, %74, %75, %76, %77, %78, %79, "
    "%80, %81, %82, %83, %84, %85, %86, %87, %88, %89, %90, %91, %92, %93, %94, %95, "
    "%96, %97, %98, %99, %100, %101, %102, %103, %104, %105, %106, %107, %108, %109, %110, %111, "
    "%112, %113, %114, %115, %116, %117, %118, %119, %120, %121, %122, %123, %124, %125, %126, %127}, "
    "{%128, %129, %130, %131}, %132, p, 1, 1, 1;\n}\n"
    : "+f"(d[O + 0]), "+f"(d[O + 1]), "+f"(d[O + 2]), "+f"(d[O + 3]), "+f"(d[O + 4]), "+f"(d[O + 5]), "+f"(d[O + 6]), "+f"(d[O + 7]),
      "+f"(d[O + 8]), "+f"(d[O + 9]), "+f"(d[O + 10]), "+f"(d[O + 11]), "+f"(d[O + 12]), "+f"(d[O + 13]), "+f"(d[O + 14]), "+f"(d[O + 15]),
      "+f"(d[O + 16]), "+f"(d[O + 17]), "+f"(d[O + 18]), "+f"(d[O + 19]), "+f"(d[O + 20]), "+f"(d[O + 21]), "+f"(d[O + 22]), "+f"(d[O + 23]),
      "+f"(d[O + 24]), "+f"(d[O + 25]), "+f"(d[O + 26]), "+f"(d[O + 27]), "+f"(d[O + 28]), "+f"(d[O + 29]), "+f"(d[O + 30]), "+f"(d[O + 31]),
      "+f"(d[O + 32]), "+f"(d[O + 33]), "+f"(d[O + 34]), "+f"(d[O + 35]), "+f"(d[O + 36]), "+f"(d[O + 37]), "+f"(d[O + 38]), "+f"(d[O + 39]),
      "+f"(d[O + 40]), "+f"(d[O + 41]), "+f"(d[O + 42]), "+f"(d[O + 43]), "+f"(d[O + 44]), "+f"(d[O + 45]), "+f"(d[O + 46]), "+f"(d[O + 47]),
      "+f"(d[O + 48]), "+f"(d[O + 49]), "+f"(d[O + 50]), "+f"(d[O + 51]), "+f"(d[O + 52]), "+f"(d[O + 53]), "+f"(d[O + 54]), "+f"(d[O + 55]),
      "+f"(d[O + 56]), "+f"(d[O + 57]), "+f"(d[O + 58]), "+f"(d[O + 59]), "+f"(d[O + 60]), "+f"(d[O + 61]), "+f"(d[O + 62]), "+f"(d[O + 63]),
      "+f"(d[O + 64]), "+f"(d[O + 65]), "+f"(d[O + 66]), "+f"(d[O + 67]), "+f"(d[O + 68]), "+f"(d[O + 69]), "+f"(d[O + 70]), "+f"(d[O + 71]),
      "+f"(d[O + 72]), "+f"(d[O + 73]), "+f"(d[O + 74]), "+f"(d[O + 75]), "+f"(d[O + 76]), "+f"(d[O + 77]), "+f"(d[O + 78]), "+f"(d[O + 79]),
      "+f"(d[O + 80]), "+f"(d[O + 81]), "+f"(d[O + 82]), "+f"(d[O + 83]), "+f"(d[O + 84]), "+f"(d[O + 85]), "+f"(d[O + 86]), "+f"(d[O + 87]),
      "+f"(d[O + 88]), "+f"(d[O + 89]), "+f"(d[O + 90]), "+f"(d[O + 91]), "+f"(d[O + 92]), "+f"(d[O + 93]), "+f"(d[O + 94]), "+f"(d[O + 95]),
      "+f"(d[O + 96]), "+f"(d[O + 97]), "+f"(d[O + 98]), "+f"(d[O + 99]), "+f"(d[O + 100]), "+f"(d[O + 101]), "+f"(d[O + 102]), "+f"(d[O + 103]),
      "+f"(d[O + 104]), "+f"(d[O + 105]), "+f"(d[O + 106]), "+f"(d[O + 107]), "+f"(d[O + 108]), "+f"(d[O + 109]), "+f"(d[O + 110]), "+f"(d[O + 111]),
      "+f"(d[O + 112]), "+f"(d[O + 113]), "+f"(d[O + 114]), "+f"(d[O + 115]), "+f"(d[O + 116]), "+f"(d[O + 117]), "+f"(d[O + 118]), "+f"(d[O + 119]),
      "+f"(d[O + 120]), "+f"(d[O + 121]), "+f"(d[O + 122]), "+f"(d[O + 123]), "+f"(d[O + 124]), "+f"(d[O + 125]), "+f"(d[O + 126]), "+f"(d[O + 127])
    : "r"(a.x), "r"(a.y), "r"(a.z), "r"(a.w), "l"(db));
}
template <int O, int T> __device__ __forceinline__ void wgmma_rs_n256_init(float (&d)[T], const uint4& a, uint64_t db) {
  asm volatile("{\n.reg .pred p;\nsetp.ne.b32 p, 0, 0;\n"
    "wgmma.mma_async.sync.aligned.m64n256k16.f32.bf16.bf16 "
    "{%0, %1, %2, %3, %4, %5, %6, %7, %8, %9, %10, %11, %12, %13, %14, %15, "
    "%16, %17, %18, %19, %20, %21, %22, %23, %24, %25, %26, %27, %28, %29, %30, %31, "
    "%32, %33, %34, %35, %36, %37, %38, %39, %40, %41, %42, %43, %44, %45, %46, %47, "
    "%48, %49, %50, %51, %52, %53, %54, %55, %56, %57, %58, %59, %60, %61, %62, %63, "
    "%64, %65, %66, %67, %68, %69, %70, %71, %72, %73, %74, %75, %76, %77, %78, %79, "
    "%80, %81, %82, %83, %84, %85, %86, %87, %88, %89, %90, %91, %92, %93, %94, %95, "
    "%96, %97, %98, %99, %100, %101, %102, %103, %104, %105, %106, %107, %108, %109, %110, %111, "
    "%112, %113, %114, %115, %116, %117, %118, %119, %120, %121, %122, %123, %124, %125, %126, %127}, "
    "{%128, %129, %130, %131}, %132, p, 1, 1, 1;\n}\n"
    : "=f"(d[O + 0]), "=f"(d[O + 1]), "=f"(d[O + 2]), "=f"(d[O + 3]), "=f"(d[O + 4]), "=f"(d[O + 5]), "=f"(d[O + 6]), "=f"(d[O + 7]),
      "=f"(d[O + 8]), "=f"(d[O + 9]), "=f"(d[O + 10]), "=f"(d[O + 11]), "=f"(d[O + 12]), "=f"(d[O + 13]), "=f"(d[O + 14]), "=f"(d[O + 15]),
      "=f"(d[O + 16]), "=f"(d[O + 17]), "=f"(d[O + 18]), "=f"(d[O + 19]), "=f"(d[O + 20]), "=f"(d[O + 21]), "=f"(d[O + 22]), "=f"(d[O + 23]),
      "=f"(d[O + 24]), "=f"(d[O + 25]), "=f"(d[O + 26]), "=f"(d[O + 27]), "=f"(d[O + 28]), "=f"(d[O + 29]), "=f"(d[O + 30]), "=f"(d[O + 31]),
      "=f"(d[O + 32]), "=f"(d[O + 33]), "=f"(d[O + 34]), "=f"(d[O + 35]), "=f"(d[O + 36]), "=f"(d[O + 37]), "=f"(d[O + 38]), "=f"(d[O + 39]),
      "=f"(d[O + 40]), "=f"(d[O + 41]), "=f"(d[O + 42]), "=f"(d[O + 43]), "=f"(d[O + 44]), "=f"(d[O + 45]), "=f"(d[O + 46]), "=f"(d[O + 47]),
      "=f"(d[O + 48]), "=f"(d[O + 49]), "=f"(d[O + 50]), "=f"(d[O + 51]), "=f"(d[O + 52]), "=f"(d[O + 53]), "=f"(d[O + 54]), "=f"(d[O + 55]),
      "=f"(d[O + 56]), "=f"(d[O + 57]), "=f"(d[O + 58]), "=f"(d[O + 59]), "=f"(d[O + 60]), "=f"(d[O + 61]), "=f"(d[O + 62]), "=f"(d[O + 63]),
      "=f"(d[O + 64]), "=f"(d[O + 65]), "=f"(d[O + 66]), "=f"(d[O + 67]), "=f"(d[O + 68]), "=f"(d[O + 69]), "=f"(d[O + 70]), "=f"(d[O + 71]),
      "=f"(d[O + 72]), "=f"(d[O + 73]), "=f"(d[O + 74]), "=f"(d[O + 75]), "=f"(d[O + 76]), "=f"(d[O + 77]), "=f"(d[O + 78]), "=f"(d[O + 79]),
      "=f"(d[O + 80]), "=f"(d[O + 81]), "=f"(d[O + 82]), "=f"(d[O + 83]), "=f"(d[O + 84]), "=f"(d[O + 85]), "=f"(d[O + 86]), "=f"(d[O + 87]),
      "=f"(d[O + 88]), "=f"(d[O + 89]), "=f"(d[O + 90]), "=f"(d[O + 91]), "=f"(d[O + 92]), "=f"(d[O + 93]), "=f"(d[O + 94]), "=f"(d[O + 95]),
      "=f"(d[O + 96]), "=f"(d[O + 97]), "=f"(d[O + 98]), "=f"(d[O + 99]), "=f"(d[O + 100]), "=f"(d[O + 101]), "=f"(d[O + 102]), "=f"(d[O + 103]),
      "=f"(d[O + 104]), "=f"(d[O + 105]), "=f"(d[O + 106]), "=f"(d[O + 107]), "=f"(d[O + 108]), "=f"(d[O + 109]), "=f"(d[O + 110]), "=f"(d[O + 111]),
      "=f"(d[O + 112]), "=f"(d[O + 113]), "=f"(d[O + 114]), "=f"(d[O + 115]), "=f"(d[O + 116]), "=f"(d[O + 117]), "=f"(d[O + 118]), "=f"(d[O + 119]),
      "=f"(d[O + 120]), "=f"(d[O + 121]), "=f"(d[O + 122]), "=f"(d[O + 123]), "=f"(d[O + 124]), "=f"(d[O + 125]), "=f"(d[O + 126]), "=f"(d[O + 127])
    : "r"(a.x), "r"(a.y), "r"(a.z), "r"(a.w), "l"(db));
}
template <bool INIT, int O, int T> __device__ __forceinline__ void wgmma_n256(float (&d)[T], const uint4& a, uint64_t db) {
  if constexpr (INIT) wgmma_rs_n256_init<O>(d, a, db); else wgmma_rs_n256<O>(d, a, db);
}

template <int N> __device__ __forceinline__ void try_pk(uint4* a, const uint4* p) {
#pragma unroll
  for (int i = 0; i < N; i++) a[i] = ld_try(p + i * 32);
}
template <int N> __device__ __forceinline__ void load_pk(uint4* a, const uint4* p) {
#pragma unroll
  for (int i = 0; i < N; i++) a[i] = ld_ll(p + i * 32);
}
__device__ __forceinline__ uint32_t xor_or(uint32_t a, uint32_t b, uint32_t t) {
  uint32_t r;
  asm("lop3.b32 %0, %1, %2, %3, 0x7E;" : "=r"(r) : "r"(a), "r"(b), "r"(t));
  return r;
}
template <int N> __device__ __forceinline__ bool ok_pk(const uint4* a, uint32_t tag) {
  static_assert(N % 2 == 0, "");
  uint32_t x = xor_or(a[0].x, a[1].x, tag);
#pragma unroll
  for (int i = 2; i < N; i += 2) x |= xor_or(a[i].x, a[i + 1].x, tag);
  return __all_sync(0xffffffffu, (x & 1u) == 0u);
}
template <int N> __device__ __forceinline__ void ensure_pk(uint4* a, const uint4* p, uint32_t tag) {
  if (ok_pk<N>(a, tag)) return;
  uint32_t n = 0;
  do { load_pk<N>(a, p); } while (!ok_pk<N>(a, tag) && ++n < SPIN_LIMIT);
}

constexpr int NSTAGE = 44;
constexpr int ST_WO = 8, ST_G1 = 12, ST_G2 = 20, ST_DN = 28;
__host__ __device__ constexpr int st_len(int s) { return s < ST_WO ? 3 : s < ST_G1 ? 2 : s < ST_G2 ? 4 : s < ST_DN ? 3 : 2; }
__host__ __device__ constexpr int st_g0(int s) {
  int pos = 0, g0 = 0;
  for (int i = 0; i <= s; i++) {
    if (pos + st_len(i) > NGRAN) pos = 0;
    g0 = pos;
    pos += st_len(i);
  }
  return g0;
}
__host__ __device__ constexpr int cnt_first(int g, int s) {
  int n = 0;
  for (int i = 0; i < s; i++) n += (st_g0(i) == g);
  return n;
}
__host__ __device__ constexpr int cnt_cover(int g, int s) {
  int n = 0;
  for (int i = 0; i < s; i++) n += (g >= st_g0(i) && g < st_g0(i) + st_len(i));
  return n;
}
__host__ __device__ constexpr uint32_t flip_mask(int s0, int s1) {
  uint32_t m = 0;
  for (int i = s0; i < s1; i++) m ^= ((1u << st_len(i)) - 1u) << st_g0(i);
  return m;
}
__host__ __device__ constexpr int dn_q(int i) { return i < 3 ? 0 : i < 6 ? 1 : i == 6 ? 0 : i == 7 ? 1 : i < 12 ? 2 : 3; }
__host__ __device__ constexpr int dn_par(int i) { return i < 8 ? (i == 2 || i == 4 || i >= 6) : (i & 1); }
__host__ __device__ constexpr int dn_kh(int i) { return i < 8 ? (i == 1 || i >= 5) : ((i & 3) >= 2); }
template <int I> struct IC { static constexpr int value = I; };
template <int B, int E, typename F> __device__ __forceinline__ void static_for(F&& f) {
  if constexpr (B < E) { f(IC<B>{}); static_for<B + 1, E>(f); }
}
template <int S> __device__ __forceinline__ void cons_acquire(uint32_t sbase, uint32_t L) {
  constexpr int g0 = st_g0(S);
  constexpr uint32_t p0 = cnt_first(g0, S) & 1, odd = cnt_first(g0, NSTAGE) & 1;
  mbar_wait(sbase + SM_MISC + BAR_FULL + 8 * g0, p0 ^ (L & odd));
}
template <int S> __device__ __forceinline__ void cons_release(uint32_t sbase, int lane) {
  if (lane < st_len(S)) mbar_arrive(sbase + SM_MISC + BAR_EMPTY + 8 * st_g0(S) + 8 * lane);
}
__device__ __forceinline__ bool elect_one() {
  uint32_t p;
  asm volatile("{\n.reg .pred P;\nelect.sync _|P, 0xffffffff;\nselp.u32 %0, 1, 0, P;\n}" : "=r"(p));
  return p != 0;
}
struct ProdRing { uint32_t pos, par; };
template <int N> __device__ __forceinline__ uint32_t prod_acquire(uint32_t sbase, ProdRing& r) {
  if (r.pos + N > NGRAN) r.pos = 0;
  const uint32_t g0 = r.pos;
#pragma unroll
  for (uint32_t i = 0; i < N; i++) mbar_wait(sbase + SM_MISC + BAR_EMPTY + 8 * (g0 + i), ((r.par >> (g0 + i)) & 1u) ^ 1u);
  r.par ^= ((1u << N) - 1u) << g0;
  r.pos = g0 + N;
  return g0;
}
template <int S> __device__ __forceinline__ void prod_acquire_static(uint32_t sbase, uint32_t L) {
  constexpr int g0 = st_g0(S);
  static_for<0, st_len(S)>([&](auto I) {
    constexpr int g = g0 + I.value;
    constexpr uint32_t p0 = cnt_cover(g, S) & 1, odd = cnt_cover(g, NSTAGE) & 1;
    mbar_wait(sbase + SM_MISC + BAR_EMPTY + 8 * g, p0 ^ (L & odd) ^ 1u);
  });
}
template <int S, int KSTEP_BYTES, int LBO, int SBO, int SWZ> __device__ __forceinline__ constexpr uint64_t st_desc(int k) {
  return (uint64_t)((SMEM_ORIGIN + st_g0(S) * GRAN + k * KSTEP_BYTES) >> 4) | ((uint64_t)(LBO >> 4) << 16) |
         ((uint64_t)(SBO >> 4) << 32) | ((uint64_t)SWZ << 62);
}

__device__ __forceinline__ void combine_stats(const uint4& p0, const uint4& p1, float& mean_lo, float& rstd_lo, float& mean_hi, float& rstd_hi) {
  float m0 = __uint_as_float(p0.x), q0 = __uint_as_float(p0.y), m0h = __uint_as_float(p0.z), q0h = __uint_as_float(p0.w);
  float m1 = __uint_as_float(p1.x), q1 = __uint_as_float(p1.y), m1h = __uint_as_float(p1.z), q1h = __uint_as_float(p1.w);
  float s = m0 + m1, sh = m0h + m1h;
  s += __shfl_xor_sync(0xffffffffu, s, 1); sh += __shfl_xor_sync(0xffffffffu, sh, 1);
  s += __shfl_xor_sync(0xffffffffu, s, 2); sh += __shfl_xor_sync(0xffffffffu, sh, 2);
  mean_lo = s * 0.125f; mean_hi = sh * 0.125f;
  float d0 = m0 - mean_lo, d1 = m1 - mean_lo, d0h = m0h - mean_hi, d1h = m1h - mean_hi;
  float t = q0 + q1 + 64.f * (d0 * d0 + d1 * d1), th = q0h + q1h + 64.f * (d0h * d0h + d1h * d1h);
  t += __shfl_xor_sync(0xffffffffu, t, 1); th += __shfl_xor_sync(0xffffffffu, th, 1);
  t += __shfl_xor_sync(0xffffffffu, t, 2); th += __shfl_xor_sync(0xffffffffu, th, 2);
  rstd_lo = rsqrtf(t * (1.f / 512.f) + 1e-5f);
  rstd_hi = rsqrtf(th * (1.f / 512.f) + 1e-5f);
}
__device__ __forceinline__ uint4 local_stats(const float (&v)[32]) {
  float s = 0.f, sh = 0.f;
#pragma unroll
  for (int i = 0; i < 4; i++) {
    s += (v[8 * i + 0] + v[8 * i + 1]) + (v[8 * i + 4] + v[8 * i + 5]);
    sh += (v[8 * i + 2] + v[8 * i + 3]) + (v[8 * i + 6] + v[8 * i + 7]);
  }
  s += __shfl_xor_sync(0xffffffffu, s, 1); sh += __shfl_xor_sync(0xffffffffu, sh, 1);
  s += __shfl_xor_sync(0xffffffffu, s, 2); sh += __shfl_xor_sync(0xffffffffu, sh, 2);
  float m = s * (1.f / 64.f), mh = sh * (1.f / 64.f);
  float q = 0.f, qh = 0.f;
#pragma unroll
  for (int i = 0; i < 4; i++) {
    float a = v[8 * i + 0] - m, b = v[8 * i + 1] - m, c = v[8 * i + 4] - m, d = v[8 * i + 5] - m;
    q += (a * a + b * b) + (c * c + d * d);
    float e = v[8 * i + 2] - mh, f = v[8 * i + 3] - mh, g = v[8 * i + 6] - mh, h = v[8 * i + 7] - mh;
    qh += (e * e + f * f) + (g * g + h * h);
  }
  q += __shfl_xor_sync(0xffffffffu, q, 1); qh += __shfl_xor_sync(0xffffffffu, qh, 1);
  q += __shfl_xor_sync(0xffffffffu, q, 2); qh += __shfl_xor_sync(0xffffffffu, qh, 2);
  return make_uint4(__float_as_uint(m), __float_as_uint(q), __float_as_uint(mh), __float_as_uint(qh));
}

__device__ __forceinline__ int slab_row0(int c, int g, int w) { return 1024 * g + 64 * c + 32 * (w >> 1) + (w & 1); }

__device__ __forceinline__ void owner_ln_publish(uint32_t sbase, const float (&v)[32], uint32_t tphase, uint32_t tag_xn, uint4 (&xraw)[4]) {
  PHASE_VARS;
  TS(40 + 4 * tphase);
  uint4 st = local_stats(v);
  if (qc == 0) sts128(sbase + SM_TSTAT + warp * 128 + qr * 16, st);
  uint4* xn = g_arena + c * ARENA + AR_XN + ((j) * 32 + 4 * warp) * 32 + lane;
  TS(41 + 4 * tphase);
  asm volatile("bar.sync 3, 256;" ::: "memory");
  TS(42 + 4 * tphase);
  const uint32_t rd = sbase + SM_TSTAT + qc * 256 + qr * 16;
  uint4 p0 = lds128(rd), p1 = lds128(rd + 128);
  float ml, rl, mh, rh;
  combine_stats(p0, p1, ml, rl, mh, rh);
  const float bl = -ml * rl, bh = -mh * rh;
#pragma unroll
  for (int i = 0; i < 4; i++) {
    uint4 o;
    o.x = set_tag(pack2(fmaf(v[8 * i + 0], rl, bl), fmaf(v[8 * i + 1], rl, bl)), tag_xn);
    o.y = pack2(fmaf(v[8 * i + 2], rh, bh), fmaf(v[8 * i + 3], rh, bh));
    o.z = pack2(fmaf(v[8 * i + 4], rl, bl), fmaf(v[8 * i + 5], rl, bl));
    o.w = pack2(fmaf(v[8 * i + 6], rh, bh), fmaf(v[8 * i + 7], rh, bh));
    st_ll(xn + i * 32, o);
  }
#pragma unroll
  for (int i = 0; i < 4; i++) {
    xraw[i].x = set_tag(pack2(v[8 * i + 0], v[8 * i + 1]), 1u);
    xraw[i].y = pack2(v[8 * i + 2], v[8 * i + 3]);
    xraw[i].z = pack2(v[8 * i + 4], v[8 * i + 5]);
    xraw[i].w = pack2(v[8 * i + 6], v[8 * i + 7]);
  }
}

__device__ __forceinline__ uint4 pack8(const float* a) {
  return make_uint4(pack2(a[0], a[1]), pack2(a[2], a[3]), pack2(a[4], a[5]), pack2(a[6], a[7]));
}
template <int U> __device__ __forceinline__ uint4 glu8(const float* g, float cl, float ch) {
  return make_uint4(pack2(g[0] * cl * g[U], g[1] * cl * g[U + 1]), pack2(g[2] * ch * g[U + 2], g[3] * ch * g[U + 3]),
                    pack2(g[4] * cl * g[U + 4], g[5] * cl * g[U + 5]), pack2(g[6] * ch * g[U + 6], g[7] * ch * g[U + 7]));
}
__device__ __forceinline__ uint32_t hfma2(uint32_t a, uint32_t b, uint32_t c) {
  uint32_t d;
  asm("fma.rn.bf16x2 %0, %1, %2, %3;" : "=r"(d) : "r"(a), "r"(b), "r"(c));
  return d;
}
__device__ __forceinline__ void keep4(const uint4 (&a)[4]) { keep(a[0]); keep(a[1]); keep(a[2]); keep(a[3]); }

#define STAGGER 0

__global__ void __launch_bounds__(NTHREADS, 1)
fused_kernel(const __grid_constant__ CUtensorMap m_qkv, const __grid_constant__ CUtensorMap m_wo,
             const __grid_constant__ CUtensorMap m_gu2, const __grid_constant__ CUtensorMap m_gu1,
             const __grid_constant__ CUtensorMap m_guh, const __grid_constant__ CUtensorMap m_wd112,
             const __grid_constant__ CUtensorMap m_wd80, const __grid_constant__ CUtensorMap m_wd32,
             const __nv_bfloat16* __restrict__ x_in,
             __nv_bfloat16* __restrict__ out
) {
  extern __shared__ __align__(1024) unsigned char smem_raw[];
  const uint32_t sbase = smem_u32(smem_raw);
  const uint32_t bars = sbase + SM_MISC;
  if ((sbase & 0xFFFFFFu) != SMEM_ORIGIN) return;
  TG(60);

  uint32_t xw[16];
  if (threadIdx.x < 256) {
    const int cc = blockIdx.x >> 3, jj = blockIdx.x & 7, ln = threadIdx.x & 31;
    const uint32_t* xp = reinterpret_cast<const uint32_t*>(x_in + (size_t)(slab_row0(cc, jj >> 2, jj & 3) + 2 * (ln >> 2)) * 512 + (threadIdx.x >> 5) * 64 + (ln & 3) * 2);
#pragma unroll
    for (int i = 0; i < 4; i++) {
      xw[4 * i] = __ldg(xp + i * 8); xw[4 * i + 1] = __ldg(xp + 16 * 256 + i * 8);
      xw[4 * i + 2] = __ldg(xp + i * 8 + 4); xw[4 * i + 3] = __ldg(xp + 16 * 256 + i * 8 + 4);
    }
  } else if (threadIdx.x == 256) {
    for (int i = 0; i < NGRAN; i++) { mbar_init(bars + BAR_FULL + 8 * i, 1); mbar_init(bars + BAR_EMPTY + 8 * i, 8); }
    for (int i = 0; i < 4; i++) mbar_init(bars + BAR_HRECV + 8 * i, 1);
    for (int i = 0; i < 2; i++) mbar_init(bars + BAR_HREADY + 8 * i, 4);
    asm volatile("fence.mbarrier_init.release.cluster;" ::: "memory");
  }
  __syncthreads();
  asm volatile("barrier.cluster.arrive.release.aligned;" ::: "memory");

  if (threadIdx.x >= 256) {
    asm volatile("setmaxnreg.dec.sync.aligned.u32 40;");
    const int warp = threadIdx.x >> 5;
    const int j = blockIdx.x & 7, b = j & 1;
    if (warp == 8) {
      ProdRing r{0u, 0u};
      const int cb0 = 224 * j + 32 * b, hb0 = 224 * j + 192 * (b ^ 1);
      const int jp = j ^ 1, cbp = 224 * jp + 32 * (b ^ 1), hbp = 224 * jp + 192 * b;
#pragma unroll 1
      for (uint32_t L = 0; L < 2; L++) {
        r.pos = 0;
        PSTOP_AT(L == 0 ? 0 : 3);
#pragma unroll 1
        for (int kb = 0; kb < 8; kb++) {
          const uint32_t g0 = prod_acquire<3>(sbase, r);
          if (elect_one()) {
            mbar_expect_tx(bars + BAR_FULL + 8 * g0, 24576);
            tma_3d(sbase + g0 * GRAN, &m_qkv, bars + BAR_FULL + 8 * g0, 64 * j, 64 * kb, 0);
          }
        }
        PSTOP_AT(10 * L + 1);
#pragma unroll 1
        for (int i = 0; i < 4; i++) {
          const uint32_t g0 = prod_acquire<2>(sbase, r);
          if (elect_one()) {
            mbar_expect_tx(bars + BAR_FULL + 8 * g0, 16384);
            tma_2d(sbase + g0 * GRAN, &m_wo, bars + BAR_FULL + 8 * g0, 64 * j, 128 * i);
          }
        }
        PSTOP_AT(10 * L + 2);
#pragma unroll 1
        for (int kb = 0; kb < 8; kb++) {
          const uint32_t g0 = prod_acquire<4>(sbase, r);
          if (elect_one()) {
            mbar_expect_tx(bars + BAR_FULL + 8 * g0, 32768);
            tma_4d(sbase + g0 * GRAN, &m_gu2, bars + BAR_FULL + 8 * g0, cb0, 64 * ((j + kb) & 7), 0, 0);
          }
        }
#pragma unroll 1
        for (int kb = 0; kb < 8; kb++) {
          const uint32_t g0 = prod_acquire<3>(sbase, r);
          if (elect_one()) {
            mbar_expect_tx(bars + BAR_FULL + 8 * g0, 24576);
            tma_4d(sbase + g0 * GRAN, &m_gu1, bars + BAR_FULL + 8 * g0, cb0 + 128, 64 * ((j + kb) & 7), 0, 0);
            tma_3d(sbase + g0 * GRAN + 16384, &m_guh, bars + BAR_FULL + 8 * g0, hb0, 64 * ((j + kb) & 7), 0);
          }
        }
        static_for<0, 16>([&](auto I) {
          constexpr int i = I.value, g0 = st_g0(ST_DN + i);
          prod_acquire_static<ST_DN + i>(sbase, L);
          if (elect_one()) {
            const uint32_t dst = sbase + g0 * GRAN, fb = bars + BAR_FULL + 8 * g0;
            const int n0 = 256 * b + 64 * dn_q(i);
            mbar_expect_tx(fb, 14336);
            if constexpr (dn_kh(i) == 0) {
              tma_2d(dst, &m_wd112, fb, n0, dn_par(i) ? cbp : cb0);
            } else {
              tma_2d(dst, &m_wd80, fb, n0, (dn_par(i) ? cbp : cb0) + 112);
              tma_2d(dst + 10240, &m_wd32, fb, n0, dn_par(i) ? hbp : hb0);
            }
          }
        });
        r.par ^= flip_mask(ST_DN, NSTAGE);
      }
    }
    __syncwarp();
    asm volatile("barrier.cluster.wait.acquire.aligned; // producer" ::: "memory");
    asm volatile("barrier.cluster.arrive.release.aligned;\nbarrier.cluster.wait.acquire.aligned; // producer" ::: "memory");
  } else {
    asm volatile("setmaxnreg.inc.sync.aligned.u32 232;");
    TS(0);
    TG(61);

    uint4 xraw[4];
    {
      float v[32];
#pragma unroll
      for (int i = 0; i < 16; i++) { v[2 * i] = bf_lo(xw[i]); v[2 * i + 1] = bf_hi(xw[i]); }
      owner_ln_publish(sbase, v, 0u, 1u, xraw);
      asm volatile("barrier.cluster.wait.acquire.aligned; // consumer" ::: "memory");
    }
    STOP_AT(0);
    TS(1);

#pragma unroll 1
    for (uint32_t L = 0; L < 2; L++) {
      const uint32_t tag = L ^ 1;
      {
        PHASE_VARS;
        uint4 qf[4], kf[4], vf[4], pp[4];
        const int blk = 16 * g + c;
        const int pb = blk > 0 ? blk - 1 : 0;
        const uint4* halo_src = g_arena + (pb & 15) * ARENA + AR_HALO + (((((L * 2 + (pb >> 4)) * 8 + j) * 2 + (w & 1)) * 4) * 32) + lane;
        {
          float acc[96];
          uint4 A[3][4];
          const uint4* xs = g_arena + c * ARENA + AR_XN + ((slab) * 32) * 32 + lane;
          bar_wg(1 + g);
          cold_delay(L);
          load_pk<4>(A[0], xs);
          ensure_pk<4>(A[0], xs, tag);
          TS(2 + 20 * L);
          try_pk<4>(A[1], xs + 128);
          static_for<0, 8>([&](auto I) {
            constexpr int kb = I.value;
            cons_acquire<kb>(sbase, L);
            wg_fence();
            static_for<0, 4>([&](auto K) { constexpr int k = K.value; wgmma_n192<kb == 0 && k == 0, 0>(acc, A[kb % 3][k], st_desc<kb, 2048, 8192, 1024, 1>(k)); });
            wg_commit();
            if constexpr (kb > 0) {
              wg_wait<1>();
              keep4(A[(kb + 2) % 3]);
              cons_release<kb - 1>(sbase, lane);
            }
            if constexpr (kb + 1 < 8) ensure_pk<4>(A[(kb + 1) % 3], xs + (kb + 1) * 128, tag);
            if constexpr (kb + 2 < 8) try_pk<4>(A[(kb + 2) % 3], xs + (kb + 2) * 128);
            if constexpr (kb == 2) {
              uint4* xr = g_arena + c * ARENA + AR_XRAW + ((j) * 32 + 4 * warp) * 32 + lane;
#pragma unroll
              for (int i = 0; i < 4; i++) st_ll(xr + i * 32, xraw[i]);
            }
          });
          wg_wait<0>();
          TS(3 + 20 * L);
          fence_acc(acc);
          keep4(A[1]);
          cons_release<7>(sbase, lane);
#pragma unroll
          for (int h = 0; h < 4; h++) {
            kf[h].y = pack2(acc[32 + 8 * h + 2], acc[32 + 8 * h + 3]); kf[h].w = pack2(acc[32 + 8 * h + 6], acc[32 + 8 * h + 7]);
            vf[h].y = movm(pack2(acc[64 + 8 * h + 2], acc[64 + 8 * h + 3])); vf[h].w = movm(pack2(acc[64 + 8 * h + 6], acc[64 + 8 * h + 7]));
            pp[h] = make_uint4(kf[h].y, kf[h].w, vf[h].y, vf[h].w);
          }
          if (w >= 2 && blk < 31) {
            uint4* hd = g_arena + c * ARENA + AR_HALO + (((((L * 2 + g) * 8 + j) * 2 + (w & 1)) * 4) * 32) + lane;
#pragma unroll
            for (int h = 0; h < 4; h++) { uint4 t = pp[h]; t.x |= 1u; st_ll(hd + h * 32, t); }
          }
#pragma unroll
          for (int h = 0; h < 4; h++) sts128(areg + (28 + h) * 2048 + t128 * 16, pp[h]);
#pragma unroll
          for (int h = 0; h < 4; h++) {
            kf[h].x = pack2(acc[32 + 8 * h], acc[32 + 8 * h + 1]); kf[h].z = pack2(acc[32 + 8 * h + 4], acc[32 + 8 * h + 5]);
            vf[h].x = movm(pack2(acc[64 + 8 * h], acc[64 + 8 * h + 1])); vf[h].z = movm(pack2(acc[64 + 8 * h + 4], acc[64 + 8 * h + 5]));
          }
#pragma unroll
          for (int h = 0; h < 4; h++) qf[h] = pack8(&acc[8 * h]);
        }
        bar_wg(1 + g);
        const bool first = (w < 2) && (blk == 0);
        if (w >= 2) {
#pragma unroll
          for (int h = 0; h < 4; h++) pp[h] = lds128(areg + (28 + h) * 2048 + (t128 - 64) * 16);
        }
        bar_wg(1 + g);
        if (w < 2 && blk > 0) {
          cold_delay(L);
          load_pk<4>(pp, halo_src);
          ensure_pk<4>(pp, halo_src, 1u);
          uint4* hz = const_cast<uint4*>(halo_src);
#pragma unroll
          for (int h = 0; h < 4; h++) st_ll(hz + h * 32, make_uint4(0, 0, 0, 0));
        }
        TS(4 + 20 * L);
        const bool n0 = 2 * qc <= qr, n1 = 2 * qc + 1 <= qr;
        const uint32_t msk = (n0 ? 0xffffu : 0u) | (n1 ? 0xffff0000u : 0u);
        const float sc = 0.25f * 1.4426950408889634f;
        const float NEG = -1e30f;
        uint4* od = g_arena + c * ARENA + AR_O + ((slab) * 32 + 4 * j) * 32 + lane;
        float l0[4], l1[4], h0[4], h1[4], ml[4], mh[4];
#pragma unroll
        for (int h = 0; h < 4; h++) {
          float sp[4], s0[4], s1[4];
          mma16816_z(sp, qf[h], pp[h].x, pp[h].y);
          mma16816_z(s0, qf[h], kf[h].x, kf[h].z);
          mma16816_z(s1, qf[h], kf[h].y, kf[h].w);
          if (first) { sp[0] = NEG; sp[1] = NEG; }
          l0[h] = n0 ? s0[0] : sp[0]; l1[h] = n1 ? s0[1] : sp[1];
          h0[h] = n0 ? s1[2] : s0[2]; h1[h] = n1 ? s1[3] : s0[3];
          ml[h] = fmaxf(l0[h], l1[h]); mh[h] = fmaxf(h0[h], h1[h]);
        }
#pragma unroll
        for (int h = 0; h < 4; h++) { ml[h] = fmaxf(ml[h], __shfl_xor_sync(0xffffffffu, ml[h], 1)); mh[h] = fmaxf(mh[h], __shfl_xor_sync(0xffffffffu, mh[h], 1)); }
#pragma unroll
        for (int h = 0; h < 4; h++) { ml[h] = fmaxf(ml[h], __shfl_xor_sync(0xffffffffu, ml[h], 2)); mh[h] = fmaxf(mh[h], __shfl_xor_sync(0xffffffffu, mh[h], 2)); }
        float sl[4], sh[4];
#pragma unroll
        for (int h = 0; h < 4; h++) {
          const float bl = -ml[h] * sc, bh = -mh[h] * sc;
          l0[h] = ex2(fmaf(l0[h], sc, bl)); l1[h] = ex2(fmaf(l1[h], sc, bl));
          h0[h] = ex2(fmaf(h0[h], sc, bh)); h1[h] = ex2(fmaf(h1[h], sc, bh));
          sl[h] = l0[h] + l1[h]; sh[h] = h0[h] + h1[h];
        }
#pragma unroll
        for (int h = 0; h < 4; h++) { sl[h] += __shfl_xor_sync(0xffffffffu, sl[h], 1); sh[h] += __shfl_xor_sync(0xffffffffu, sh[h], 1); }
#pragma unroll
        for (int h = 0; h < 4; h++) { sl[h] += __shfl_xor_sync(0xffffffffu, sl[h], 2); sh[h] += __shfl_xor_sync(0xffffffffu, sh[h], 2); }
#pragma unroll
        for (int h = 0; h < 4; h++) {
          const float il = rcp(sl[h]), ih = rcp(sh[h]);
          const uint32_t pl = pack2(l0[h] * il, l1[h] * il), ph = pack2(h0[h] * ih, h1[h] * ih);
          const uint4 P = make_uint4(pl & msk, ph & ~msk, 0u, ph & msk);
          float o0[4], o1[4];
          mma16816_z(o0, P, vf[h].x, vf[h].y);
          mma16816_z(o1, P, vf[h].z, vf[h].w);
          mma1688(o0, pl & ~msk, 0u, pp[h].z);
          mma1688(o1, pl & ~msk, 0u, pp[h].w);
          st_ll(od + h * 32, make_uint4(set_tag(pack2(o0[0], o0[1]), tag), pack2(o0[2], o0[3]), pack2(o1[0], o1[1]), pack2(o1[2], o1[3])));
        }
      }
      TS(5 + 20 * L);
      if (L == 0) { STOP_AT(1); } else { STOP_AT(11); }
      uint4 x1own[4];
      {
        PHASE_VARS;
        float acc[32];
        uint4 A[32], xr[4];
        const uint4* os = g_arena + c * ARENA + AR_O + ((slab) * 32) * 32 + lane;
        uint4* xp = g_arena + c * ARENA + AR_XRAW + ((slab) * 32 + 4 * j) * 32 + lane;
        load_pk<4>(xr, xp);
        cold_delay(L);
        load_pk<4>(A, os);
        ensure_pk<4>(A, os, tag);
        TS(6 + 20 * L);
        try_pk<28>(A + 4, os + 128);
        static_for<0, 8>([&](auto I) {
          constexpr int kb = I.value;
          if constexpr ((kb & 1) == 0) cons_acquire<ST_WO + kb / 2>(sbase, L);
          if constexpr (kb > 0) ensure_pk<4>(A + 4 * kb, os + kb * 128, tag);
          wg_fence();
          static_for<0, 4>([&](auto K) {
            constexpr int k = K.value;
            wgmma_n64<kb == 0 && k == 0, 0>(acc, A[4 * kb + k], st_desc<ST_WO + kb / 2, 2048, 8192, 1024, 1>(4 * (kb & 1) + k));
          });
          wg_commit();
          if constexpr ((kb & 1) == 0 && kb > 0) { wg_wait<1>(); cons_release<ST_WO + kb / 2 - 1>(sbase, lane); }
        });
        wg_wait<0>();
        TS(7 + 20 * L);
        fence_acc(acc);
#pragma unroll
        for (int k = 0; k < 32; k++) keep(A[k]);
        cons_release<ST_WO + 3>(sbase, lane);
        ensure_pk<4>(xr, xp, 1u);
#pragma unroll
        for (int i = 0; i < 4; i++) {
          acc[8 * i + 0] += bf_lo(xr[i].x); acc[8 * i + 1] += bf_hi(xr[i].x); acc[8 * i + 2] += bf_lo(xr[i].y); acc[8 * i + 3] += bf_hi(xr[i].y);
          acc[8 * i + 4] += bf_lo(xr[i].z); acc[8 * i + 5] += bf_hi(xr[i].z); acc[8 * i + 6] += bf_lo(xr[i].w); acc[8 * i + 7] += bf_hi(xr[i].w);
        }
        uint4 st = local_stats(acc);
        st.x = set_tag(st.x, tag);
        if (qc == 0) st_ll(g_arena + c * ARENA + AR_STATS + (slab * 8 + j) * 8 + qr, st);
#pragma unroll
        for (int i = 0; i < 4; i++) {
          x1own[i] = pack8(&acc[8 * i]);
          x1own[i].x = set_tag(x1own[i].x, 0u);
          st_ll(xp + i * 32, x1own[i]);
        }
      }
      TS(8 + 20 * L);
      if (L == 0) { STOP_AT(2); } else { STOP_AT(12); }
      uint4 hs[14];
      {
        PHASE_VARS;
        float acc[128];
        uint4 A[3][4];
        const uint4* xs = g_arena + c * ARENA + AR_XRAW + ((slab) * 32) * 32 + lane;
        const uint4* sp = g_arena + c * ARENA + AR_STATS + (slab * 8 + 2 * qc) * 8 + qr;
        const uint32_t sm = areg + t128 * 16;
        uint32_t rl2, rh2, bl2, bh2;
        float cl, ch;
        auto xsrc = [&](int p) { return xs + ((j + p) & 7) * 128; };
        {
          uint4 p[2];
#pragma unroll
          for (int k = 0; k < 4; k++) A[0][k] = x1own[k];
          cold_delay(L);
          p[0] = ld_ll(sp); p[1] = ld_ll(sp + 8);
          try_pk<4>(A[1], xsrc(1));
          for (uint32_t n = 0; !ok_pk<2>(p, tag) && n < SPIN_LIMIT; n++) { p[0] = ld_ll(sp); p[1] = ld_ll(sp + 8); }
          TS(9 + 20 * L);
          float ml, rl, mh, rh;
          combine_stats(p[0], p[1], ml, rl, mh, rh);
          rl2 = pack2(rl, rl); rh2 = pack2(rh, rh);
          const float rlb = bf_lo(rl2), rhb = bf_lo(rh2);
          bl2 = pack2(-ml * rlb, -ml * rlb); bh2 = pack2(-mh * rhb, -mh * rhb);
          cl = rl / rlb; cl *= cl; ch = rh / rhb; ch *= ch;
        }
        auto normalise = [&](uint4 (&xb)[4], int kb) {
#pragma unroll
          for (int k = 0; k < 4; k++) {
            xb[k].x = hfma2(xb[k].x, rl2, bl2); xb[k].y = hfma2(xb[k].y, rh2, bh2);
            xb[k].z = hfma2(xb[k].z, rl2, bl2); xb[k].w = hfma2(xb[k].w, rh2, bh2);
            sts128(sm + (kb * 4 + k) * 2048, xb[k]);
          }
        };
        normalise(A[0], 0);
        static_for<0, 8>([&](auto I) {
          constexpr int kb = I.value;
          cons_acquire<ST_G1 + kb>(sbase, L);
          wg_fence();
          static_for<0, 4>([&](auto K) { constexpr int k = K.value; wgmma_n256<kb == 0 && k == 0, 0>(acc, A[kb % 3][k], st_desc<ST_G1 + kb, 2048, 8192, 1024, 1>(k)); });
          wg_commit();
          if constexpr (kb > 0) {
            wg_wait<1>();
            keep4(A[(kb + 2) % 3]);
            cons_release<ST_G1 + kb - 1>(sbase, lane);
          }
          if constexpr (kb + 1 < 8) ensure_pk<4>(A[(kb + 1) % 3], xsrc(kb + 1), 0u);
          if constexpr (kb + 2 < 8) try_pk<4>(A[(kb + 2) % 3], xsrc(kb + 2));
          if constexpr (kb + 1 < 8) normalise(A[(kb + 1) % 3], kb + 1);
        });
        wg_wait<0>();
        TS(10 + 20 * L);
        fence_acc(acc);
        keep4(A[1]);
        cons_release<ST_G1 + 7>(sbase, lane);
        uint4 B[2][4];
#pragma unroll
        for (int k = 0; k < 4; k++) B[0][k] = lds128(sm + k * 2048);
#pragma unroll
        for (int s = 0; s < 8; s++) hs[s] = glu8<32>(&acc[64 * (s >> 2) + 8 * (s & 3)], cl, ch);
        float acc2[96];
        const uint32_t hdst = mapa(sm, cbit ^ 1);
        const uint32_t hbar1 = mapa(bars + BAR_HRECV + 16 * g, cbit ^ 1);
        if (t128 == 0) { mbar_expect_tx(bars + BAR_HRECV + 16 * g, 8 * 2048); mbar_expect_tx(bars + BAR_HRECV + 16 * g + 8, 6 * 2048); }
        static_for<0, 8>([&](auto I) {
          constexpr int kb = I.value;
          cons_acquire<ST_G2 + kb>(sbase, L);
          wg_fence();
          static_for<0, 4>([&](auto K) {
            constexpr int k = K.value;
            wgmma_n128<kb == 0 && k == 0, 0>(acc2, B[kb & 1][k], st_desc<ST_G2 + kb, 2048, 8192, 1024, 1>(k));
            wgmma_n64<kb == 0 && k == 0, 64>(acc2, B[kb & 1][k], st_desc<ST_G2 + kb, 1024, 4096, 512, 2>(k) + (16384 >> 4));
          });
          wg_commit();
          if constexpr (kb > 0) {
            wg_wait<1>();
            keep4(B[(kb + 1) & 1]);
            cons_release<ST_G2 + kb - 1>(sbase, lane);
          }
          if constexpr (kb + 1 < 8) {
#pragma unroll
            for (int k = 0; k < 4; k++) B[(kb + 1) & 1][k] = lds128(sm + ((kb + 1) * 4 + k) * 2048);
          }
          if constexpr (kb == 3) {
            __syncwarp();
            if (lane == 0) mbar_arrive_remote(mapa(bars + BAR_HREADY + 8 * g, cbit ^ 1));
          }
          if constexpr (kb >= 4) {
            if constexpr (kb == 4) mbar_wait(bars + BAR_HREADY + 8 * g, L);
            st_async128(hdst + (2 * kb - 8) * 2048, hs[2 * kb - 8], hbar1);
            st_async128(hdst + (2 * kb - 7) * 2048, hs[2 * kb - 7], hbar1);
          }
        });
        wg_wait<0>();
        TS(11 + 20 * L);
        fence_acc(acc2);
        keep4(B[1]);
        cons_release<ST_G2 + 7>(sbase, lane);
#pragma unroll
        for (int s = 0; s < 4; s++) hs[8 + s] = glu8<32>(&acc2[8 * s], cl, ch);
#pragma unroll
        for (int s = 0; s < 2; s++) hs[12 + s] = glu8<16>(&acc2[64 + 8 * s], cl, ch);
      }
      {
        PHASE_VARS;
        TS(12 + 20 * L);
        const uint32_t hdst = mapa(areg + t128 * 16, cbit ^ 1);
        const uint32_t hbar2 = mapa(bars + BAR_HRECV + 16 * g + 8, cbit ^ 1);
        uint4* pd = g_arena + c * ARENA + AR_PART + (((slab * 2 + cbit) * 4 + ca) * 16) * 32 + lane;
        const uint4* ps = g_arena + c * ARENA + AR_PART + (((j * 2 + g) * 4) * 16 + 4 * w) * 32 + lane;
        auto fetch_partials = [&]() {
#pragma unroll
          for (int src = 0; src < 4; src++)
#pragma unroll
            for (int k = 0; k < 4; k++) cp_async16(areg + t128 * 16 + (14 + 4 * src + k) * 2048, ps + src * (16 * 32) + k * 32);
        };
        uint4 hb[7];
        float a0[32], a1[32], a2[32], a3[32];
        auto publish = [&](float (&a)[32], int q, int s0, int s1) {
#pragma unroll
          for (int s = s0; s < s1; s++) {
            uint4 o = pack8(&a[8 * s]);
            o.x = set_tag(o.x, tag);
            st_ll(pd + (4 * q + s) * 32, o);
          }
        };
        static_for<0, 16>([&](auto I) {
          constexpr int i = I.value, q = dn_q(i), par = dn_par(i), kh = dn_kh(i);
          auto mm = [&](auto K) {
            constexpr int k = decltype(K)::value;
            constexpr bool init = (k == 0 && par == 0 && kh == 0);
            constexpr uint64_t db = st_desc<ST_DN + i, 2048, 8192, 1024, 1>(k);
            if constexpr (q == 0) { if constexpr (par) wgmma_n64<init, 0>(a0, hb[k], db); else wgmma_n64<init, 0>(a0, hs[7 * kh + k], db); }
            if constexpr (q == 1) { if constexpr (par) wgmma_n64<init, 0>(a1, hb[k], db); else wgmma_n64<init, 0>(a1, hs[7 * kh + k], db); }
            if constexpr (q == 2) { if constexpr (par) wgmma_n64<init, 0>(a2, hb[k], db); else wgmma_n64<init, 0>(a2, hs[7 * kh + k], db); }
            if constexpr (q == 3) { if constexpr (par) wgmma_n64<init, 0>(a3, hb[k], db); else wgmma_n64<init, 0>(a3, hs[7 * kh + k], db); }
          };
          cons_acquire<ST_DN + i>(sbase, L);
          wg_fence();
          mm(IC<0>{}); mm(IC<1>{}); mm(IC<2>{}); mm(IC<3>{}); mm(IC<4>{}); mm(IC<5>{}); mm(IC<6>{});
          wg_commit();
          if constexpr (i > 0) { wg_wait<1>(); cons_release<ST_DN + i - 1>(sbase, lane); }
          if constexpr (i < 3) {
            st_async128(hdst + (8 + 2 * i) * 2048, hs[8 + 2 * i], hbar2);
            st_async128(hdst + (9 + 2 * i) * 2048, hs[9 + 2 * i], hbar2);
          }
          constexpr int n = i + 1;
          if constexpr (n < 16 && dn_par(n) && n != 4 && n != 7) {
            if constexpr (n == 2) { mbar_wait(bars + BAR_HRECV + 16 * g, L); TS(13 + 20 * L); }
            if constexpr (n == 6) { mbar_wait(bars + BAR_HRECV + 16 * g + 8, L); TS(14 + 20 * L); }
#pragma unroll
            for (int k = 0; k < 7; k++) { if constexpr (n != 2) keep(hb[k]); hb[k] = lds128(areg + t128 * 16 + (7 * dn_kh(n) + k) * 2048); }
          }
          if constexpr (i == 7) { fence_acc(a0); publish(a0, 0, 0, 4); }
          if constexpr (i == 8) { fence_acc(a1); publish(a1, 1, 0, 2); }
          if constexpr (i == 9) publish(a1, 1, 2, 4);
          if constexpr (i == 12) { fence_acc(a2); publish(a2, 2, 0, 2); }
          if constexpr (i == 13) publish(a2, 2, 2, 4);
          if constexpr (i == 10) { if (w == 0) fetch_partials(); }
          if constexpr (i == 12) { if (w == 1) fetch_partials(); }
        });
        wg_wait<0>();
        TS(15 + 20 * L);
        fence_acc(a3);
#pragma unroll
        for (int k = 0; k < 7; k++) { keep(hb[k]); keep(hs[7 + k]); }
        cons_release<NSTAGE - 1>(sbase, lane);
        publish(a3, 3, 0, 4);
        if (w >= 2) { cold_delay(L); fetch_partials(); }
      }
      {
        PHASE_VARS;
        const uint4* xq = g_arena + c * ARENA + AR_XRAW + ((j) * 32 + 4 * warp) * 32 + lane;
        const uint4* ps = g_arena + c * ARENA + AR_PART + (((j * 2 + g) * 4) * 16 + 4 * w) * 32 + lane;
        uint4 xr[4], P[4][4];
        float v[32];
        load_pk<4>(xr, xq);
        cp_wait_all();
#pragma unroll
        for (int k = 0; k < 16; k++) P[k >> 2][k & 3] = lds128(areg + t128 * 16 + (14 + k) * 2048);
        for (uint32_t n = 0; !ok_pk<16>(&P[0][0], tag) && n < SPIN_LIMIT; n++) {
#pragma unroll
          for (int src = 0; src < 4; src++) load_pk<4>(P[src], ps + src * (16 * 32));
        }
        TS(16 + 20 * L);
        ensure_pk<4>(xr, xq, 0u);
#pragma unroll
        for (int i = 0; i < 4; i++) {
          v[8 * i + 0] = bf_lo(xr[i].x); v[8 * i + 1] = bf_hi(xr[i].x); v[8 * i + 2] = bf_lo(xr[i].y); v[8 * i + 3] = bf_hi(xr[i].y);
          v[8 * i + 4] = bf_lo(xr[i].z); v[8 * i + 5] = bf_hi(xr[i].z); v[8 * i + 6] = bf_lo(xr[i].w); v[8 * i + 7] = bf_hi(xr[i].w);
          float d[8] = {0, 0, 0, 0, 0, 0, 0, 0};
#pragma unroll
          for (int src = 0; src < 4; src++) {
            const uint4 p = P[src][i];
            d[0] += bf_lo(p.x); d[1] += bf_hi(p.x); d[2] += bf_lo(p.y); d[3] += bf_hi(p.y);
            d[4] += bf_lo(p.z); d[5] += bf_hi(p.z); d[6] += bf_lo(p.w); d[7] += bf_hi(p.w);
          }
#pragma unroll
          for (int k = 0; k < 8; k++) v[8 * i + k] += d[k];
        }
        if (L == 0) {
          owner_ln_publish(sbase, v, 1u, 0u, xraw);
        } else {
#pragma unroll
          for (int i = 0; i < 4; i++) xraw[i] = make_uint4(0, 0, 0, 0);
          uint32_t* op = reinterpret_cast<uint32_t*>(out + (size_t)(slab_row0(c, j >> 2, j & 3) + 2 * qr) * 512 + warp * 64 + qc * 2);
#pragma unroll
          for (int i = 0; i < 4; i++) {
            op[i * 8] = pack2(v[8 * i], v[8 * i + 1]);
            op[16 * 256 + i * 8] = pack2(v[8 * i + 2], v[8 * i + 3]);
            op[i * 8 + 4] = pack2(v[8 * i + 4], v[8 * i + 5]);
            op[16 * 256 + i * 8 + 4] = pack2(v[8 * i + 6], v[8 * i + 7]);
          }
        }
      }
      TS(17 + 20 * L);
      if (L == 0) { STOP_AT(3); }
    }
    TG(62);
    asm volatile("barrier.cluster.arrive.release.aligned;\nbarrier.cluster.wait.acquire.aligned; // consumer" ::: "memory");
    TG(63);
  }
}

typedef CUresult (*EncodeFn)(CUtensorMap*, CUtensorMapDataType, cuuint32_t, void*, const cuuint64_t*, const cuuint64_t*,
                             const cuuint32_t*, const cuuint32_t*, CUtensorMapInterleave, CUtensorMapSwizzle,
                             CUtensorMapL2promotion, CUtensorMapFloatOOBfill);

void encode(EncodeFn fn, CUtensorMap* m, int rank, const void* base, const cuuint64_t* dims, const cuuint64_t* strides,
            const cuuint32_t* box, CUtensorMapSwizzle sw) {
  cuuint32_t es[5] = {1, 1, 1, 1, 1};
  fn(m, CU_TENSOR_MAP_DATA_TYPE_BFLOAT16, (cuuint32_t)rank, const_cast<void*>(base), dims, strides, box, es,
     CU_TENSOR_MAP_INTERLEAVE_NONE, sw, CU_TENSOR_MAP_L2_PROMOTION_L2_128B, CU_TENSOR_MAP_FLOAT_OOB_FILL_NONE);
}

}

extern "C" void kernel_launch(void* const* d_in, const int* in_sizes, int n_in, void* d_out, int out_size) {
  (void)in_sizes; (void)n_in; (void)out_size;
  const __nv_bfloat16* x = (const __nv_bfloat16*)d_in[0];
  const char* wqkv = (const char*)d_in[1];
  const char* wo = (const char*)d_in[2];
  const char* wg = (const char*)d_in[4];
  const char* wu = (const char*)d_in[5];
  const char* wd = (const char*)d_in[6];

  static EncodeFn fn = nullptr;
  if (!fn) {
    void* p = nullptr;
    cudaDriverEntryPointQueryResult st;
    cudaGetDriverEntryPoint("cuTensorMapEncodeTiled", &p, cudaEnableDefault, &st);
    fn = (EncodeFn)p;
    cudaFuncSetAttribute(fused_kernel, cudaFuncAttributeMaxDynamicSharedMemorySize, SMEM_BYTES);
  }
  CUtensorMap m_qkv, m_wo, m_gu2, m_gu1, m_guh, m_wd112, m_wd80, m_wd32;
  {
    cuuint64_t dims[3] = {512, 512, 3}, str[2] = {3072, 1024};
    cuuint32_t box[3] = {64, 64, 3};
    encode(fn, &m_qkv, 3, wqkv, dims, str, box, CU_TENSOR_MAP_SWIZZLE_128B);
  }
  {
    cuuint64_t dims[2] = {512, 512}, str[1] = {1024};
    cuuint32_t box[2] = {64, 128};
    encode(fn, &m_wo, 2, wo, dims, str, box, CU_TENSOR_MAP_SWIZZLE_128B);
  }
  {
    const char* lo = wg < wu ? wg : wu;
    cuuint64_t diff = (cuuint64_t)(wg < wu ? wu - wg : wg - wu);
    cuuint64_t dims[4] = {1792, 512, 2, 2}, str[3] = {3584, diff, 128};
    cuuint32_t box2[4] = {64, 64, 2, 2}, box1[4] = {64, 64, 2, 1}, boxh[3] = {32, 64, 2};
    encode(fn, &m_gu2, 4, lo, dims, str, box2, CU_TENSOR_MAP_SWIZZLE_128B);
    encode(fn, &m_gu1, 4, lo, dims, str, box1, CU_TENSOR_MAP_SWIZZLE_128B);
    encode(fn, &m_guh, 3, lo, dims, str, boxh, CU_TENSOR_MAP_SWIZZLE_64B);
  }
  {
    cuuint64_t dims[2] = {512, 1792}, str[1] = {1024};
    cuuint32_t b112[2] = {64, 112}, b80[2] = {64, 80}, b32[2] = {64, 32};
    encode(fn, &m_wd112, 2, wd, dims, str, b112, CU_TENSOR_MAP_SWIZZLE_128B);
    encode(fn, &m_wd80, 2, wd, dims, str, b80, CU_TENSOR_MAP_SWIZZLE_128B);
    encode(fn, &m_wd32, 2, wd, dims, str, b32, CU_TENSOR_MAP_SWIZZLE_128B);
  }
  cudaLaunchConfig_t cfg = {};
  cfg.gridDim = dim3(128);
  cfg.blockDim = dim3(NTHREADS);
  cfg.dynamicSmemBytes = SMEM_BYTES;
  cfg.stream = cudaStreamPerThread;
  cudaLaunchAttribute at[1];
  at[0].id = cudaLaunchAttributeClusterDimension;
  at[0].val.clusterDim.x = 2; at[0].val.clusterDim.y = 1; at[0].val.clusterDim.z = 1;
  cfg.attrs = at; cfg.numAttrs = 1;
  cudaLaunchKernelEx(&cfg, fused_kernel, m_qkv, m_wo, m_gu2, m_gu1, m_guh, m_wd112, m_wd80, m_wd32, x, (__nv_bfloat16*)d_out
  );
}
```

```cpp
#include <cuda_runtime.h>
#include <cuda_bf16.h>
#include <cuda.h>
#include <stdint.h>

namespace {

constexpr int NTHREADS = 384;
constexpr int GRAN = 8192;
constexpr int NGRAN = 12;
constexpr int SM_AREG = NGRAN * GRAN;
constexpr int SM_MISC = SM_AREG + 131072;
constexpr int SM_TSTAT = SM_MISC + 256;
constexpr int SMEM_BYTES = SM_TSTAT + 1024;
constexpr int BAR_FULL = 0, BAR_EMPTY = 96, BAR_HRECV = 192, BAR_HREADY = 224;

constexpr int AR_XN = 0, AR_XRAW = 8192, AR_O = 16384, AR_STATS = 24576, AR_HALO = 25088, AR_PART = 33280, ARENA = 66048;
__device__ __align__(1024) uint4 g_arena[16 * ARENA];

#define TS(n)
#define TG(n)
#define OPAQUE(x) asm volatile("" : "+r"(x))
#define PHASE_VARS                                                                                   \
  int tid_ = threadIdx.x, bid_ = blockIdx.x;                                                         \
  OPAQUE(tid_); OPAQUE(bid_);                                                                        \
  const int lane = tid_ & 31, warp = tid_ >> 5, g = warp >> 2, w = warp & 3, t128 = tid_ & 127;      \
  const int qr = lane >> 2, qc = lane & 3, slab = warp;                                              \
  const int c = bid_ >> 3, j = bid_ & 7, ca = j >> 1, cbit = j & 1;                                  \
  const uint32_t areg = sbase + SM_AREG + g * 65536;                                                 \
  (void)g; (void)j; (void)w; (void)t128; (void)qr; (void)qc; (void)slab; (void)c; (void)ca; (void)cbit; (void)areg; (void)lane
#define STOP_AT(n)
#define PSTOP_AT(n)

__device__ __forceinline__ uint32_t smem_u32(const void* p) { return (uint32_t)__cvta_generic_to_shared(p); }
__device__ __forceinline__ void mbar_init(uint32_t bar, uint32_t cnt) {
  asm volatile("mbarrier.init.shared::cta.b64 [%0], %1;" ::"r"(bar), "r"(cnt) : "memory");
}
__device__ __forceinline__ void mbar_expect_tx(uint32_t bar, uint32_t bytes) {
  asm volatile("mbarrier.arrive.expect_tx.shared::cta.b64 _, [%0], %1;" ::"r"(bar), "r"(bytes) : "memory");
}
__device__ __forceinline__ void mbar_arrive(uint32_t bar) {
  asm volatile("mbarrier.arrive.shared::cta.b64 _, [%0];" ::"r"(bar) : "memory");
}
__device__ __forceinline__ void mbar_arrive_remote(uint32_t cluster_addr) {
  asm volatile("mbarrier.arrive.relaxed.cluster.shared::cluster.b64 _, [%0];" ::"r"(cluster_addr) : "memory");
}
__device__ __forceinline__ bool mbar_try(uint32_t bar, uint32_t parity) {
  uint32_t ok;
  asm volatile("{\n.reg .pred p;\nmbarrier.try_wait.parity.shared::cta.b64 p, [%1], %2;\nselp.u32 %0, 1, 0, p;\n}"
               : "=r"(ok) : "r"(bar), "r"(parity) : "memory");
  return ok != 0;
}
constexpr uint32_t SPIN_LIMIT = 1u << 16;
constexpr uint32_t SMEM_ORIGIN = 1024;
__device__ __forceinline__ void mbar_wait(uint32_t bar, uint32_t parity) {
  for (uint32_t n = 0; !mbar_try(bar, parity) && n < SPIN_LIMIT; n++) {}
}
__device__ __forceinline__ uint32_t mapa(uint32_t addr, uint32_t rank) {
  uint32_t r;
  asm volatile("mapa.shared::cluster.u32 %0, %1, %2;" : "=r"(r) : "r"(addr), "r"(rank));
  return r;
}

__device__ __forceinline__ void tma_2d(uint32_t dst, const CUtensorMap* m, uint32_t bar, int c0, int c1) {
  asm volatile("cp.async.bulk.tensor.2d.shared::cluster.global.mbarrier::complete_tx::bytes [%0], [%1, {%3, %4}], [%2];"
               ::"r"(dst), "l"(m), "r"(bar), "r"(c0), "r"(c1) : "memory");
}
__device__ __forceinline__ void tma_3d(uint32_t dst, const CUtensorMap* m, uint32_t bar, int c0, int c1, int c2) {
  asm volatile("cp.async.bulk.tensor.3d.shared::cluster.global.mbarrier::complete_tx::bytes [%0], [%1, {%3, %4, %5}], [%2];"
               ::"r"(dst), "l"(m), "r"(bar), "r"(c0), "r"(c1), "r"(c2) : "memory");
}
__device__ __forceinline__ void tma_4d(uint32_t dst, const CUtensorMap* m, uint32_t bar, int c0, int c1, int c2, int c3) {
  asm volatile("cp.async.bulk.tensor.4d.shared::cluster.global.mbarrier::complete_tx::bytes [%0], [%1, {%3, %4, %5, %6}], [%2];"
               ::"r"(dst), "l"(m), "r"(bar), "r"(c0), "r"(c1), "r"(c2), "r"(c3) : "memory");
}

__device__ __forceinline__ uint4 ld_ll(const uint4* p) {
  uint4 v;
  asm volatile("ld.relaxed.gpu.global.v4.u32 {%0,%1,%2,%3}, [%4];" : "=r"(v.x), "=r"(v.y), "=r"(v.z), "=r"(v.w) : "l"(p) : "memory");
  return v;
}
__device__ __forceinline__ void st_ll(uint4* p, uint4 v) {
  asm volatile("st.relaxed.gpu.global.v4.u32 [%0], {%1,%2,%3,%4};" ::"l"(p), "r"(v.x), "r"(v.y), "r"(v.z), "r"(v.w) : "memory");
}
__device__ __forceinline__ uint4 lds128(uint32_t a) {
  uint4 v;
  asm volatile("ld.shared.v4.u32 {%0,%1,%2,%3}, [%4];" : "=r"(v.x), "=r"(v.y), "=r"(v.z), "=r"(v.w) : "r"(a) : "memory");
  return v;
}
__device__ __forceinline__ void sts128(uint32_t a, uint4 v) {
  asm volatile("st.shared.v4.u32 [%0], {%1,%2,%3,%4};" ::"r"(a), "r"(v.x), "r"(v.y), "r"(v.z), "r"(v.w) : "memory");
}
__device__ __forceinline__ void st_async128(uint32_t cluster_addr, uint4 v, uint32_t cluster_bar) {
  asm volatile("st.async.weak.shared::cluster.mbarrier::complete_tx::bytes.v4.b32 [%0], {%1,%2,%3,%4}, [%5];"
               ::"r"(cluster_addr), "r"(v.x), "r"(v.y), "r"(v.z), "r"(v.w), "r"(cluster_bar) : "memory");
}
__device__ __forceinline__ uint32_t pack2(float lo, float hi) {
  uint32_t r;
  asm("cvt.rn.bf16x2.f32 %0, %1, %2;" : "=r"(r) : "f"(hi), "f"(lo));
  return r;
}
__device__ __forceinline__ float bf_lo(uint32_t w) { return __uint_as_float(w << 16); }
__device__ __forceinline__ float bf_hi(uint32_t w) { return __uint_as_float(w & 0xffff0000u); }
__device__ __forceinline__ uint32_t set_tag(uint32_t w, uint32_t tag) { return (w & ~1u) | tag; }
__device__ __forceinline__ uint32_t movm(uint32_t a) {
  uint32_t d;
  asm("movmatrix.sync.aligned.m8n8.trans.b16 %0, %1;" : "=r"(d) : "r"(a));
  return d;
}
__device__ __forceinline__ void mma1688(float (&d)[4], uint32_t a0, uint32_t a1, uint32_t b0) {
  asm("mma.sync.aligned.m16n8k8.row.col.f32.bf16.bf16.f32 {%0,%1,%2,%3}, {%4,%5}, {%6}, {%0,%1,%2,%3};"
      : "+f"(d[0]), "+f"(d[1]), "+f"(d[2]), "+f"(d[3])
      : "r"(a0), "r"(a1), "r"(b0));
}
__device__ __forceinline__ void mma16816_z(float (&d)[4], const uint4& a, uint32_t b0, uint32_t b1) {
  asm("mma.sync.aligned.m16n8k16.row.col.f32.bf16.bf16.f32 {%0,%1,%2,%3}, {%4,%5,%6,%7}, {%8,%9}, {%10,%10,%10,%10};"
      : "=f"(d[0]), "=f"(d[1]), "=f"(d[2]), "=f"(d[3])
      : "r"(a.x), "r"(a.y), "r"(a.z), "r"(a.w), "r"(b0), "r"(b1), "f"(0.f));
}
__device__ __forceinline__ float ex2(float x) {
  float y;
  asm("ex2.approx.ftz.f32 %0, %1;" : "=f"(y) : "f"(x));
  return y;
}
__device__ __forceinline__ float rcp(float x) {
  float y;
  asm("rcp.approx.ftz.f32 %0, %1;" : "=f"(y) : "f"(x));
  return y;
}
__device__ __forceinline__ void cp_async16(uint32_t dst, const void* src) {
  asm volatile("cp.async.cg.shared.global [%0], [%1], 16;" ::"r"(dst), "l"(src) : "memory");
}
__device__ __forceinline__ void cp_wait_all() { asm volatile("cp.async.wait_all;" ::: "memory"); }
template <int N> __device__ __forceinline__ void cp_wait() { asm volatile("cp.async.wait_group %0;" ::"n"(N) : "memory"); }
__device__ __forceinline__ void bar_wg(int id) { asm volatile("bar.sync %0, 128;" ::"r"(id) : "memory"); }
__device__ __forceinline__ void spin_for(uint32_t clks) {
  const uint32_t t0 = (uint32_t)clock();
  while ((uint32_t)clock() - t0 < clks) {}
}
#define D_XN0 1200
#define D_XN1 500
#define D_HALO0 1200
#define D_HALO1 500
#define D_O0 1200
#define D_O1 500
#define D_ST0 1200
#define D_ST1 500
#define D_PT0 1200
#define D_PT1 500
__device__ __forceinline__ void wg_fence() { asm volatile("wgmma.fence.sync.aligned;" ::: "memory"); }
__device__ __forceinline__ void wg_commit() { asm volatile("wgmma.commit_group.sync.aligned;" ::: "memory"); }
template <int N> __device__ __forceinline__ void wg_wait() { asm volatile("wgmma.wait_group.sync.aligned %0;" ::"n"(N) : "memory"); }
__device__ __forceinline__ void keep(const uint4& a) { asm volatile("" ::"r"(a.x), "r"(a.y), "r"(a.z), "r"(a.w) : "memory"); }
template <int T> __device__ __forceinline__ void zero_acc(float (&d)[T]) {
#pragma unroll
  for (int i = 0; i < T; i++) d[i] = 0.f;
}
template <int T> __device__ __forceinline__ void fence_acc(float (&d)[T]) {
#pragma unroll
  for (int i = 0; i < T; i++) asm volatile("" : "+f"(d[i])::"memory");
}

template <int O, int T> __device__ __forceinline__ void wgmma_rs_n64(float (&d)[T], const uint4& a, uint64_t db) {
  asm volatile("{\n.reg .pred p;\nsetp.ne.b32 p, 1, 0;\n"
    "wgmma.mma_async.sync.aligned.m64n64k16.f32.bf16.bf16 "
    "{%0, %1, %2, %3, %4, %5, %6, %7, %8, %9, %10, %11, %12, %13, %14, %15, "
    "%16, %17, %18, %19, %20, %21, %22, %23, %24, %25, %26, %27, %28, %29, %30, %31}, "
    "{%32, %33, %34, %35}, %36, p, 1, 1, 1;\n}\n"
    : "+f"(d[O + 0]), "+f"(d[O + 1]), "+f"(d[O + 2]), "+f"(d[O + 3]), "+f"(d[O + 4]), "+f"(d[O + 5]), "+f"(d[O + 6]), "+f"(d[O + 7]),
      "+f"(d[O + 8]), "+f"(d[O + 9]), "+f"(d[O + 10]), "+f"(d[O + 11]), "+f"(d[O + 12]), "+f"(d[O + 13]), "+f"(d[O + 14]), "+f"(d[O + 15]),
      "+f"(d[O + 16]), "+f"(d[O + 17]), "+f"(d[O + 18]), "+f"(d[O + 19]), "+f"(d[O + 20]), "+f"(d[O + 21]), "+f"(d[O + 22]), "+f"(d[O + 23]),
      "+f"(d[O + 24]), "+f"(d[O + 25]), "+f"(d[O + 26]), "+f"(d[O + 27]), "+f"(d[O + 28]), "+f"(d[O + 29]), "+f"(d[O + 30]), "+f"(d[O + 31])
    : "r"(a.x), "r"(a.y), "r"(a.z), "r"(a.w), "l"(db));
}
template <int O, int T> __device__ __forceinline__ void wgmma_rs_n64_init(float (&d)[T], const uint4& a, uint64_t db) {
  asm volatile("{\n.reg .pred p;\nsetp.ne.b32 p, 0, 0;\n"
    "wgmma.mma_async.sync.aligned.m64n64k16.f32.bf16.bf16 "
    "{%0, %1, %2, %3, %4, %5, %6, %7, %8, %9, %10, %11, %12, %13, %14, %15, "
    "%16, %17, %18, %19, %20, %21, %22, %23, %24, %25, %26, %27, %28, %29, %30, %31}, "
    "{%32, %33, %34, %35}, %36, p, 1, 1, 1;\n}\n"
    : "=f"(d[O + 0]), "=f"(d[O + 1]), "=f"(d[O + 2]), "=f"(d[O + 3]), "=f"(d[O + 4]), "=f"(d[O + 5]), "=f"(d[O + 6]), "=f"(d[O + 7]),
      "=f"(d[O + 8]), "=f"(d[O + 9]), "=f"(d[O + 10]), "=f"(d[O + 11]), "=f"(d[O + 12]), "=f"(d[O + 13]), "=f"(d[O + 14]), "=f"(d[O + 15]),
      "=f"(d[O + 16]), "=f"(d[O + 17]), "=f"(d[O + 18]), "=f"(d[O + 19]), "=f"(d[O + 20]), "=f"(d[O + 21]), "=f"(d[O + 22]), "=f"(d[O + 23]),
      "=f"(d[O + 24]), "=f"(d[O + 25]), "=f"(d[O + 26]), "=f"(d[O + 27]), "=f"(d[O + 28]), "=f"(d[O + 29]), "=f"(d[O + 30]), "=f"(d[O + 31])
    : "r"(a.x), "r"(a.y), "r"(a.z), "r"(a.w), "l"(db));
}
template <bool INIT, int O, int T> __device__ __forceinline__ void wgmma_n64(float (&d)[T], const uint4& a, uint64_t db) {
  if constexpr (INIT) wgmma_rs_n64_init<O>(d, a, db); else wgmma_rs_n64<O>(d, a, db);
}
template <int O, int T> __device__ __forceinline__ void wgmma_rs_n128(float (&d)[T], const uint4& a, uint64_t db) {
  asm volatile("{\n.reg .pred p;\nsetp.ne.b32 p, 1, 0;\n"
    "wgmma.mma_async.sync.aligned.m64n128k16.f32.bf16.bf16 "
    "{%0, %1, %2, %3, %4, %5, %6, %7, %8, %9, %10, %11, %12, %13, %14, %15, "
    "%16, %17, %18, %19, %20, %21, %22, %23, %24, %25, %26, %27, %28, %29, %30, %31, "
    "%32, %33, %34, %35, %36, %37, %38, %39, %40, %41, %42, %43, %44, %45, %46, %47, "
    "%48, %49, %50, %51, %52, %53, %54, %55, %56, %57, %58, %59, %60, %61, %62, %63}, "
    "{%64, %65, %66, %67}, %68, p, 1, 1, 1;\n}\n"
    : "+f"(d[O + 0]), "+f"(d[O + 1]), "+f"(d[O + 2]), "+f"(d[O + 3]), "+f"(d[O + 4]), "+f"(d[O + 5]), "+f"(d[O + 6]), "+f"(d[O + 7]),
      "+f"(d[O + 8]), "+f"(d[O + 9]), "+f"(d[O + 10]), "+f"(d[O + 11]), "+f"(d[O + 12]), "+f"(d[O + 13]), "+f"(d[O + 14]), "+f"(d[O + 15]),
      "+f"(d[O + 16]), "+f"(d[O + 17]), "+f"(d[O + 18]), "+f"(d[O + 19]), "+f"(d[O + 20]), "+f"(d[O + 21]), "+f"(d[O + 22]), "+f"(d[O + 23]),
      "+f"(d[O + 24]), "+f"(d[O + 25]), "+f"(d[O + 26]), "+f"(d[O + 27]), "+f"(d[O + 28]), "+f"(d[O + 29]), "+f"(d[O + 30]), "+f"(d[O + 31]),
      "+f"(d[O + 32]), "+f"(d[O + 33]), "+f"(d[O + 34]), "+f"(d[O + 35]), "+f"(d[O + 36]), "+f"(d[O + 37]), "+f"(d[O + 38]), "+f"(d[O + 39]),
      "+f"(d[O + 40]), "+f"(d[O + 41]), "+f"(d[O + 42]), "+f"(d[O + 43]), "+f"(d[O + 44]), "+f"(d[O + 45]), "+f"(d[O + 46]), "+f"(d[O + 47]),
      "+f"(d[O + 48]), "+f"(d[O + 49]), "+f"(d[O + 50]), "+f"(d[O + 51]), "+f"(d[O + 52]), "+f"(d[O + 53]), "+f"(d[O + 54]), "+f"(d[O + 55]),
      "+f"(d[O + 56]), "+f"(d[O + 57]), "+f"(d[O + 58]), "+f"(d[O + 59]), "+f"(d[O + 60]), "+f"(d[O + 61]), "+f"(d[O + 62]), "+f"(d[O + 63])
    : "r"(a.x), "r"(a.y), "r"(a.z), "r"(a.w), "l"(db));
}
template <int O, int T> __device__ __forceinline__ void wgmma_rs_n128_init(float (&d)[T], const uint4& a, uint64_t db) {
  asm volatile("{\n.reg .pred p;\nsetp.ne.b32 p, 0, 0;\n"
    "wgmma.mma_async.sync.aligned.m64n128k16.f32.bf16.bf16 "
    "{%0, %1, %2, %3, %4, %5, %6, %7, %8, %9, %10, %11, %12, %13, %14, %15, "
    "%16, %17, %18, %19, %20, %21, %22, %23, %24, %25, %26, %27, %28, %29, %30, %31, "
    "%32, %33, %34, %35, %36, %37, %38, %39, %40, %41, %42, %43, %44, %45, %46, %47, "
    "%48, %49, %50, %51, %52, %53, %54, %55, %56, %57, %58, %59, %60, %61, %62, %63}, "
    "{%64, %65, %66, %67}, %68, p, 1, 1, 1;\n}\n"
    : "=f"(d[O + 0]), "=f"(d[O + 1]), "=f"(d[O + 2]), "=f"(d[O + 3]), "=f"(d[O + 4]), "=f"(d[O + 5]), "=f"(d[O + 6]), "=f"(d[O + 7]),
      "=f"(d[O + 8]), "=f"(d[O + 9]), "=f"(d[O + 10]), "=f"(d[O + 11]), "=f"(d[O + 12]), "=f"(d[O + 13]), "=f"(d[O + 14]), "=f"(d[O + 15]),
      "=f"(d[O + 16]), "=f"(d[O + 17]), "=f"(d[O + 18]), "=f"(d[O + 19]), "=f"(d[O + 20]), "=f"(d[O + 21]), "=f"(d[O + 22]), "=f"(d[O + 23]),
      "=f"(d[O + 24]), "=f"(d[O + 25]), "=f"(d[O + 26]), "=f"(d[O + 27]), "=f"(d[O + 28]), "=f"(d[O + 29]), "=f"(d[O + 30]), "=f"(d[O + 31]),
      "=f"(d[O + 32]), "=f"(d[O + 33]), "=f"(d[O + 34]), "=f"(d[O + 35]), "=f"(d[O + 36]), "=f"(d[O + 37]), "=f"(d[O + 38]), "=f"(d[O + 39]),
      "=f"(d[O + 40]), "=f"(d[O + 41]), "=f"(d[O + 42]), "=f"(d[O + 43]), "=f"(d[O + 44]), "=f"(d[O + 45]), "=f"(d[O + 46]), "=f"(d[O + 47]),
      "=f"(d[O + 48]), "=f"(d[O + 49]), "=f"(d[O + 50]), "=f"(d[O + 51]), "=f"(d[O + 52]), "=f"(d[O + 53]), "=f"(d[O + 54]), "=f"(d[O + 55]),
      "=f"(d[O + 56]), "=f"(d[O + 57]), "=f"(d[O + 58]), "=f"(d[O + 59]), "=f"(d[O + 60]), "=f"(d[O + 61]), "=f"(d[O + 62]), "=f"(d[O + 63])
    : "r"(a.x), "r"(a.y), "r"(a.z), "r"(a.w), "l"(db));
}
template <bool INIT, int O, int T> __device__ __forceinline__ void wgmma_n128(float (&d)[T], const uint4& a, uint64_t db) {
  if constexpr (INIT) wgmma_rs_n128_init<O>(d, a, db); else wgmma_rs_n128<O>(d, a, db);
}
template <int O, int T> __device__ __forceinline__ void wgmma_rs_n192(float (&d)[T], const uint4& a, uint64_t db) {
  asm volatile("{\n.reg .pred p;\nsetp.ne.b32 p, 1, 0;\n"
    "wgmma.mma_async.sync.aligned.m64n192k16.f32.bf16.bf16 "
    "{%0, %1, %2, %3, %4, %5, %6, %7, %8, %9, %10, %11, %12, %13, %14, %15, "
    "%16, %17, %18, %19, %20, %21, %22, %23, %24, %25, %26, %27, %28, %29, %30, %31, "
    "%32, %33, %34, %35, %36, %37, %38, %39, %40, %41, %42, %43, %44, %45, %46, %47, "
    "%48, %49, %50, %51, %52, %53, %54, %55, %56, %57, %58, %59, %60, %61, %62, %63, "
    "%64, %65, %66, %67, %68, %69, %70, %71, %72, %73, %74, %75, %76, %77, %78, %79, "
    "%80, %81, %82, %83, %84, %85, %86, %87, %88, %89, %90, %91, %92, %93, %94, %95}, "
    "{%96, %97, %98, %99}, %100, p, 1, 1, 1;\n}\n"
    : "+f"(d[O + 0]), "+f"(d[O + 1]), "+f"(d[O + 2]), "+f"(d[O + 3]), "+f"(d[O + 4]), "+f"(d[O + 5]), "+f"(d[O + 6]), "+f"(d[O + 7]),
      "+f"(d[O + 8]), "+f"(d[O + 9]), "+f"(d[O + 10]), "+f"(d[O + 11]), "+f"(d[O + 12]), "+f"(d[O + 13]), "+f"(d[O + 14]), "+f"(d[O + 15]),
      "+f"(d[O + 16]), "+f"(d[O + 17]), "+f"(d[O + 18]), "+f"(d[O + 19]), "+f"(d[O + 20]), "+f"(d[O + 21]), "+f"(d[O + 22]), "+f"(d[O + 23]),
      "+f"(d[O + 24]), "+f"(d[O + 25]), "+f"(d[O + 26]), "+f"(d[O + 27]), "+f"(d[O + 28]), "+f"(d[O + 29]), "+f"(d[O + 30]), "+f"(d[O + 31]),
      "+f"(d[O + 32]), "+f"(d[O + 33]), "+f"(d[O + 34]), "+f"(d[O + 35]), "+f"(d[O + 36]), "+f"(d[O + 37]), "+f"(d[O + 38]), "+f"(d[O + 39]),
      "+f"(d[O + 40]), "+f"(d[O + 41]), "+f"(d[O + 42]), "+f"(d[O + 43]), "+f"(d[O + 44]), "+f"(d[O + 45]), "+f"(d[O + 46]), "+f"(d[O + 47]),
      "+f"(d[O + 48]), "+f"(d[O + 49]), "+f"(d[O + 50]), "+f"(d[O + 51]), "+f"(d[O + 52]), "+f"(d[O + 53]), "+f"(d[O + 54]), "+f"(d[O + 55]),
      "+f"(d[O + 56]), "+f"(d[O + 57]), "+f"(d[O + 58]), "+f"(d[O + 59]), "+f"(d[O + 60]), "+f"(d[O + 61]), "+f"(d[O + 62]), "+f"(d[O + 63]),
      "+f"(d[O + 64]), "+f"(d[O + 65]), "+f"(d[O + 66]), "+f"(d[O + 67]), "+f"(d[O + 68]), "+f"(d[O + 69]), "+f"(d[O + 70]), "+f"(d[O + 71]),
      "+f"(d[O + 72]), "+f"(d[O + 73]), "+f"(d[O + 74]), "+f"(d[O + 75]), "+f"(d[O + 76]), "+f"(d[O + 77]), "+f"(d[O + 78]), "+f"(d[O + 79]),
      "+f"(d[O + 80]), "+f"(d[O + 81]), "+f"(d[O + 82]), "+f"(d[O + 83]), "+f"(d[O + 84]), "+f"(d[O + 85]), "+f"(d[O + 86]), "+f"(d[O + 87]),
      "+f"(d[O + 88]), "+f"(d[O + 89]), "+f"(d[O + 90]), "+f"(d[O + 91]), "+f"(d[O + 92]), "+f"(d[O + 93]), "+f"(d[O + 94]), "+f"(d[O + 95])
    : "r"(a.x), "r"(a.y), "r"(a.z), "r"(a.w), "l"(db));
}
template <int O, int T> __device__ __forceinline__ void wgmma_rs_n192_init(float (&d)[T], const uint4& a, uint64_t db) {
  asm volatile("{\n.reg .pred p;\nsetp.ne.b32 p, 0, 0;\n"
    "wgmma.mma_async.sync.aligned.m64n192k16.f32.bf16.bf16 "
    "{%0, %1, %2, %3, %4, %5, %6, %7, %8, %9, %10, %11, %12, %13, %14, %15, "
    "%16, %17, %18, %19, %20, %21, %22, %23, %24, %25, %26, %27, %28, %29, %30, %31, "
    "%32, %33, %34, %35, %36, %37, %38, %39, %40, %41, %42, %43, %44, %45, %46, %47, "
    "%48, %49, %50, %51, %52, %53, %54, %55, %56, %57, %58, %59, %60, %61, %62, %63, "
    "%64, %65, %66, %67, %68, %69, %70, %71, %72, %73, %74, %75, %76, %77, %78, %79, "
    "%80, %81, %82, %83, %84, %85, %86, %87, %88, %89, %90, %91, %92, %93, %94, %95}, "
    "{%96, %97, %98, %99}, %100, p, 1, 1, 1;\n}\n"
    : "=f"(d[O + 0]), "=f"(d[O + 1]), "=f"(d[O + 2]), "=f"(d[O + 3]), "=f"(d[O + 4]), "=f"(d[O + 5]), "=f"(d[O + 6]), "=f"(d[O + 7]),
      "=f"(d[O + 8]), "=f"(d[O + 9]), "=f"(d[O + 10]), "=f"(d[O + 11]), "=f"(d[O + 12]), "=f"(d[O + 13]), "=f"(d[O + 14]), "=f"(d[O + 15]),
      "=f"(d[O + 16]), "=f"(d[O + 17]), "=f"(d[O + 18]), "=f"(d[O + 19]), "=f"(d[O + 20]), "=f"(d[O + 21]), "=f"(d[O + 22]), "=f"(d[O + 23]),
      "=f"(d[O + 24]), "=f"(d[O + 25]), "=f"(d[O + 26]), "=f"(d[O + 27]), "=f"(d[O + 28]), "=f"(d[O + 29]), "=f"(d[O + 30]), "=f"(d[O + 31]),
      "=f"(d[O + 32]), "=f"(d[O + 33]), "=f"(d[O + 34]), "=f"(d[O + 35]), "=f"(d[O + 36]), "=f"(d[O + 37]), "=f"(d[O + 38]), "=f"(d[O + 39]),
      "=f"(d[O + 40]), "=f"(d[O + 41]), "=f"(d[O + 42]), "=f"(d[O + 43]), "=f"(d[O + 44]), "=f"(d[O + 45]), "=f"(d[O + 46]), "=f"(d[O + 47]),
      "=f"(d[O + 48]), "=f"(d[O + 49]), "=f"(d[O + 50]), "=f"(d[O + 51]), "=f"(d[O + 52]), "=f"(d[O + 53]), "=f"(d[O + 54]), "=f"(d[O + 55]),
      "=f"(d[O + 56]), "=f"(d[O + 57]), "=f"(d[O + 58]), "=f"(d[O + 59]), "=f"(d[O + 60]), "=f"(d[O + 61]), "=f"(d[O + 62]), "=f"(d[O + 63]),
      "=f"(d[O + 64]), "=f"(d[O + 65]), "=f"(d[O + 66]), "=f"(d[O + 67]), "=f"(d[O + 68]), "=f"(d[O + 69]), "=f"(d[O + 70]), "=f"(d[O + 71]),
      "=f"(d[O + 72]), "=f"(d[O + 73]), "=f"(d[O + 74]), "=f"(d[O + 75]), "=f"(d[O + 76]), "=f"(d[O + 77]), "=f"(d[O + 78]), "=f"(d[O + 79]),
      "=f"(d[O + 80]), "=f"(d[O + 81]), "=f"(d[O + 82]), "=f"(d[O + 83]), "=f"(d[O + 84]), "=f"(d[O + 85]), "=f"(d[O + 86]), "=f"(d[O + 87]),
      "=f"(d[O + 88]), "=f"(d[O + 89]), "=f"(d[O + 90]), "=f"(d[O + 91]), "=f"(d[O + 92]), "=f"(d[O + 93]), "=f"(d[O + 94]), "=f"(d[O + 95])
    : "r"(a.x), "r"(a.y), "r"(a.z), "r"(a.w), "l"(db));
}
template <bool INIT, int O, int T> __device__ __forceinline__ void wgmma_n192(float (&d)[T], const uint4& a, uint64_t db) {
  if constexpr (INIT) wgmma_rs_n192_init<O>(d, a, db); else wgmma_rs_n192<O>(d, a, db);
}
template <int O, int T> __device__ __forceinline__ void wgmma_rs_n256(float (&d)[T], const uint4& a, uint64_t db) {
  asm volatile("{\n.reg .pred p;\nsetp.ne.b32 p, 1, 0;\n"
    "wgmma.mma_async.sync.aligned.m64n256k16.f32.bf16.bf16 "
    "{%0, %1, %2, %3, %4, %5, %6, %7, %8, %9, %10, %11, %12, %13, %14, %15, "
    "%16, %17, %18, %19, %20, %21, %22, %23, %24, %25, %26, %27, %28, %29, %30, %31, "
    "%32, %33, %34, %35, %36, %37, %38, %39, %40, %41, %42, %43, %44, %45, %46, %47, "
    "%48, %49, %50, %51, %52, %53, %54, %55, %56, %57, %58, %59, %60, %61, %62, %63, "
    "%64, %65, %66, %67, %68, %69, %70, %71, %72, %73, %74, %75, %76, %77, %78, %79, "
    "%80, %81, %82, %83, %84, %85, %86, %87, %88, %89, %90, %91, %92, %93, %94, %95, "
    "%96, %97, %98, %99, %100, %101, %102, %103, %104, %105, %106, %107, %108, %109, %110, %111, "
    "%112, %113, %114, %115, %116, %117, %118, %119, %120, %121, %122, %123, %124, %125, %126, %127}, "
    "{%128, %129, %130, %131}, %132, p, 1, 1, 1;\n}\n"
    : "+f"(d[O + 0]), "+f"(d[O + 1]), "+f"(d[O + 2]), "+f"(d[O + 3]), "+f"(d[O + 4]), "+f"(d[O + 5]), "+f"(d[O + 6]), "+f"(d[O + 7]),
      "+f"(d[O + 8]), "+f"(d[O + 9]), "+f"(d[O + 10]), "+f"(d[O + 11]), "+f"(d[O + 12]), "+f"(d[O + 13]), "+f"(d[O + 14]), "+f"(d[O + 15]),
      "+f"(d[O + 16]), "+f"(d[O + 17]), "+f"(d[O + 18]), "+f"(d[O + 19]), "+f"(d[O + 20]), "+f"(d[O + 21]), "+f"(d[O + 22]), "+f"(d[O + 23]),
      "+f"(d[O + 24]), "+f"(d[O + 25]), "+f"(d[O + 26]), "+f"(d[O + 27]), "+f"(d[O + 28]), "+f"(d[O + 29]), "+f"(d[O + 30]), "+f"(d[O + 31]),
      "+f"(d[O + 32]), "+f"(d[O + 33]), "+f"(d[O + 34]), "+f"(d[O + 35]), "+f"(d[O + 36]), "+f"(d[O + 37]), "+f"(d[O + 38]), "+f"(d[O + 39]),
      "+f"(d[O + 40]), "+f"(d[O + 41]), "+f"(d[O + 42]), "+f"(d[O + 43]), "+f"(d[O + 44]), "+f"(d[O + 45]), "+f"(d[O + 46]), "+f"(d[O + 47]),
      "+f"(d[O + 48]), "+f"(d[O + 49]), "+f"(d[O + 50]), "+f"(d[O + 51]), "+f"(d[O + 52]), "+f"(d[O + 53]), "+f"(d[O + 54]), "+f"(d[O + 55]),
      "+f"(d[O + 56]), "+f"(d[O + 57]), "+f"(d[O + 58]), "+f"(d[O + 59]), "+f"(d[O + 60]), "+f"(d[O + 61]), "+f"(d[O + 62]), "+f"(d[O + 63]),
      "+f"(d[O + 64]), "+f"(d[O + 65]), "+f"(d[O + 66]), "+f"(d[O + 67]), "+f"(d[O + 68]), "+f"(d[O + 69]), "+f"(d[O + 70]), "+f"(d[O + 71]),
      "+f"(d[O + 72]), "+f"(d[O + 73]), "+f"(d[O + 74]), "+f"(d[O + 75]), "+f"(d[O + 76]), "+f"(d[O + 77]), "+f"(d[O + 78]), "+f"(d[O + 79]),
      "+f"(d[O + 80]), "+f"(d[O + 81]), "+f"(d[O + 82]), "+f"(d[O + 83]), "+f"(d[O + 84]), "+f"(d[O + 85]), "+f"(d[O + 86]), "+f"(d[O + 87]),
      "+f"(d[O + 88]), "+f"(d[O + 89]), "+f"(d[O + 90]), "+f"(d[O + 91]), "+f"(d[O + 92]), "+f"(d[O + 93]), "+f"(d[O + 94]), "+f"(d[O + 95]),
      "+f"(d[O + 96]), "+f"(d[O + 97]), "+f"(d[O + 98]), "+f"(d[O + 99]), "+f"(d[O + 100]), "+f"(d[O + 101]), "+f"(d[O + 102]), "+f"(d[O + 103]),
      "+f"(d[O + 104]), "+f"(d[O + 105]), "+f"(d[O + 106]), "+f"(d[O + 107]), "+f"(d[O + 108]), "+f"(d[O + 109]), "+f"(d[O + 110]), "+f"(d[O + 111]),
      "+f"(d[O + 112]), "+f"(d[O + 113]), "+f"(d[O + 114]), "+f"(d[O + 115]), "+f"(d[O + 116]), "+f"(d[O + 117]), "+f"(d[O + 118]), "+f"(d[O + 119]),
      "+f"(d[O + 120]), "+f"(d[O + 121]), "+f"(d[O + 122]), "+f"(d[O + 123]), "+f"(d[O + 124]), "+f"(d[O + 125]), "+f"(d[O + 126]), "+f"(d[O + 127])
    : "r"(a.x), "r"(a.y), "r"(a.z), "r"(a.w), "l"(db));
}
template <int O, int T> __device__ __forceinline__ void wgmma_rs_n256_init(float (&d)[T], const uint4& a, uint64_t db) {
  asm volatile("{\n.reg .pred p;\nsetp.ne.b32 p, 0, 0;\n"
    "wgmma.mma_async.sync.aligned.m64n256k16.f32.bf16.bf16 "
    "{%0, %1, %2, %3, %4, %5, %6, %7, %8, %9, %10, %11, %12, %13, %14, %15, "
    "%16, %17, %18, %19, %20, %21, %22, %23, %24, %25, %26, %27, %28, %29, %30, %31, "
    "%32, %33, %34, %35, %36, %37, %38, %39, %40, %41, %42, %43, %44, %45, %46, %47, "
    "%48, %49, %50, %51, %52, %53, %54, %55, %56, %57, %58, %59, %60, %61, %62, %63, "
    "%64, %65, %66, %67, %68, %69, %70, %71, %72, %73, %74, %75, %76, %77, %78, %79, "
    "%80, %81, %82, %83, %84, %85, %86, %87, %88, %89, %90, %91, %92, %93, %94, %95, "
    "%96, %97, %98, %99, %100, %101, %102, %103, %104, %105, %106, %107, %108, %109, %110, %111, "
    "%112, %113, %114, %115, %116, %117, %118, %119, %120, %121, %122, %123, %124, %125, %126, %127}, "
    "{%128, %129, %130, %131}, %132, p, 1, 1, 1;\n}\n"
    : "=f"(d[O + 0]), "=f"(d[O + 1]), "=f"(d[O + 2]), "=f"(d[O + 3]), "=f"(d[O + 4]), "=f"(d[O + 5]), "=f"(d[O + 6]), "=f"(d[O + 7]),
      "=f"(d[O + 8]), "=f"(d[O + 9]), "=f"(d[O + 10]), "=f"(d[O + 11]), "=f"(d[O + 12]), "=f"(d[O + 13]), "=f"(d[O + 14]), "=f"(d[O + 15]),
      "=f"(d[O + 16]), "=f"(d[O + 17]), "=f"(d[O + 18]), "=f"(d[O + 19]), "=f"(d[O + 20]), "=f"(d[O + 21]), "=f"(d[O + 22]), "=f"(d[O + 23]),
      "=f"(d[O + 24]), "=f"(d[O + 25]), "=f"(d[O + 26]), "=f"(d[O + 27]), "=f"(d[O + 28]), "=f"(d[O + 29]), "=f"(d[O + 30]), "=f"(d[O + 31]),
      "=f"(d[O + 32]), "=f"(d[O + 33]), "=f"(d[O + 34]), "=f"(d[O + 35]), "=f"(d[O + 36]), "=f"(d[O + 37]), "=f"(d[O + 38]), "=f"(d[O + 39]),
      "=f"(d[O + 40]), "=f"(d[O + 41]), "=f"(d[O + 42]), "=f"(d[O + 43]), "=f"(d[O + 44]), "=f"(d[O + 45]), "=f"(d[O + 46]), "=f"(d[O + 47]),
      "=f"(d[O + 48]), "=f"(d[O + 49]), "=f"(d[O + 50]), "=f"(d[O + 51]), "=f"(d[O + 52]), "=f"(d[O + 53]), "=f"(d[O + 54]), "=f"(d[O + 55]),
      "=f"(d[O + 56]), "=f"(d[O + 57]), "=f"(d[O + 58]), "=f"(d[O + 59]), "=f"(d[O + 60]), "=f"(d[O + 61]), "=f"(d[O + 62]), "=f"(d[O + 63]),
      "=f"(d[O + 64]), "=f"(d[O + 65]), "=f"(d[O + 66]), "=f"(d[O + 67]), "=f"(d[O + 68]), "=f"(d[O + 69]), "=f"(d[O + 70]), "=f"(d[O + 71]),
      "=f"(d[O + 72]), "=f"(d[O + 73]), "=f"(d[O + 74]), "=f"(d[O + 75]), "=f"(d[O + 76]), "=f"(d[O + 77]), "=f"(d[O + 78]), "=f"(d[O + 79]),
      "=f"(d[O + 80]), "=f"(d[O + 81]), "=f"(d[O + 82]), "=f"(d[O + 83]), "=f"(d[O + 84]), "=f"(d[O + 85]), "=f"(d[O + 86]), "=f"(d[O + 87]),
      "=f"(d[O + 88]), "=f"(d[O + 89]), "=f"(d[O + 90]), "=f"(d[O + 91]), "=f"(d[O + 92]), "=f"(d[O + 93]), "=f"(d[O + 94]), "=f"(d[O + 95]),
      "=f"(d[O + 96]), "=f"(d[O + 97]), "=f"(d[O + 98]), "=f"(d[O + 99]), "=f"(d[O + 100]), "=f"(d[O + 101]), "=f"(d[O + 102]), "=f"(d[O + 103]),
      "=f"(d[O + 104]), "=f"(d[O + 105]), "=f"(d[O + 106]), "=f"(d[O + 107]), "=f"(d[O + 108]), "=f"(d[O + 109]), "=f"(d[O + 110]), "=f"(d[O + 111]),
      "=f"(d[O + 112]), "=f"(d[O + 113]), "=f"(d[O + 114]), "=f"(d[O + 115]), "=f"(d[O + 116]), "=f"(d[O + 117]), "=f"(d[O + 118]), "=f"(d[O + 119]),
      "=f"(d[O + 120]), "=f"(d[O + 121]), "=f"(d[O + 122]), "=f"(d[O + 123]), "=f"(d[O + 124]), "=f"(d[O + 125]), "=f"(d[O + 126]), "=f"(d[O + 127])
    : "r"(a.x), "r"(a.y), "r"(a.z), "r"(a.w), "l"(db));
}
template <bool INIT, int O, int T> __device__ __forceinline__ void wgmma_n256(float (&d)[T], const uint4& a, uint64_t db) {
  if constexpr (INIT) wgmma_rs_n256_init<O>(d, a, db); else wgmma_rs_n256<O>(d, a, db);
}

template <int N> __device__ __forceinline__ void load_pk(uint4* a, const uint4* p) {
#pragma unroll
  for (int i = 0; i < N; i++) a[i] = ld_ll(p + i * 32);
}
__device__ __forceinline__ uint32_t xor_or(uint32_t a, uint32_t b, uint32_t t) {
  uint32_t r;
  asm("lop3.b32 %0, %1, %2, %3, 0x7E;" : "=r"(r) : "r"(a), "r"(b), "r"(t));
  return r;
}
template <int N> __device__ __forceinline__ bool ok_pk(const uint4* a, uint32_t tag) {
  static_assert(N % 2 == 0, "");
  uint32_t x = xor_or(a[0].x, a[1].x, tag);
#pragma unroll
  for (int i = 2; i < N; i += 2) x |= xor_or(a[i].x, a[i + 1].x, tag);
  return __all_sync(0xffffffffu, (x & 1u) == 0u);
}
template <int N> __device__ __forceinline__ void ensure_pk(uint4* a, const uint4* p, uint32_t tag) {
  if (ok_pk<N>(a, tag)) return;
  uint32_t n = 0;
  do { load_pk<N>(a, p); } while (!ok_pk<N>(a, tag) && ++n < SPIN_LIMIT);
}

constexpr int NSTAGE = 44;
constexpr int ST_WO = 8, ST_G1 = 12, ST_G2 = 20, ST_DN = 28;
__host__ __device__ constexpr int st_len(int s) { return s < ST_WO ? 3 : s < ST_G1 ? 2 : s < ST_G2 ? 4 : s < ST_DN ? 3 : 2; }
__host__ __device__ constexpr int st_g0(int s) {
  int pos = 0, g0 = 0;
  for (int i = 0; i <= s; i++) {
    if (pos + st_len(i) > NGRAN) pos = 0;
    g0 = pos;
    pos += st_len(i);
  }
  return g0;
}
__host__ __device__ constexpr int cnt_first(int g, int s) {
  int n = 0;
  for (int i = 0; i < s; i++) n += (st_g0(i) == g);
  return n;
}
__host__ __device__ constexpr int cnt_cover(int g, int s) {
  int n = 0;
  for (int i = 0; i < s; i++) n += (g >= st_g0(i) && g < st_g0(i) + st_len(i));
  return n;
}
__host__ __device__ constexpr uint32_t flip_mask(int s0, int s1) {
  uint32_t m = 0;
  for (int i = s0; i < s1; i++) m ^= ((1u << st_len(i)) - 1u) << st_g0(i);
  return m;
}
__host__ __device__ constexpr int dn_q(int i) { return i < 3 ? 0 : i < 6 ? 1 : i == 6 ? 0 : i == 7 ? 1 : i < 12 ? 2 : 3; }
__host__ __device__ constexpr int dn_par(int i) { return i < 8 ? (i == 2 || i == 4 || i >= 6) : (i & 1); }
__host__ __device__ constexpr int dn_kh(int i) { return i < 8 ? (i == 1 || i >= 5) : ((i & 3) >= 2); }
template <int I> struct IC { static constexpr int value = I; };
template <int B, int E, typename F> __device__ __forceinline__ void static_for(F&& f) {
  if constexpr (B < E) { f(IC<B>{}); static_for<B + 1, E>(f); }
}
template <int S> __device__ __forceinline__ void cons_acquire(uint32_t sbase, uint32_t L) {
  constexpr int g0 = st_g0(S);
  constexpr uint32_t p0 = cnt_first(g0, S) & 1, odd = cnt_first(g0, NSTAGE) & 1;
  mbar_wait(sbase + SM_MISC + BAR_FULL + 8 * g0, p0 ^ (L & odd));
}
template <int S> __device__ __forceinline__ void cons_release(uint32_t sbase, int lane) {
  if (lane < st_len(S)) mbar_arrive(sbase + SM_MISC + BAR_EMPTY + 8 * st_g0(S) + 8 * lane);
}
__device__ __forceinline__ bool elect_one() {
  uint32_t p;
  asm volatile("{\n.reg .pred P;\nelect.sync _|P, 0xffffffff;\nselp.u32 %0, 1, 0, P;\n}" : "=r"(p));
  return p != 0;
}
struct ProdRing { uint32_t pos, par; };
template <int N> __device__ __forceinline__ uint32_t prod_acquire(uint32_t sbase, ProdRing& r) {
  if (r.pos + N > NGRAN) r.pos = 0;
  const uint32_t g0 = r.pos;
#pragma unroll
  for (uint32_t i = 0; i < N; i++) mbar_wait(sbase + SM_MISC + BAR_EMPTY + 8 * (g0 + i), ((r.par >> (g0 + i)) & 1u) ^ 1u);
  r.par ^= ((1u << N) - 1u) << g0;
  r.pos = g0 + N;
  return g0;
}
template <int S> __device__ __forceinline__ void prod_acquire_static(uint32_t sbase, uint32_t L) {
  constexpr int g0 = st_g0(S);
  static_for<0, st_len(S)>([&](auto I) {
    constexpr int g = g0 + I.value;
    constexpr uint32_t p0 = cnt_cover(g, S) & 1, odd = cnt_cover(g, NSTAGE) & 1;
    mbar_wait(sbase + SM_MISC + BAR_EMPTY + 8 * g, p0 ^ (L & odd) ^ 1u);
  });
}
template <int S, int KSTEP_BYTES, int LBO, int SBO, int SWZ> __device__ __forceinline__ constexpr uint64_t st_desc(int k) {
  return (uint64_t)((SMEM_ORIGIN + st_g0(S) * GRAN + k * KSTEP_BYTES) >> 4) | ((uint64_t)(LBO >> 4) << 16) |
         ((uint64_t)(SBO >> 4) << 32) | ((uint64_t)SWZ << 62);
}

__device__ __forceinline__ void combine_stats(const uint4& p0, const uint4& p1, float& mean_lo, float& rstd_lo, float& mean_hi, float& rstd_hi) {
  float m0 = __uint_as_float(p0.x), q0 = __uint_as_float(p0.y), m0h = __uint_as_float(p0.z), q0h = __uint_as_float(p0.w);
  float m1 = __uint_as_float(p1.x), q1 = __uint_as_float(p1.y), m1h = __uint_as_float(p1.z), q1h = __uint_as_float(p1.w);
  float s = m0 + m1, sh = m0h + m1h;
  s += __shfl_xor_sync(0xffffffffu, s, 1); sh += __shfl_xor_sync(0xffffffffu, sh, 1);
  s += __shfl_xor_sync(0xffffffffu, s, 2); sh += __shfl_xor_sync(0xffffffffu, sh, 2);
  mean_lo = s * 0.125f; mean_hi = sh * 0.125f;
  float d0 = m0 - mean_lo, d1 = m1 - mean_lo, d0h = m0h - mean_hi, d1h = m1h - mean_hi;
  float t = q0 + q1 + 64.f * (d0 * d0 + d1 * d1), th = q0h + q1h + 64.f * (d0h * d0h + d1h * d1h);
  t += __shfl_xor_sync(0xffffffffu, t, 1); th += __shfl_xor_sync(0xffffffffu, th, 1);
  t += __shfl_xor_sync(0xffffffffu, t, 2); th += __shfl_xor_sync(0xffffffffu, th, 2);
  rstd_lo = rsqrtf(t * (1.f / 512.f) + 1e-5f);
  rstd_hi = rsqrtf(th * (1.f / 512.f) + 1e-5f);
}
__device__ __forceinline__ uint4 local_stats(const float (&v)[32]) {
  float s = 0.f, sh = 0.f;
#pragma unroll
  for (int i = 0; i < 4; i++) {
    s += (v[8 * i + 0] + v[8 * i + 1]) + (v[8 * i + 4] + v[8 * i + 5]);
    sh += (v[8 * i + 2] + v[8 * i + 3]) + (v[8 * i + 6] + v[8 * i + 7]);
  }
  s += __shfl_xor_sync(0xffffffffu, s, 1); sh += __shfl_xor_sync(0xffffffffu, sh, 1);
  s += __shfl_xor_sync(0xffffffffu, s, 2); sh += __shfl_xor_sync(0xffffffffu, sh, 2);
  float m = s * (1.f / 64.f), mh = sh * (1.f / 64.f);
  float q = 0.f, qh = 0.f;
#pragma unroll
  for (int i = 0; i < 4; i++) {
    float a = v[8 * i + 0] - m, b = v[8 * i + 1] - m, c = v[8 * i + 4] - m, d = v[8 * i + 5] - m;
    q += (a * a + b * b) + (c * c + d * d);
    float e = v[8 * i + 2] - mh, f = v[8 * i + 3] - mh, g = v[8 * i + 6] - mh, h = v[8 * i + 7] - mh;
    qh += (e * e + f * f) + (g * g + h * h);
  }
  q += __shfl_xor_sync(0xffffffffu, q, 1); qh += __shfl_xor_sync(0xffffffffu, qh, 1);
  q += __shfl_xor_sync(0xffffffffu, q, 2); qh += __shfl_xor_sync(0xffffffffu, qh, 2);
  return make_uint4(__float_as_uint(m), __float_as_uint(q), __float_as_uint(mh), __float_as_uint(qh));
}

__device__ __forceinline__ int slab_row0(int c, int g, int w) { return 1024 * g + 64 * c + 32 * (w >> 1) + (w & 1); }

__device__ __forceinline__ void owner_ln_publish(uint32_t sbase, const float (&v)[32], uint32_t tphase, uint32_t tag_xn, uint4 (&xraw)[4]) {
  PHASE_VARS;
  TS(40 + 4 * tphase);
  uint4 st = local_stats(v);
  if (qc == 0) sts128(sbase + SM_TSTAT + warp * 128 + qr * 16, st);
  uint4* xn = g_arena + c * ARENA + AR_XN + ((j) * 32 + 4 * warp) * 32 + lane;
  TS(41 + 4 * tphase);
  asm volatile("bar.sync 3, 256;" ::: "memory");
  TS(42 + 4 * tphase);
  const uint32_t rd = sbase + SM_TSTAT + qc * 256 + qr * 16;
  uint4 p0 = lds128(rd), p1 = lds128(rd + 128);
  float ml, rl, mh, rh;
  combine_stats(p0, p1, ml, rl, mh, rh);
  const float bl = -ml * rl, bh = -mh * rh;
#pragma unroll
  for (int i = 0; i < 4; i++) {
    uint4 o;
    o.x = set_tag(pack2(fmaf(v[8 * i + 0], rl, bl), fmaf(v[8 * i + 1], rl, bl)), tag_xn);
    o.y = pack2(fmaf(v[8 * i + 2], rh, bh), fmaf(v[8 * i + 3], rh, bh));
    o.z = pack2(fmaf(v[8 * i + 4], rl, bl), fmaf(v[8 * i + 5], rl, bl));
    o.w = pack2(fmaf(v[8 * i + 6], rh, bh), fmaf(v[8 * i + 7], rh, bh));
    st_ll(xn + i * 32, o);
  }
#pragma unroll
  for (int i = 0; i < 4; i++) {
    xraw[i].x = set_tag(pack2(v[8 * i + 0], v[8 * i + 1]), 1u);
    xraw[i].y = pack2(v[8 * i + 2], v[8 * i + 3]);
    xraw[i].z = pack2(v[8 * i + 4], v[8 * i + 5]);
    xraw[i].w = pack2(v[8 * i + 6], v[8 * i + 7]);
  }
}

__device__ __forceinline__ uint4 pack8(const float* a) {
  return make_uint4(pack2(a[0], a[1]), pack2(a[2], a[3]), pack2(a[4], a[5]), pack2(a[6], a[7]));
}
template <int U> __device__ __forceinline__ uint4 glu8(const float* g, float cl, float ch) {
  return make_uint4(pack2(g[0] * cl * g[U], g[1] * cl * g[U + 1]), pack2(g[2] * ch * g[U + 2], g[3] * ch * g[U + 3]),
                    pack2(g[4] * cl * g[U + 4], g[5] * cl * g[U + 5]), pack2(g[6] * ch * g[U + 6], g[7] * ch * g[U + 7]));
}
__device__ __forceinline__ uint32_t hfma2(uint32_t a, uint32_t b, uint32_t c) {
  uint32_t d;
  asm("fma.rn.bf16x2 %0, %1, %2, %3;" : "=r"(d) : "r"(a), "r"(b), "r"(c));
  return d;
}
__device__ __forceinline__ void keep4(const uint4 (&a)[4]) { keep(a[0]); keep(a[1]); keep(a[2]); keep(a[3]); }

#define STAGGER 0

__global__ void __launch_bounds__(NTHREADS, 1)
fused_kernel(const __grid_constant__ CUtensorMap m_qkv, const __grid_constant__ CUtensorMap m_wo,
             const __grid_constant__ CUtensorMap m_gu2, const __grid_constant__ CUtensorMap m_gu1,
             const __grid_constant__ CUtensorMap m_guh, const __grid_constant__ CUtensorMap m_wd112,
             const __grid_constant__ CUtensorMap m_wd80, const __grid_constant__ CUtensorMap m_wd32,
             const __nv_bfloat16* __restrict__ x_in,
             __nv_bfloat16* __restrict__ out
) {
  extern __shared__ __align__(1024) unsigned char smem_raw[];
  const uint32_t sbase = smem_u32(smem_raw);
  const uint32_t bars = sbase + SM_MISC;
  if ((sbase & 0xFFFFFFu) != SMEM_ORIGIN) return;
  TG(60);

  uint32_t xw[16];
  if (threadIdx.x < 256) {
    const int cc = blockIdx.x >> 3, jj = blockIdx.x & 7, ln = threadIdx.x & 31;
    const uint32_t* xp = reinterpret_cast<const uint32_t*>(x_in + (size_t)(slab_row0(cc, jj >> 2, jj & 3) + 2 * (ln >> 2)) * 512 + (threadIdx.x >> 5) * 64 + (ln & 3) * 2);
#pragma unroll
    for (int i = 0; i < 4; i++) {
      xw[4 * i] = __ldg(xp + i * 8); xw[4 * i + 1] = __ldg(xp + 16 * 256 + i * 8);
      xw[4 * i + 2] = __ldg(xp + i * 8 + 4); xw[4 * i + 3] = __ldg(xp + 16 * 256 + i * 8 + 4);
    }
  } else if (threadIdx.x == 256) {
    for (int i = 0; i < NGRAN; i++) { mbar_init(bars + BAR_FULL + 8 * i, 1); mbar_init(bars + BAR_EMPTY + 8 * i, 8); }
    for (int i = 0; i < 4; i++) mbar_init(bars + BAR_HRECV + 8 * i, 1);
    for (int i = 0; i < 2; i++) mbar_init(bars + BAR_HREADY + 8 * i, 4);
    asm volatile("fence.mbarrier_init.release.cluster;" ::: "memory");
  }
  TG(56);
  __syncthreads();
  TG(57);
  asm volatile("barrier.cluster.arrive.relaxed.aligned;" ::: "memory");

  if (threadIdx.x >= 256) {
    asm volatile("setmaxnreg.dec.sync.aligned.u32 40;");
    const int warp = threadIdx.x >> 5;
    const int j = blockIdx.x & 7, b = j & 1;
    if (warp == 8) {
      ProdRing r{0u, 0u};
      const int cb0 = 224 * j + 32 * b, hb0 = 224 * j + 192 * (b ^ 1);
      const int jp = j ^ 1, cbp = 224 * jp + 32 * (b ^ 1), hbp = 224 * jp + 192 * b;
#pragma unroll 1
      for (uint32_t L = 0; L < 2; L++) {
        r.pos = 0;
        PSTOP_AT(L == 0 ? 0 : 3);
#pragma unroll 1
        for (int kb = 0; kb < 8; kb++) {
          const uint32_t g0 = prod_acquire<3>(sbase, r);
          if (elect_one()) {
            mbar_expect_tx(bars + BAR_FULL + 8 * g0, 24576);
            tma_3d(sbase + g0 * GRAN, &m_qkv, bars + BAR_FULL + 8 * g0, 64 * j, 64 * kb, 0);
          }
        }
        PSTOP_AT(10 * L + 1);
#pragma unroll 1
        for (int i = 0; i < 4; i++) {
          const uint32_t g0 = prod_acquire<2>(sbase, r);
          if (elect_one()) {
            mbar_expect_tx(bars + BAR_FULL + 8 * g0, 16384);
            tma_2d(sbase + g0 * GRAN, &m_wo, bars + BAR_FULL + 8 * g0, 64 * j, 128 * i);
          }
        }
        PSTOP_AT(10 * L + 2);
#pragma unroll 1
        for (int kb = 0; kb < 8; kb++) {
          const uint32_t g0 = prod_acquire<4>(sbase, r);
          if (elect_one()) {
            mbar_expect_tx(bars + BAR_FULL + 8 * g0, 32768);
            tma_4d(sbase + g0 * GRAN, &m_gu2, bars + BAR_FULL + 8 * g0, cb0, 64 * ((j + kb) & 7), 0, 0);
          }
        }
#pragma unroll 1
        for (int kb = 0; kb < 8; kb++) {
          const uint32_t g0 = prod_acquire<3>(sbase, r);
          if (elect_one()) {
            mbar_expect_tx(bars + BAR_FULL + 8 * g0, 24576);
            tma_4d(sbase + g0 * GRAN, &m_gu1, bars + BAR_FULL + 8 * g0, cb0 + 128, 64 * ((j + kb) & 7), 0, 0);
            tma_3d(sbase + g0 * GRAN + 16384, &m_guh, bars + BAR_FULL + 8 * g0, hb0, 64 * ((j + kb) & 7), 0);
          }
        }
        static_for<0, 16>([&](auto I) {
          constexpr int i = I.value, g0 = st_g0(ST_DN + i);
          prod_acquire_static<ST_DN + i>(sbase, L);
          if (elect_one()) {
            const uint32_t dst = sbase + g0 * GRAN, fb = bars + BAR_FULL + 8 * g0;
            const int n0 = 256 * b + 64 * dn_q(i);
            mbar_expect_tx(fb, 14336);
            if constexpr (dn_kh(i) == 0) {
              tma_2d(dst, &m_wd112, fb, n0, dn_par(i) ? cbp : cb0);
            } else {
              tma_2d(dst, &m_wd80, fb, n0, (dn_par(i) ? cbp : cb0) + 112);
              tma_2d(dst + 10240, &m_wd32, fb, n0, dn_par(i) ? hbp : hb0);
            }
          }
        });
        r.par ^= flip_mask(ST_DN, NSTAGE);
      }
    }
    __syncwarp();
    asm volatile("barrier.cluster.wait.acquire.aligned; // producer" ::: "memory");
    asm volatile("barrier.cluster.arrive.relaxed.aligned;\nbarrier.cluster.wait.aligned; // producer" ::: "memory");
  } else {
    TG(58);
    asm volatile("setmaxnreg.inc.sync.aligned.u32 232;");
    TS(0);
    TG(61);

    uint4 xraw[4];
    {
      float v[32];
#pragma unroll
      for (int i = 0; i < 16; i++) { v[2 * i] = bf_lo(xw[i]); v[2 * i + 1] = bf_hi(xw[i]); }
      owner_ln_publish(sbase, v, 0u, 1u, xraw);
      asm volatile("barrier.cluster.wait.acquire.aligned; // consumer" ::: "memory");
    }
    STOP_AT(0);
    TS(1);

#pragma unroll 1
    for (uint32_t L = 0; L < 2; L++) {
      const uint32_t tag = L ^ 1;
      {
        PHASE_VARS;
        uint4 qf[4], kf[4], vf[4], pp[4];
        const int blk = 16 * g + c;
        const int pb = blk > 0 ? blk - 1 : 0;
        const uint4* halo_src = g_arena + (pb & 15) * ARENA + AR_HALO + (((((L * 2 + (pb >> 4)) * 8 + j) * 2 + (w & 1)) * 4) * 32) + lane;
        {
          float acc[96];
          uint4 A[3][4];
          const uint4* xs = g_arena + c * ARENA + AR_XN + ((slab) * 32) * 32 + lane;
          bar_wg(1 + g);
          spin_for(L ? D_XN1 : D_XN0);
          load_pk<4>(A[0], xs);
          ensure_pk<4>(A[0], xs, tag);
          TS(2 + 20 * L);
          load_pk<4>(A[1], xs + 128);
          static_for<0, 8>([&](auto I) {
            constexpr int kb = I.value;
            cons_acquire<kb>(sbase, L);
            wg_fence();
            static_for<0, 4>([&](auto K) { constexpr int k = K.value; wgmma_n192<kb == 0 && k == 0, 0>(acc, A[kb % 3][k], st_desc<kb, 2048, 8192, 1024, 1>(k)); });
            wg_commit();
            if constexpr (kb > 0) {
              wg_wait<1>();
              keep4(A[(kb + 2) % 3]);
              cons_release<kb - 1>(sbase, lane);
            }
            if constexpr (kb + 1 < 8) ensure_pk<4>(A[(kb + 1) % 3], xs + (kb + 1) * 128, tag);
            if constexpr (kb + 2 < 8) load_pk<4>(A[(kb + 2) % 3], xs + (kb + 2) * 128);
            if constexpr (kb == 2) {
              uint4* xr = g_arena + c * ARENA + AR_XRAW + ((j) * 32 + 4 * warp) * 32 + lane;
#pragma unroll
              for (int i = 0; i < 4; i++) st_ll(xr + i * 32, xraw[i]);
            }
          });
          wg_wait<0>();
          TS(3 + 20 * L);
          fence_acc(acc);
          keep4(A[1]);
          cons_release<7>(sbase, lane);
#pragma unroll
          for (int h = 0; h < 4; h++) {
            kf[h].y = pack2(acc[32 + 8 * h + 2], acc[32 + 8 * h + 3]); kf[h].w = pack2(acc[32 + 8 * h + 6], acc[32 + 8 * h + 7]);
            vf[h].y = movm(pack2(acc[64 + 8 * h + 2], acc[64 + 8 * h + 3])); vf[h].w = movm(pack2(acc[64 + 8 * h + 6], acc[64 + 8 * h + 7]));
            pp[h] = make_uint4(kf[h].y, kf[h].w, vf[h].y, vf[h].w);
          }
          if (w >= 2 && blk < 31) {
            uint4* hd = g_arena + c * ARENA + AR_HALO + (((((L * 2 + g) * 8 + j) * 2 + (w & 1)) * 4) * 32) + lane;
#pragma unroll
            for (int h = 0; h < 4; h++) { uint4 t = pp[h]; t.x |= 1u; st_ll(hd + h * 32, t); }
          }
#pragma unroll
          for (int h = 0; h < 4; h++) sts128(areg + (28 + h) * 2048 + t128 * 16, pp[h]);
#pragma unroll
          for (int h = 0; h < 4; h++) {
            kf[h].x = pack2(acc[32 + 8 * h], acc[32 + 8 * h + 1]); kf[h].z = pack2(acc[32 + 8 * h + 4], acc[32 + 8 * h + 5]);
            vf[h].x = movm(pack2(acc[64 + 8 * h], acc[64 + 8 * h + 1])); vf[h].z = movm(pack2(acc[64 + 8 * h + 4], acc[64 + 8 * h + 5]));
          }
#pragma unroll
          for (int h = 0; h < 4; h++) qf[h] = pack8(&acc[8 * h]);
        }
        bar_wg(1 + g);
        const bool first = (w < 2) && (blk == 0);
        if (w >= 2) {
#pragma unroll
          for (int h = 0; h < 4; h++) pp[h] = lds128(areg + (28 + h) * 2048 + (t128 - 64) * 16);
        }
        bar_wg(1 + g);
        if (w < 2 && blk > 0) {
          spin_for(L ? D_HALO1 : D_HALO0);
          load_pk<4>(pp, halo_src);
          ensure_pk<4>(pp, halo_src, 1u);
          uint4* hz = const_cast<uint4*>(halo_src);
#pragma unroll
          for (int h = 0; h < 4; h++) st_ll(hz + h * 32, make_uint4(0, 0, 0, 0));
        }
        TS(4 + 20 * L);
        const bool n0 = 2 * qc <= qr, n1 = 2 * qc + 1 <= qr;
        const uint32_t msk = (n0 ? 0xffffu : 0u) | (n1 ? 0xffff0000u : 0u);
        const float sc = 0.25f * 1.4426950408889634f;
        const float NEG = -1e30f;
        uint4* od = g_arena + c * ARENA + AR_O + ((slab) * 32 + 4 * j) * 32 + lane;
        float l0[4], l1[4], h0[4], h1[4], ml[4], mh[4];
#pragma unroll
        for (int h = 0; h < 4; h++) {
          float sp[4], s0[4], s1[4];
          mma16816_z(sp, qf[h], pp[h].x, pp[h].y);
          mma16816_z(s0, qf[h], kf[h].x, kf[h].z);
          mma16816_z(s1, qf[h], kf[h].y, kf[h].w);
          if (first) { sp[0] = NEG; sp[1] = NEG; }
          l0[h] = n0 ? s0[0] : sp[0]; l1[h] = n1 ? s0[1] : sp[1];
          h0[h] = n0 ? s1[2] : s0[2]; h1[h] = n1 ? s1[3] : s0[3];
          ml[h] = fmaxf(l0[h], l1[h]); mh[h] = fmaxf(h0[h], h1[h]);
        }
#pragma unroll
        for (int h = 0; h < 4; h++) { ml[h] = fmaxf(ml[h], __shfl_xor_sync(0xffffffffu, ml[h], 1)); mh[h] = fmaxf(mh[h], __shfl_xor_sync(0xffffffffu, mh[h], 1)); }
#pragma unroll
        for (int h = 0; h < 4; h++) { ml[h] = fmaxf(ml[h], __shfl_xor_sync(0xffffffffu, ml[h], 2)); mh[h] = fmaxf(mh[h], __shfl_xor_sync(0xffffffffu, mh[h], 2)); }
        float sl[4], sh[4];
#pragma unroll
        for (int h = 0; h < 4; h++) {
          const float bl = -ml[h] * sc, bh = -mh[h] * sc;
          l0[h] = ex2(fmaf(l0[h], sc, bl)); l1[h] = ex2(fmaf(l1[h], sc, bl));
          h0[h] = ex2(fmaf(h0[h], sc, bh)); h1[h] = ex2(fmaf(h1[h], sc, bh));
          sl[h] = l0[h] + l1[h]; sh[h] = h0[h] + h1[h];
        }
#pragma unroll
        for (int h = 0; h < 4; h++) { sl[h] += __shfl_xor_sync(0xffffffffu, sl[h], 1); sh[h] += __shfl_xor_sync(0xffffffffu, sh[h], 1); }
#pragma unroll
        for (int h = 0; h < 4; h++) { sl[h] += __shfl_xor_sync(0xffffffffu, sl[h], 2); sh[h] += __shfl_xor_sync(0xffffffffu, sh[h], 2); }
#pragma unroll
        for (int h = 0; h < 4; h++) {
          const float il = rcp(sl[h]), ih = rcp(sh[h]);
          const uint32_t pl = pack2(l0[h] * il, l1[h] * il), ph = pack2(h0[h] * ih, h1[h] * ih);
          const uint4 P = make_uint4(pl & msk, ph & ~msk, 0u, ph & msk);
          float o0[4], o1[4];
          mma16816_z(o0, P, vf[h].x, vf[h].y);
          mma16816_z(o1, P, vf[h].z, vf[h].w);
          mma1688(o0, pl & ~msk, 0u, pp[h].z);
          mma1688(o1, pl & ~msk, 0u, pp[h].w);
          st_ll(od + h * 32, make_uint4(set_tag(pack2(o0[0], o0[1]), tag), pack2(o0[2], o0[3]), pack2(o1[0], o1[1]), pack2(o1[2], o1[3])));
        }
      }
      TS(5 + 20 * L);
      if (L == 0) { STOP_AT(1); } else { STOP_AT(11); }
      uint4 x1own[4];
      {
        PHASE_VARS;
        float acc[32];
        uint4 A[32], xr[4];
        const uint4* os = g_arena + c * ARENA + AR_O + ((slab) * 32) * 32 + lane;
        uint4* xp = g_arena + c * ARENA + AR_XRAW + ((slab) * 32 + 4 * j) * 32 + lane;
        load_pk<4>(xr, xp);
        spin_for(L ? D_O1 : D_O0);
        load_pk<4>(A, os);
        ensure_pk<4>(A, os, tag);
        TS(6 + 20 * L);
        load_pk<28>(A + 4, os + 128);
        static_for<0, 8>([&](auto I) {
          constexpr int kb = I.value;
          if constexpr ((kb & 1) == 0) cons_acquire<ST_WO + kb / 2>(sbase, L);
          if constexpr (kb > 0) ensure_pk<4>(A + 4 * kb, os + kb * 128, tag);
          wg_fence();
          static_for<0, 4>([&](auto K) {
            constexpr int k = K.value;
            wgmma_n64<kb == 0 && k == 0, 0>(acc, A[4 * kb + k], st_desc<ST_WO + kb / 2, 2048, 8192, 1024, 1>(4 * (kb & 1) + k));
          });
          wg_commit();
          if constexpr ((kb & 1) == 0 && kb > 0) { wg_wait<1>(); cons_release<ST_WO + kb / 2 - 1>(sbase, lane); }
        });
        wg_wait<0>();
        TS(7 + 20 * L);
        fence_acc(acc);
#pragma unroll
        for (int k = 0; k < 32; k++) keep(A[k]);
        cons_release<ST_WO + 3>(sbase, lane);
        ensure_pk<4>(xr, xp, 1u);
#pragma unroll
        for (int i = 0; i < 4; i++) {
          acc[8 * i + 0] += bf_lo(xr[i].x); acc[8 * i + 1] += bf_hi(xr[i].x); acc[8 * i + 2] += bf_lo(xr[i].y); acc[8 * i + 3] += bf_hi(xr[i].y);
          acc[8 * i + 4] += bf_lo(xr[i].z); acc[8 * i + 5] += bf_hi(xr[i].z); acc[8 * i + 6] += bf_lo(xr[i].w); acc[8 * i + 7] += bf_hi(xr[i].w);
        }
        uint4 st = local_stats(acc);
        st.x = set_tag(st.x, tag);
        if (qc == 0) st_ll(g_arena + c * ARENA + AR_STATS + (slab * 8 + j) * 8 + qr, st);
#pragma unroll
        for (int i = 0; i < 4; i++) {
          x1own[i] = pack8(&acc[8 * i]);
          x1own[i].x = set_tag(x1own[i].x, 0u);
          st_ll(xp + i * 32, x1own[i]);
        }
      }
      TS(8 + 20 * L);
      if (L == 0) { STOP_AT(2); } else { STOP_AT(12); }
      uint4 hs[14];
      {
        PHASE_VARS;
        float acc[128];
        uint4 A[3][4];
        const uint4* xs = g_arena + c * ARENA + AR_XRAW + ((slab) * 32) * 32 + lane;
        const uint4* sp = g_arena + c * ARENA + AR_STATS + (slab * 8 + 2 * qc) * 8 + qr;
        const uint32_t sm = areg + t128 * 16;
        uint32_t rl2, rh2, bl2, bh2;
        float cl, ch;
        auto xsrc = [&](int p) { return xs + ((j + p) & 7) * 128; };
        {
          uint4 p[2];
#pragma unroll
          for (int k = 0; k < 4; k++) A[0][k] = x1own[k];
          spin_for(L ? D_ST1 : D_ST0);
          p[0] = ld_ll(sp); p[1] = ld_ll(sp + 8);
          load_pk<4>(A[1], xsrc(1));
          for (uint32_t n = 0; !ok_pk<2>(p, tag) && n < SPIN_LIMIT; n++) { p[0] = ld_ll(sp); p[1] = ld_ll(sp + 8); }
          TS(9 + 20 * L);
          float ml, rl, mh, rh;
          combine_stats(p[0], p[1], ml, rl, mh, rh);
          rl2 = pack2(rl, rl); rh2 = pack2(rh, rh);
          const float rlb = bf_lo(rl2), rhb = bf_lo(rh2);
          bl2 = pack2(-ml * rlb, -ml * rlb); bh2 = pack2(-mh * rhb, -mh * rhb);
          cl = rl / rlb; cl *= cl; ch = rh / rhb; ch *= ch;
        }
        auto normalise = [&](uint4 (&xb)[4], int kb) {
#pragma unroll
          for (int k = 0; k < 4; k++) {
            xb[k].x = hfma2(xb[k].x, rl2, bl2); xb[k].y = hfma2(xb[k].y, rh2, bh2);
            xb[k].z = hfma2(xb[k].z, rl2, bl2); xb[k].w = hfma2(xb[k].w, rh2, bh2);
            sts128(sm + (kb * 4 + k) * 2048, xb[k]);
          }
        };
        normalise(A[0], 0);
        static_for<0, 8>([&](auto I) {
          constexpr int kb = I.value;
          cons_acquire<ST_G1 + kb>(sbase, L);
          wg_fence();
          static_for<0, 4>([&](auto K) { constexpr int k = K.value; wgmma_n256<kb == 0 && k == 0, 0>(acc, A[kb % 3][k], st_desc<ST_G1 + kb, 2048, 8192, 1024, 1>(k)); });
          wg_commit();
          if constexpr (kb > 0) {
            wg_wait<1>();
            keep4(A[(kb + 2) % 3]);
            cons_release<ST_G1 + kb - 1>(sbase, lane);
          }
          if constexpr (kb + 1 < 8) ensure_pk<4>(A[(kb + 1) % 3], xsrc(kb + 1), 0u);
          if constexpr (kb + 2 < 8) load_pk<4>(A[(kb + 2) % 3], xsrc(kb + 2));
          if constexpr (kb + 1 < 8) normalise(A[(kb + 1) % 3], kb + 1);
        });
        wg_wait<0>();
        TS(10 + 20 * L);
        fence_acc(acc);
        keep4(A[1]);
        cons_release<ST_G1 + 7>(sbase, lane);
        uint4 B[2][4];
#pragma unroll
        for (int k = 0; k < 4; k++) B[0][k] = lds128(sm + k * 2048);
#pragma unroll
        for (int s = 0; s < 8; s++) hs[s] = glu8<32>(&acc[64 * (s >> 2) + 8 * (s & 3)], cl, ch);
        float acc2[96];
        const uint32_t hdst = mapa(sm, cbit ^ 1);
        const uint32_t hbar1 = mapa(bars + BAR_HRECV + 16 * g, cbit ^ 1);
        if (t128 == 0) { mbar_expect_tx(bars + BAR_HRECV + 16 * g, 8 * 2048); mbar_expect_tx(bars + BAR_HRECV + 16 * g + 8, 6 * 2048); }
        static_for<0, 8>([&](auto I) {
          constexpr int kb = I.value;
          cons_acquire<ST_G2 + kb>(sbase, L);
          wg_fence();
          static_for<0, 4>([&](auto K) {
            constexpr int k = K.value;
            wgmma_n128<kb == 0 && k == 0, 0>(acc2, B[kb & 1][k], st_desc<ST_G2 + kb, 2048, 8192, 1024, 1>(k));
            wgmma_n64<kb == 0 && k == 0, 64>(acc2, B[kb & 1][k], st_desc<ST_G2 + kb, 1024, 4096, 512, 2>(k) + (16384 >> 4));
          });
          wg_commit();
          if constexpr (kb > 0) {
            wg_wait<1>();
            keep4(B[(kb + 1) & 1]);
            cons_release<ST_G2 + kb - 1>(sbase, lane);
          }
          if constexpr (kb + 1 < 8) {
#pragma unroll
            for (int k = 0; k < 4; k++) B[(kb + 1) & 1][k] = lds128(sm + ((kb + 1) * 4 + k) * 2048);
          }
          if constexpr (kb == 3) {
            __syncwarp();
            if (lane == 0) mbar_arrive_remote(mapa(bars + BAR_HREADY + 8 * g, cbit ^ 1));
          }
          if constexpr (kb >= 4) {
            if constexpr (kb == 4) mbar_wait(bars + BAR_HREADY + 8 * g, L);
            st_async128(hdst + (2 * kb - 8) * 2048, hs[2 * kb - 8], hbar1);
            st_async128(hdst + (2 * kb - 7) * 2048, hs[2 * kb - 7], hbar1);
          }
        });
        wg_wait<0>();
        TS(11 + 20 * L);
        fence_acc(acc2);
        keep4(B[1]);
        cons_release<ST_G2 + 7>(sbase, lane);
#pragma unroll
        for (int s = 0; s < 4; s++) hs[8 + s] = glu8<32>(&acc2[8 * s], cl, ch);
#pragma unroll
        for (int s = 0; s < 2; s++) hs[12 + s] = glu8<16>(&acc2[64 + 8 * s], cl, ch);
      }
      {
        PHASE_VARS;
        TS(12 + 20 * L);
        const uint32_t hdst = mapa(areg + t128 * 16, cbit ^ 1);
        const uint32_t hbar2 = mapa(bars + BAR_HRECV + 16 * g + 8, cbit ^ 1);
        uint4* pd = g_arena + c * ARENA + AR_PART + (((slab * 2 + cbit) * 4 + ca) * 16) * 32 + lane;
        const uint4* ps = g_arena + c * ARENA + AR_PART + (((j * 2 + g) * 4) * 16 + 4 * w) * 32 + lane;
        auto fetch_partials = [&]() {
#pragma unroll
          for (int src = 0; src < 4; src++)
#pragma unroll
            for (int k = 0; k < 4; k++) cp_async16(areg + t128 * 16 + (14 + 4 * src + k) * 2048, ps + src * (16 * 32) + k * 32);
        };
        uint4 hb[7];
        float a0[32], a1[32], a2[32], a3[32];
        auto publish = [&](float (&a)[32], int q, int s0, int s1) {
#pragma unroll
          for (int s = s0; s < s1; s++) {
            uint4 o = pack8(&a[8 * s]);
            o.x = set_tag(o.x, tag);
            st_ll(pd + (4 * q + s) * 32, o);
          }
        };
        static_for<0, 16>([&](auto I) {
          constexpr int i = I.value, q = dn_q(i), par = dn_par(i), kh = dn_kh(i);
          auto mm = [&](auto K) {
            constexpr int k = decltype(K)::value;
            constexpr bool init = (k == 0 && par == 0 && kh == 0);
            constexpr uint64_t db = st_desc<ST_DN + i, 2048, 8192, 1024, 1>(k);
            if constexpr (q == 0) { if constexpr (par) wgmma_n64<init, 0>(a0, hb[k], db); else wgmma_n64<init, 0>(a0, hs[7 * kh + k], db); }
            if constexpr (q == 1) { if constexpr (par) wgmma_n64<init, 0>(a1, hb[k], db); else wgmma_n64<init, 0>(a1, hs[7 * kh + k], db); }
            if constexpr (q == 2) { if constexpr (par) wgmma_n64<init, 0>(a2, hb[k], db); else wgmma_n64<init, 0>(a2, hs[7 * kh + k], db); }
            if constexpr (q == 3) { if constexpr (par) wgmma_n64<init, 0>(a3, hb[k], db); else wgmma_n64<init, 0>(a3, hs[7 * kh + k], db); }
          };
          cons_acquire<ST_DN + i>(sbase, L);
          wg_fence();
          mm(IC<0>{}); mm(IC<1>{}); mm(IC<2>{}); mm(IC<3>{}); mm(IC<4>{}); mm(IC<5>{}); mm(IC<6>{});
          wg_commit();
          if constexpr (i > 0) { wg_wait<1>(); cons_release<ST_DN + i - 1>(sbase, lane); }
          if constexpr (i < 3) {
            st_async128(hdst + (8 + 2 * i) * 2048, hs[8 + 2 * i], hbar2);
            st_async128(hdst + (9 + 2 * i) * 2048, hs[9 + 2 * i], hbar2);
          }
          constexpr int n = i + 1;
          if constexpr (n < 16 && dn_par(n) && n != 4 && n != 7) {
            if constexpr (n == 2) { mbar_wait(bars + BAR_HRECV + 16 * g, L); TS(13 + 20 * L); }
            if constexpr (n == 6) { mbar_wait(bars + BAR_HRECV + 16 * g + 8, L); TS(14 + 20 * L); }
#pragma unroll
            for (int k = 0; k < 7; k++) { if constexpr (n != 2) keep(hb[k]); hb[k] = lds128(areg + t128 * 16 + (7 * dn_kh(n) + k) * 2048); }
          }
          if constexpr (i == 7) { fence_acc(a0); publish(a0, 0, 0, 4); }
          if constexpr (i == 8) { fence_acc(a1); publish(a1, 1, 0, 2); }
          if constexpr (i == 9) publish(a1, 1, 2, 4);
          if constexpr (i == 12) { fence_acc(a2); publish(a2, 2, 0, 2); }
          if constexpr (i == 13) publish(a2, 2, 2, 4);
          if constexpr (i == 10) { if (w == 0) fetch_partials(); }
          if constexpr (i == 12) { if (w == 1) fetch_partials(); }
        });
        wg_wait<0>();
        TS(15 + 20 * L);
        fence_acc(a3);
#pragma unroll
        for (int k = 0; k < 7; k++) { keep(hb[k]); keep(hs[7 + k]); }
        cons_release<NSTAGE - 1>(sbase, lane);
        publish(a3, 3, 0, 4);
        if (w >= 2) { spin_for(L ? D_PT1 : D_PT0); fetch_partials(); }
      }
      {
        PHASE_VARS;
        const uint4* xq = g_arena + c * ARENA + AR_XRAW + ((j) * 32 + 4 * warp) * 32 + lane;
        const uint4* ps = g_arena + c * ARENA + AR_PART + (((j * 2 + g) * 4) * 16 + 4 * w) * 32 + lane;
        uint4 xr[4], P[4][4];
        float v[32];
        load_pk<4>(xr, xq);
        cp_wait_all();
#pragma unroll
        for (int k = 0; k < 16; k++) P[k >> 2][k & 3] = lds128(areg + t128 * 16 + (14 + k) * 2048);
        for (uint32_t n = 0; !ok_pk<16>(&P[0][0], tag) && n < SPIN_LIMIT; n++) {
#pragma unroll
          for (int src = 0; src < 4; src++) load_pk<4>(P[src], ps + src * (16 * 32));
        }
        TS(16 + 20 * L);
        ensure_pk<4>(xr, xq, 0u);
#pragma unroll
        for (int i = 0; i < 4; i++) {
          v[8 * i + 0] = bf_lo(xr[i].x); v[8 * i + 1] = bf_hi(xr[i].x); v[8 * i + 2] = bf_lo(xr[i].y); v[8 * i + 3] = bf_hi(xr[i].y);
          v[8 * i + 4] = bf_lo(xr[i].z); v[8 * i + 5] = bf_hi(xr[i].z); v[8 * i + 6] = bf_lo(xr[i].w); v[8 * i + 7] = bf_hi(xr[i].w);
          float d[8] = {0, 0, 0, 0, 0, 0, 0, 0};
#pragma unroll
          for (int src = 0; src < 4; src++) {
            const uint4 p = P[src][i];
            d[0] += bf_lo(p.x); d[1] += bf_hi(p.x); d[2] += bf_lo(p.y); d[3] += bf_hi(p.y);
            d[4] += bf_lo(p.z); d[5] += bf_hi(p.z); d[6] += bf_lo(p.w); d[7] += bf_hi(p.w);
          }
#pragma unroll
          for (int k = 0; k < 8; k++) v[8 * i + k] += d[k];
        }
        if (L == 0) {
          owner_ln_publish(sbase, v, 1u, 0u, xraw);
        } else {
#pragma unroll
          for (int i = 0; i < 4; i++) xraw[i] = make_uint4(0, 0, 0, 0);
          uint32_t* op = reinterpret_cast<uint32_t*>(out + (size_t)(slab_row0(c, j >> 2, j & 3) + 2 * qr) * 512 + warp * 64 + qc * 2);
#pragma unroll
          for (int i = 0; i < 4; i++) {
            op[i * 8] = pack2(v[8 * i], v[8 * i + 1]);
            op[16 * 256 + i * 8] = pack2(v[8 * i + 2], v[8 * i + 3]);
            op[i * 8 + 4] = pack2(v[8 * i + 4], v[8 * i + 5]);
            op[16 * 256 + i * 8 + 4] = pack2(v[8 * i + 6], v[8 * i + 7]);
          }
        }
      }
      TS(17 + 20 * L);
      if (L == 0) { STOP_AT(3); }
    }
    TG(62);
    asm volatile("barrier.cluster.arrive.relaxed.aligned;\nbarrier.cluster.wait.aligned; // consumer" ::: "memory");
    TG(63);
  }
}

typedef CUresult (*EncodeFn)(CUtensorMap*, CUtensorMapDataType, cuuint32_t, void*, const cuuint64_t*, const cuuint64_t*,
                             const cuuint32_t*, const cuuint32_t*, CUtensorMapInterleave, CUtensorMapSwizzle,
                             CUtensorMapL2promotion, CUtensorMapFloatOOBfill);

void encode(EncodeFn fn, CUtensorMap* m, int rank, const void* base, const cuuint64_t* dims, const cuuint64_t* strides,
            const cuuint32_t* box, CUtensorMapSwizzle sw) {
  cuuint32_t es[5] = {1, 1, 1, 1, 1};
  fn(m, CU_TENSOR_MAP_DATA_TYPE_BFLOAT16, (cuuint32_t)rank, const_cast<void*>(base), dims, strides, box, es,
     CU_TENSOR_MAP_INTERLEAVE_NONE, sw, CU_TENSOR_MAP_L2_PROMOTION_L2_128B, CU_TENSOR_MAP_FLOAT_OOB_FILL_NONE);
}

}

extern "C" void kernel_launch(void* const* d_in, const int* in_sizes, int n_in, void* d_out, int out_size) {
  (void)in_sizes; (void)n_in; (void)out_size;
  const __nv_bfloat16* x = (const __nv_bfloat16*)d_in[0];
  const char* wqkv = (const char*)d_in[1];
  const char* wo = (const char*)d_in[2];
  const char* wg = (const char*)d_in[4];
  const char* wu = (const char*)d_in[5];
  const char* wd = (const char*)d_in[6];

  static EncodeFn fn = nullptr;
  if (!fn) {
    void* p = nullptr;
    cudaDriverEntryPointQueryResult st;
    cudaGetDriverEntryPoint("cuTensorMapEncodeTiled", &p, cudaEnableDefault, &st);
    fn = (EncodeFn)p;
    cudaFuncSetAttribute(fused_kernel, cudaFuncAttributeMaxDynamicSharedMemorySize, SMEM_BYTES);
  }
  CUtensorMap m_qkv, m_wo, m_gu2, m_gu1, m_guh, m_wd112, m_wd80, m_wd32;
  {
    cuuint64_t dims[3] = {512, 512, 3}, str[2] = {3072, 1024};
    cuuint32_t box[3] = {64, 64, 3};
    encode(fn, &m_qkv, 3, wqkv, dims, str, box, CU_TENSOR_MAP_SWIZZLE_128B);
  }
  {
    cuuint64_t dims[2] = {512, 512}, str[1] = {1024};
    cuuint32_t box[2] = {64, 128};
    encode(fn, &m_wo, 2, wo, dims, str, box, CU_TENSOR_MAP_SWIZZLE_128B);
  }
  {
    const char* lo = wg < wu ? wg : wu;
    cuuint64_t diff = (cuuint64_t)(wg < wu ? wu - wg : wg - wu);
    cuuint64_t dims[4] = {1792, 512, 2, 2}, str[3] = {3584, diff, 128};
    cuuint32_t box2[4] = {64, 64, 2, 2}, box1[4] = {64, 64, 2, 1}, boxh[3] = {32, 64, 2};
    encode(fn, &m_gu2, 4, lo, dims, str, box2, CU_TENSOR_MAP_SWIZZLE_128B);
    encode(fn, &m_gu1, 4, lo, dims, str, box1, CU_TENSOR_MAP_SWIZZLE_128B);
    encode(fn, &m_guh, 3, lo, dims, str, boxh, CU_TENSOR_MAP_SWIZZLE_64B);
  }
  {
    cuuint64_t dims[2] = {512, 1792}, str[1] = {1024};
    cuuint32_t b112[2] = {64, 112}, b80[2] = {64, 80}, b32[2] = {64, 32};
    encode(fn, &m_wd112, 2, wd, dims, str, b112, CU_TENSOR_MAP_SWIZZLE_128B);
    encode(fn, &m_wd80, 2, wd, dims, str, b80, CU_TENSOR_MAP_SWIZZLE_128B);
    encode(fn, &m_wd32, 2, wd, dims, str, b32, CU_TENSOR_MAP_SWIZZLE_128B);
  }
  cudaLaunchConfig_t cfg = {};
  cfg.gridDim = dim3(128);
  cfg.blockDim = dim3(NTHREADS);
  cfg.dynamicSmemBytes = SMEM_BYTES;
  cfg.stream = cudaStreamPerThread;
  cudaLaunchAttribute at[1];
  at[0].id = cudaLaunchAttributeClusterDimension;
  at[0].val.clusterDim.x = 2; at[0].val.clusterDim.y = 1; at[0].val.clusterDim.z = 1;
  cfg.attrs = at; cfg.numAttrs = 1;
  cudaLaunchKernelEx(&cfg, fused_kernel, m_qkv, m_wo, m_gu2, m_gu1, m_guh, m_wd112, m_wd80, m_wd32, x, (__nv_bfloat16*)d_out
  );
}
```

```cpp
#include <cuda_runtime.h>
#include <cuda_bf16.h>
#include <cuda.h>
#include <stdint.h>

namespace {

constexpr int NTHREADS = 384;
constexpr int GRAN = 8192;
constexpr int NGRAN = 12;
constexpr int SM_AREG = NGRAN * GRAN;
constexpr int SM_MISC = SM_AREG + 131072;
constexpr int SM_TSTAT = SM_MISC + 256;
constexpr int SMEM_BYTES = SM_TSTAT + 1024;
constexpr int BAR_FULL = 0, BAR_EMPTY = 96, BAR_HRECV = 192, BAR_HREADY = 224;

constexpr int AR_XN = 0, AR_XRAW = 8192, AR_O = 16384, AR_STATS = 24576, AR_HALO = 25088, AR_PART = 33280, ARENA = 66048;
__device__ __align__(1024) uint4 g_arena[16 * ARENA];

#define TS(n)
#define TG(n)
#define OPAQUE(x) asm volatile("" : "+r"(x))
#define PHASE_VARS                                                                                   \
  int tid_ = threadIdx.x, bid_ = blockIdx.x;                                                         \
  OPAQUE(tid_); OPAQUE(bid_);                                                                        \
  const int lane = tid_ & 31, warp = tid_ >> 5, g = warp >> 2, w = warp & 3, t128 = tid_ & 127;      \
  const int qr = lane >> 2, qc = lane & 3, slab = warp;                                              \
  const int c = bid_ >> 3, j = bid_ & 7, ca = j >> 1, cbit = j & 1;                                  \
  const uint32_t areg = sbase + SM_AREG + g * 65536;                                                 \
  (void)g; (void)j; (void)w; (void)t128; (void)qr; (void)qc; (void)slab; (void)c; (void)ca; (void)cbit; (void)areg; (void)lane
#define STOP_AT(n)
#define PSTOP_AT(n)

__device__ __forceinline__ uint32_t smem_u32(const void* p) { return (uint32_t)__cvta_generic_to_shared(p); }
__device__ __forceinline__ void mbar_init(uint32_t bar, uint32_t cnt) {
  asm volatile("mbarrier.init.shared::cta.b64 [%0], %1;" ::"r"(bar), "r"(cnt) : "memory");
}
__device__ __forceinline__ void mbar_expect_tx(uint32_t bar, uint32_t bytes) {
  asm volatile("mbarrier.arrive.expect_tx.shared::cta.b64 _, [%0], %1;" ::"r"(bar), "r"(bytes) : "memory");
}
__device__ __forceinline__ void mbar_arrive(uint32_t bar) {
  asm volatile("mbarrier.arrive.shared::cta.b64 _, [%0];" ::"r"(bar) : "memory");
}
__device__ __forceinline__ void mbar_arrive_remote(uint32_t cluster_addr) {
  asm volatile("mbarrier.arrive.relaxed.cluster.shared::cluster.b64 _, [%0];" ::"r"(cluster_addr) : "memory");
}
__device__ __forceinline__ bool mbar_try(uint32_t bar, uint32_t parity) {
  uint32_t ok;
  asm volatile("{\n.reg .pred p;\nmbarrier.try_wait.parity.shared::cta.b64 p, [%1], %2;\nselp.u32 %0, 1, 0, p;\n}"
               : "=r"(ok) : "r"(bar), "r"(parity) : "memory");
  return ok != 0;
}
constexpr uint32_t SPIN_LIMIT = 1u << 16;
constexpr uint32_t SMEM_ORIGIN = 1024;
__device__ __forceinline__ void mbar_wait(uint32_t bar, uint32_t parity) {
  for (uint32_t n = 0; !mbar_try(bar, parity) && n < SPIN_LIMIT; n++) {}
}
__device__ __forceinline__ uint32_t mapa(uint32_t addr, uint32_t rank) {
  uint32_t r;
  asm volatile("mapa.shared::cluster.u32 %0, %1, %2;" : "=r"(r) : "r"(addr), "r"(rank));
  return r;
}

__device__ __forceinline__ void tma_2d(uint32_t dst, const CUtensorMap* m, uint32_t bar, int c0, int c1) {
  asm volatile("cp.async.bulk.tensor.2d.shared::cluster.global.mbarrier::complete_tx::bytes [%0], [%1, {%3, %4}], [%2];"
               ::"r"(dst), "l"(m), "r"(bar), "r"(c0), "r"(c1) : "memory");
}
__device__ __forceinline__ void tma_3d(uint32_t dst, const CUtensorMap* m, uint32_t bar, int c0, int c1, int c2) {
  asm volatile("cp.async.bulk.tensor.3d.shared::cluster.global.mbarrier::complete_tx::bytes [%0], [%1, {%3, %4, %5}], [%2];"
               ::"r"(dst), "l"(m), "r"(bar), "r"(c0), "r"(c1), "r"(c2) : "memory");
}
__device__ __forceinline__ void tma_4d(uint32_t dst, const CUtensorMap* m, uint32_t bar, int c0, int c1, int c2, int c3) {
  asm volatile("cp.async.bulk.tensor.4d.shared::cluster.global.mbarrier::complete_tx::bytes [%0], [%1, {%3, %4, %5, %6}], [%2];"
               ::"r"(dst), "l"(m), "r"(bar), "r"(c0), "r"(c1), "r"(c2), "r"(c3) : "memory");
}

__device__ __forceinline__ uint4 ld_ll(const uint4* p) {
  uint4 v;
  asm volatile("ld.relaxed.gpu.global.v4.u32 {%0,%1,%2,%3}, [%4];" : "=r"(v.x), "=r"(v.y), "=r"(v.z), "=r"(v.w) : "l"(p) : "memory");
  return v;
}
__device__ __forceinline__ void st_ll(uint4* p, uint4 v) {
  asm volatile("st.relaxed.gpu.global.v4.u32 [%0], {%1,%2,%3,%4};" ::"l"(p), "r"(v.x), "r"(v.y), "r"(v.z), "r"(v.w) : "memory");
}
__device__ __forceinline__ uint4 lds128(uint32_t a) {
  uint4 v;
  asm volatile("ld.shared.v4.u32 {%0,%1,%2,%3}, [%4];" : "=r"(v.x), "=r"(v.y), "=r"(v.z), "=r"(v.w) : "r"(a) : "memory");
  return v;
}
__device__ __forceinline__ void sts128(uint32_t a, uint4 v) {
  asm volatile("st.shared.v4.u32 [%0], {%1,%2,%3,%4};" ::"r"(a), "r"(v.x), "r"(v.y), "r"(v.z), "r"(v.w) : "memory");
}
__device__ __forceinline__ void st_async128(uint32_t cluster_addr, uint4 v, uint32_t cluster_bar) {
  asm volatile("st.async.weak.shared::cluster.mbarrier::complete_tx::bytes.v4.b32 [%0], {%1,%2,%3,%4}, [%5];"
               ::"r"(cluster_addr), "r"(v.x), "r"(v.y), "r"(v.z), "r"(v.w), "r"(cluster_bar) : "memory");
}
__device__ __forceinline__ uint32_t pack2(float lo, float hi) {
  uint32_t r;
  asm("cvt.rn.bf16x2.f32 %0, %1, %2;" : "=r"(r) : "f"(hi), "f"(lo));
  return r;
}
__device__ __forceinline__ float bf_lo(uint32_t w) { return __uint_as_float(w << 16); }
__device__ __forceinline__ float bf_hi(uint32_t w) { return __uint_as_float(w & 0xffff0000u); }
__device__ __forceinline__ uint32_t set_tag(uint32_t w, uint32_t tag) { return (w & ~1u) | tag; }
__device__ __forceinline__ uint32_t movm(uint32_t a) {
  uint32_t d;
  asm("movmatrix.sync.aligned.m8n8.trans.b16 %0, %1;" : "=r"(d) : "r"(a));
  return d;
}
__device__ __forceinline__ void mma1688(float (&d)[4], uint32_t a0, uint32_t a1, uint32_t b0) {
  asm("mma.sync.aligned.m16n8k8.row.col.f32.bf16.bf16.f32 {%0,%1,%2,%3}, {%4,%5}, {%6}, {%0,%1,%2,%3};"
      : "+f"(d[0]), "+f"(d[1]), "+f"(d[2]), "+f"(d[3])
      : "r"(a0), "r"(a1), "r"(b0));
}
__device__ __forceinline__ void mma16816_z(float (&d)[4], const uint4& a, uint32_t b0, uint32_t b1) {
  asm("mma.sync.aligned.m16n8k16.row.col.f32.bf16.bf16.f32 {%0,%1,%2,%3}, {%4,%5,%6,%7}, {%8,%9}, {%10,%10,%10,%10};"
      : "=f"(d[0]), "=f"(d[1]), "=f"(d[2]), "=f"(d[3])
      : "r"(a.x), "r"(a.y), "r"(a.z), "r"(a.w), "r"(b0), "r"(b1), "f"(0.f));
}
__device__ __forceinline__ float ex2(float x) {
  float y;
  asm("ex2.approx.ftz.f32 %0, %1;" : "=f"(y) : "f"(x));
  return y;
}
__device__ __forceinline__ float rcp(float x) {
  float y;
  asm("rcp.approx.ftz.f32 %0, %1;" : "=f"(y) : "f"(x));
  return y;
}
__device__ __forceinline__ void cp_async16(uint32_t dst, const void* src) {
  asm volatile("cp.async.cg.shared.global [%0], [%1], 16;" ::"r"(dst), "l"(src) : "memory");
}
__device__ __forceinline__ void cp_wait_all() { asm volatile("cp.async.wait_all;" ::: "memory"); }
template <int N> __device__ __forceinline__ void cp_wait() { asm volatile("cp.async.wait_group %0;" ::"n"(N) : "memory"); }
__device__ __forceinline__ void bar_wg(int id) { asm volatile("bar.sync %0, 128;" ::"r"(id) : "memory"); }
__device__ __forceinline__ void spin_for(uint32_t clks) {
  const uint32_t t0 = (uint32_t)clock();
  while ((uint32_t)clock() - t0 < clks) {}
}
#define D_XN0 1200
#define D_XN1 500
#define D_HALO0 1200
#define D_HALO1 500
#define D_O0 1200
#define D_O1 500
#define D_ST0 1200
#define D_ST1 500
#define D_PT0 1200
#define D_PT1 500
__device__ __forceinline__ void wg_fence() { asm volatile("wgmma.fence.sync.aligned;" ::: "memory"); }
__device__ __forceinline__ void wg_commit() { asm volatile("wgmma.commit_group.sync.aligned;" ::: "memory"); }
template <int N> __device__ __forceinline__ void wg_wait() { asm volatile("wgmma.wait_group.sync.aligned %0;" ::"n"(N) : "memory"); }
__device__ __forceinline__ void keep(const uint4& a) { asm volatile("" ::"r"(a.x), "r"(a.y), "r"(a.z), "r"(a.w) : "memory"); }
template <int T> __device__ __forceinline__ void zero_acc(float (&d)[T]) {
#pragma unroll
  for (int i = 0; i < T; i++) d[i] = 0.f;
}
template <int T> __device__ __forceinline__ void fence_acc(float (&d)[T]) {
#pragma unroll
  for (int i = 0; i < T; i++) asm volatile("" : "+f"(d[i])::"memory");
}

template <int O, int T> __device__ __forceinline__ void wgmma_rs_n64(float (&d)[T], const uint4& a, uint64_t db) {
  asm volatile("{\n.reg .pred p;\nsetp.ne.b32 p, 1, 0;\n"
    "wgmma.mma_async.sync.aligned.m64n64k16.f32.bf16.bf16 "
    "{%0, %1, %2, %3, %4, %5, %6, %7, %8, %9, %10, %11, %12, %13, %14, %15, "
    "%16, %17, %18, %19, %20, %21, %22, %23, %24, %25, %26, %27, %28, %29, %30, %31}, "
    "{%32, %33, %34, %35}, %36, p, 1, 1, 1;\n}\n"
    : "+f"(d[O + 0]), "+f"(d[O + 1]), "+f"(d[O + 2]), "+f"(d[O + 3]), "+f"(d[O + 4]), "+f"(d[O + 5]), "+f"(d[O + 6]), "+f"(d[O + 7]),
      "+f"(d[O + 8]), "+f"(d[O + 9]), "+f"(d[O + 10]), "+f"(d[O + 11]), "+f"(d[O + 12]), "+f"(d[O + 13]), "+f"(d[O + 14]), "+f"(d[O + 15]),
      "+f"(d[O + 16]), "+f"(d[O + 17]), "+f"(d[O + 18]), "+f"(d[O + 19]), "+f"(d[O + 20]), "+f"(d[O + 21]), "+f"(d[O + 22]), "+f"(d[O + 23]),
      "+f"(d[O + 24]), "+f"(d[O + 25]), "+f"(d[O + 26]), "+f"(d[O + 27]), "+f"(d[O + 28]), "+f"(d[O + 29]), "+f"(d[O + 30]), "+f"(d[O + 31])
    : "r"(a.x), "r"(a.y), "r"(a.z), "r"(a.w), "l"(db));
}
template <int O, int T> __device__ __forceinline__ void wgmma_rs_n64_init(float (&d)[T], const uint4& a, uint64_t db) {
  asm volatile("{\n.reg .pred p;\nsetp.ne.b32 p, 0, 0;\n"
    "wgmma.mma_async.sync.aligned.m64n64k16.f32.bf16.bf16 "
    "{%0, %1, %2, %3, %4, %5, %6, %7, %8, %9, %10, %11, %12, %13, %14, %15, "
    "%16, %17, %18, %19, %20, %21, %22, %23, %24, %25, %26, %27, %28, %29, %30, %31}, "
    "{%32, %33, %34, %35}, %36, p, 1, 1, 1;\n}\n"
    : "=f"(d[O + 0]), "=f"(d[O + 1]), "=f"(d[O + 2]), "=f"(d[O + 3]), "=f"(d[O + 4]), "=f"(d[O + 5]), "=f"(d[O + 6]), "=f"(d[O + 7]),
      "=f"(d[O + 8]), "=f"(d[O + 9]), "=f"(d[O + 10]), "=f"(d[O + 11]), "=f"(d[O + 12]), "=f"(d[O + 13]), "=f"(d[O + 14]), "=f"(d[O + 15]),
      "=f"(d[O + 16]), "=f"(d[O + 17]), "=f"(d[O + 18]), "=f"(d[O + 19]), "=f"(d[O + 20]), "=f"(d[O + 21]), "=f"(d[O + 22]), "=f"(d[O + 23]),
      "=f"(d[O + 24]), "=f"(d[O + 25]), "=f"(d[O + 26]), "=f"(d[O + 27]), "=f"(d[O + 28]), "=f"(d[O + 29]), "=f"(d[O + 30]), "=f"(d[O + 31])
    : "r"(a.x), "r"(a.y), "r"(a.z), "r"(a.w), "l"(db));
}
template <bool INIT, int O, int T> __device__ __forceinline__ void wgmma_n64(float (&d)[T], const uint4& a, uint64_t db) {
  if constexpr (INIT) wgmma_rs_n64_init<O>(d, a, db); else wgmma_rs_n64<O>(d, a, db);
}
template <int O, int T> __device__ __forceinline__ void wgmma_rs_n128(float (&d)[T], const uint4& a, uint64_t db) {
  asm volatile("{\n.reg .pred p;\nsetp.ne.b32 p, 1, 0;\n"
    "wgmma.mma_async.sync.aligned.m64n128k16.f32.bf16.bf16 "
    "{%0, %1, %2, %3, %4, %5, %6, %7, %8, %9, %10, %11, %12, %13, %14, %15, "
    "%16, %17, %18, %19, %20, %21, %22, %23, %24, %25, %26, %27, %28, %29, %30, %31, "
    "%32, %33, %34, %35, %36, %37, %38, %39, %40, %41, %42, %43, %44, %45, %46, %47, "
    "%48, %49, %50, %51, %52, %53, %54, %55, %56, %57, %58, %59, %60, %61, %62, %63}, "
    "{%64, %65, %66, %67}, %68, p, 1, 1, 1;\n}\n"
    : "+f"(d[O + 0]), "+f"(d[O + 1]), "+f"(d[O + 2]), "+f"(d[O + 3]), "+f"(d[O + 4]), "+f"(d[O + 5]), "+f"(d[O + 6]), "+f"(d[O + 7]),
      "+f"(d[O + 8]), "+f"(d[O + 9]), "+f"(d[O + 10]), "+f"(d[O + 11]), "+f"(d[O + 12]), "+f"(d[O + 13]), "+f"(d[O + 14]), "+f"(d[O + 15]),
      "+f"(d[O + 16]), "+f"(d[O + 17]), "+f"(d[O + 18]), "+f"(d[O + 19]), "+f"(d[O + 20]), "+f"(d[O + 21]), "+f"(d[O + 22]), "+f"(d[O + 23]),
      "+f"(d[O + 24]), "+f"(d[O + 25]), "+f"(d[O + 26]), "+f"(d[O + 27]), "+f"(d[O + 28]), "+f"(d[O + 29]), "+f"(d[O + 30]), "+f"(d[O + 31]),
      "+f"(d[O + 32]), "+f"(d[O + 33]), "+f"(d[O + 34]), "+f"(d[O + 35]), "+f"(d[O + 36]), "+f"(d[O + 37]), "+f"(d[O + 38]), "+f"(d[O + 39]),
      "+f"(d[O + 40]), "+f"(d[O + 41]), "+f"(d[O + 42]), "+f"(d[O + 43]), "+f"(d[O + 44]), "+f"(d[O + 45]), "+f"(d[O + 46]), "+f"(d[O + 47]),
      "+f"(d[O + 48]), "+f"(d[O + 49]), "+f"(d[O + 50]), "+f"(d[O + 51]), "+f"(d[O + 52]), "+f"(d[O + 53]), "+f"(d[O + 54]), "+f"(d[O + 55]),
      "+f"(d[O + 56]), "+f"(d[O + 57]), "+f"(d[O + 58]), "+f"(d[O + 59]), "+f"(d[O + 60]), "+f"(d[O + 61]), "+f"(d[O + 62]), "+f"(d[O + 63])
    : "r"(a.x), "r"(a.y), "r"(a.z), "r"(a.w), "l"(db));
}
template <int O, int T> __device__ __forceinline__ void wgmma_rs_n128_init(float (&d)[T], const uint4& a, uint64_t db) {
  asm volatile("{\n.reg .pred p;\nsetp.ne.b32 p, 0, 0;\n"
    "wgmma.mma_async.sync.aligned.m64n128k16.f32.bf16.bf16 "
    "{%0, %1, %2, %3, %4, %5, %6, %7, %8, %9, %10, %11, %12, %13, %14, %15, "
    "%16, %17, %18, %19, %20, %21, %22, %23, %24, %25, %26, %27, %28, %29, %30, %31, "
    "%32, %33, %34, %35, %36, %37, %38, %39, %40, %41, %42, %43, %44, %45, %46, %47, "
    "%48, %49, %50, %51, %52, %53, %54, %55, %56, %57, %58, %59, %60, %61, %62, %63}, "
    "{%64, %65, %66, %67}, %68, p, 1, 1, 1;\n}\n"
    : "=f"(d[O + 0]), "=f"(d[O + 1]), "=f"(d[O + 2]), "=f"(d[O + 3]), "=f"(d[O + 4]), "=f"(d[O + 5]), "=f"(d[O + 6]), "=f"(d[O + 7]),
      "=f"(d[O + 8]), "=f"(d[O + 9]), "=f"(d[O + 10]), "=f"(d[O + 11]), "=f"(d[O + 12]), "=f"(d[O + 13]), "=f"(d[O + 14]), "=f"(d[O + 15]),
      "=f"(d[O + 16]), "=f"(d[O + 17]), "=f"(d[O + 18]), "=f"(d[O + 19]), "=f"(d[O + 20]), "=f"(d[O + 21]), "=f"(d[O + 22]), "=f"(d[O + 23]),
      "=f"(d[O + 24]), "=f"(d[O + 25]), "=f"(d[O + 26]), "=f"(d[O + 27]), "=f"(d[O + 28]), "=f"(d[O + 29]), "=f"(d[O + 30]), "=f"(d[O + 31]),
      "=f"(d[O + 32]), "=f"(d[O + 33]), "=f"(d[O + 34]), "=f"(d[O + 35]), "=f"(d[O + 36]), "=f"(d[O + 37]), "=f"(d[O + 38]), "=f"(d[O + 39]),
      "=f"(d[O + 40]), "=f"(d[O + 41]), "=f"(d[O + 42]), "=f"(d[O + 43]), "=f"(d[O + 44]), "=f"(d[O + 45]), "=f"(d[O + 46]), "=f"(d[O + 47]),
      "=f"(d[O + 48]), "=f"(d[O + 49]), "=f"(d[O + 50]), "=f"(d[O + 51]), "=f"(d[O + 52]), "=f"(d[O + 53]), "=f"(d[O + 54]), "=f"(d[O + 55]),
      "=f"(d[O + 56]), "=f"(d[O + 57]), "=f"(d[O + 58]), "=f"(d[O + 59]), "=f"(d[O + 60]), "=f"(d[O + 61]), "=f"(d[O + 62]), "=f"(d[O + 63])
    : "r"(a.x), "r"(a.y), "r"(a.z), "r"(a.w), "l"(db));
}
template <bool INIT, int O, int T> __device__ __forceinline__ void wgmma_n128(float (&d)[T], const uint4& a, uint64_t db) {
  if constexpr (INIT) wgmma_rs_n128_init<O>(d, a, db); else wgmma_rs_n128<O>(d, a, db);
}
template <int O, int T> __device__ __forceinline__ void wgmma_rs_n192(float (&d)[T], const uint4& a, uint64_t db) {
  asm volatile("{\n.reg .pred p;\nsetp.ne.b32 p, 1, 0;\n"
    "wgmma.mma_async.sync.aligned.m64n192k16.f32.bf16.bf16 "
    "{%0, %1, %2, %3, %4, %5, %6, %7, %8, %9, %10, %11, %12, %13, %14, %15, "
    "%16, %17, %18, %19, %20, %21, %22, %23, %24, %25, %26, %27, %28, %29, %30, %31, "
    "%32, %33, %34, %35, %36, %37, %38, %39, %40, %41, %42, %43, %44, %45, %46, %47, "
    "%48, %49, %50, %51, %52, %53, %54, %55, %56, %57, %58, %59, %60, %61, %62, %63, "
    "%64, %65, %66, %67, %68, %69, %70, %71, %72, %73, %74, %75, %76, %77, %78, %79, "
    "%80, %81, %82, %83, %84, %85, %86, %87, %88, %89, %90, %91, %92, %93, %94, %95}, "
    "{%96, %97, %98, %99}, %100, p, 1, 1, 1;\n}\n"
    : "+f"(d[O + 0]), "+f"(d[O + 1]), "+f"(d[O + 2]), "+f"(d[O + 3]), "+f"(d[O + 4]), "+f"(d[O + 5]), "+f"(d[O + 6]), "+f"(d[O + 7]),
      "+f"(d[O + 8]), "+f"(d[O + 9]), "+f"(d[O + 10]), "+f"(d[O + 11]), "+f"(d[O + 12]), "+f"(d[O + 13]), "+f"(d[O + 14]), "+f"(d[O + 15]),
      "+f"(d[O + 16]), "+f"(d[O + 17]), "+f"(d[O + 18]), "+f"(d[O + 19]), "+f"(d[O + 20]), "+f"(d[O + 21]), "+f"(d[O + 22]), "+f"(d[O + 23]),
      "+f"(d[O + 24]), "+f"(d[O + 25]), "+f"(d[O + 26]), "+f"(d[O + 27]), "+f"(d[O + 28]), "+f"(d[O + 29]), "+f"(d[O + 30]), "+f"(d[O + 31]),
      "+f"(d[O + 32]), "+f"(d[O + 33]), "+f"(d[O + 34]), "+f"(d[O + 35]), "+f"(d[O + 36]), "+f"(d[O + 37]), "+f"(d[O + 38]), "+f"(d[O + 39]),
      "+f"(d[O + 40]), "+f"(d[O + 41]), "+f"(d[O + 42]), "+f"(d[O + 43]), "+f"(d[O + 44]), "+f"(d[O + 45]), "+f"(d[O + 46]), "+f"(d[O + 47]),
      "+f"(d[O + 48]), "+f"(d[O + 49]), "+f"(d[O + 50]), "+f"(d[O + 51]), "+f"(d[O + 52]), "+f"(d[O + 53]), "+f"(d[O + 54]), "+f"(d[O + 55]),
      "+f"(d[O + 56]), "+f"(d[O + 57]), "+f"(d[O + 58]), "+f"(d[O + 59]), "+f"(d[O + 60]), "+f"(d[O + 61]), "+f"(d[O + 62]), "+f"(d[O + 63]),
      "+f"(d[O + 64]), "+f"(d[O + 65]), "+f"(d[O + 66]), "+f"(d[O + 67]), "+f"(d[O + 68]), "+f"(d[O + 69]), "+f"(d[O + 70]), "+f"(d[O + 71]),
      "+f"(d[O + 72]), "+f"(d[O + 73]), "+f"(d[O + 74]), "+f"(d[O + 75]), "+f"(d[O + 76]), "+f"(d[O + 77]), "+f"(d[O + 78]), "+f"(d[O + 79]),
      "+f"(d[O + 80]), "+f"(d[O + 81]), "+f"(d[O + 82]), "+f"(d[O + 83]), "+f"(d[O + 84]), "+f"(d[O + 85]), "+f"(d[O + 86]), "+f"(d[O + 87]),
      "+f"(d[O + 88]), "+f"(d[O + 89]), "+f"(d[O + 90]), "+f"(d[O + 91]), "+f"(d[O + 92]), "+f"(d[O + 93]), "+f"(d[O + 94]), "+f"(d[O + 95])
    : "r"(a.x), "r"(a.y), "r"(a.z), "r"(a.w), "l"(db));
}
template <int O, int T> __device__ __forceinline__ void wgmma_rs_n192_init(float (&d)[T], const uint4& a, uint64_t db) {
  asm volatile("{\n.reg .pred p;\nsetp.ne.b32 p, 0, 0;\n"
    "wgmma.mma_async.sync.aligned.m64n192k16.f32.bf16.bf16 "
    "{%0, %1, %2, %3, %4, %5, %6, %7, %8, %9, %10, %11, %12, %13, %14, %15, "
    "%16, %17, %18, %19, %20, %21, %22, %23, %24, %25, %26, %27, %28, %29, %30, %31, "
    "%32, %33, %34, %35, %36, %37, %38, %39, %40, %41, %42, %43, %44, %45, %46, %47, "
    "%48, %49, %50, %51, %52, %53, %54, %55, %56, %57, %58, %59, %60, %61, %62, %63, "
    "%64, %65, %66, %67, %68, %69, %70, %71, %72, %73, %74, %75, %76, %77, %78, %79, "
    "%80, %81, %82, %83, %84, %85, %86, %87, %88, %89, %90, %91, %92, %93, %94, %95}, "
    "{%96, %97, %98, %99}, %100, p, 1, 1, 1;\n}\n"
    : "=f"(d[O + 0]), "=f"(d[O + 1]), "=f"(d[O + 2]), "=f"(d[O + 3]), "=f"(d[O + 4]), "=f"(d[O + 5]), "=f"(d[O + 6]), "=f"(d[O + 7]),
      "=f"(d[O + 8]), "=f"(d[O + 9]), "=f"(d[O + 10]), "=f"(d[O + 11]), "=f"(d[O + 12]), "=f"(d[O + 13]), "=f"(d[O + 14]), "=f"(d[O + 15]),
      "=f"(d[O + 16]), "=f"(d[O + 17]), "=f"(d[O + 18]), "=f"(d[O + 19]), "=f"(d[O + 20]), "=f"(d[O + 21]), "=f"(d[O + 22]), "=f"(d[O + 23]),
      "=f"(d[O + 24]), "=f"(d[O + 25]), "=f"(d[O + 26]), "=f"(d[O + 27]), "=f"(d[O + 28]), "=f"(d[O + 29]), "=f"(d[O + 30]), "=f"(d[O + 31]),
      "=f"(d[O + 32]), "=f"(d[O + 33]), "=f"(d[O + 34]), "=f"(d[O + 35]), "=f"(d[O + 36]), "=f"(d[O + 37]), "=f"(d[O + 38]), "=f"(d[O + 39]),
      "=f"(d[O + 40]), "=f"(d[O + 41]), "=f"(d[O + 42]), "=f"(d[O + 43]), "=f"(d[O + 44]), "=f"(d[O + 45]), "=f"(d[O + 46]), "=f"(d[O + 47]),
      "=f"(d[O + 48]), "=f"(d[O + 49]), "=f"(d[O + 50]), "=f"(d[O + 51]), "=f"(d[O + 52]), "=f"(d[O + 53]), "=f"(d[O + 54]), "=f"(d[O + 55]),
      "=f"(d[O + 56]), "=f"(d[O + 57]), "=f"(d[O + 58]), "=f"(d[O + 59]), "=f"(d[O + 60]), "=f"(d[O + 61]), "=f"(d[O + 62]), "=f"(d[O + 63]),
      "=f"(d[O + 64]), "=f"(d[O + 65]), "=f"(d[O + 66]), "=f"(d[O + 67]), "=f"(d[O + 68]), "=f"(d[O + 69]), "=f"(d[O + 70]), "=f"(d[O + 71]),
      "=f"(d[O + 72]), "=f"(d[O + 73]), "=f"(d[O + 74]), "=f"(d[O + 75]), "=f"(d[O + 76]), "=f"(d[O + 77]), "=f"(d[O + 78]), "=f"(d[O + 79]),
      "=f"(d[O + 80]), "=f"(d[O + 81]), "=f"(d[O + 82]), "=f"(d[O + 83]), "=f"(d[O + 84]), "=f"(d[O + 85]), "=f"(d[O + 86]), "=f"(d[O + 87]),
      "=f"(d[O + 88]), "=f"(d[O + 89]), "=f"(d[O + 90]), "=f"(d[O + 91]), "=f"(d[O + 92]), "=f"(d[O + 93]), "=f"(d[O + 94]), "=f"(d[O + 95])
    : "r"(a.x), "r"(a.y), "r"(a.z), "r"(a.w), "l"(db));
}
template <bool INIT, int O, int T> __device__ __forceinline__ void wgmma_n192(float (&d)[T], const uint4& a, uint64_t db) {
  if constexpr (INIT) wgmma_rs_n192_init<O>(d, a, db); else wgmma_rs_n192<O>(d, a, db);
}
template <int O, int T> __device__ __forceinline__ void wgmma_rs_n256(float (&d)[T], const uint4& a, uint64_t db) {
  asm volatile("{\n.reg .pred p;\nsetp.ne.b32 p, 1, 0;\n"
    "wgmma.mma_async.sync.aligned.m64n256k16.f32.bf16.bf16 "
    "{%0, %1, %2, %3, %4, %5, %6, %7, %8, %9, %10, %11, %12, %13, %14, %15, "
    "%16, %17, %18, %19, %20, %21, %22, %23, %24, %25, %26, %27, %28, %29, %30, %31, "
    "%32, %33, %34, %35, %36, %37, %38, %39, %40, %41, %42, %43, %44, %45, %46, %47, "
    "%48, %49, %50, %51, %52, %53, %54, %55, %56, %57, %58, %59, %60, %61, %62, %63, "
    "%64, %65, %66, %67, %68, %69, %70, %71, %72, %73, %74, %75, %76, %77, %78, %79, "
    "%80, %81, %82, %83, %84, %85, %86, %87, %88, %89, %90, %91, %92, %93, %94, %95, "
    "%96, %97, %98, %99, %100, %101, %102, %103, %104, %105, %106, %107, %108, %109, %110, %111, "
    "%112, %113, %114, %115, %116, %117, %118, %119, %120, %121, %122, %123, %124, %125, %126, %127}, "
    "{%128, %129, %130, %131}, %132, p, 1, 1, 1;\n}\n"
    : "+f"(d[O + 0]), "+f"(d[O + 1]), "+f"(d[O + 2]), "+f"(d[O + 3]), "+f"(d[O + 4]), "+f"(d[O + 5]), "+f"(d[O + 6]), "+f"(d[O + 7]),
      "+f"(d[O + 8]), "+f"(d[O + 9]), "+f"(d[O + 10]), "+f"(d[O + 11]), "+f"(d[O + 12]), "+f"(d[O + 13]), "+f"(d[O + 14]), "+f"(d[O + 15]),
      "+f"(d[O + 16]), "+f"(d[O + 17]), "+f"(d[O + 18]), "+f"(d[O + 19]), "+f"(d[O + 20]), "+f"(d[O + 21]), "+f"(d[O + 22]), "+f"(d[O + 23]),
      "+f"(d[O + 24]), "+f"(d[O + 25]), "+f"(d[O + 26]), "+f"(d[O + 27]), "+f"(d[O + 28]), "+f"(d[O + 29]), "+f"(d[O + 30]), "+f"(d[O + 31]),
      "+f"(d[O + 32]), "+f"(d[O + 33]), "+f"(d[O + 34]), "+f"(d[O + 35]), "+f"(d[O + 36]), "+f"(d[O + 37]), "+f"(d[O + 38]), "+f"(d[O + 39]),
      "+f"(d[O + 40]), "+f"(d[O + 41]), "+f"(d[O + 42]), "+f"(d[O + 43]), "+f"(d[O + 44]), "+f"(d[O + 45]), "+f"(d[O + 46]), "+f"(d[O + 47]),
      "+f"(d[O + 48]), "+f"(d[O + 49]), "+f"(d[O + 50]), "+f"(d[O + 51]), "+f"(d[O + 52]), "+f"(d[O + 53]), "+f"(d[O + 54]), "+f"(d[O + 55]),
      "+f"(d[O + 56]), "+f"(d[O + 57]), "+f"(d[O + 58]), "+f"(d[O + 59]), "+f"(d[O + 60]), "+f"(d[O + 61]), "+f"(d[O + 62]), "+f"(d[O + 63]),
      "+f"(d[O + 64]), "+f"(d[O + 65]), "+f"(d[O + 66]), "+f"(d[O + 67]), "+f"(d[O + 68]), "+f"(d[O + 69]), "+f"(d[O + 70]), "+f"(d[O + 71]),
      "+f"(d[O + 72]), "+f"(d[O + 73]), "+f"(d[O + 74]), "+f"(d[O + 75]), "+f"(d[O + 76]), "+f"(d[O + 77]), "+f"(d[O + 78]), "+f"(d[O + 79]),
      "+f"(d[O + 80]), "+f"(d[O + 81]), "+f"(d[O + 82]), "+f"(d[O + 83]), "+f"(d[O + 84]), "+f"(d[O + 85]), "+f"(d[O + 86]), "+f"(d[O + 87]),
      "+f"(d[O + 88]), "+f"(d[O + 89]), "+f"(d[O + 90]), "+f"(d[O + 91]), "+f"(d[O + 92]), "+f"(d[O + 93]), "+f"(d[O + 94]), "+f"(d[O + 95]),
      "+f"(d[O + 96]), "+f"(d[O + 97]), "+f"(d[O + 98]), "+f"(d[O + 99]), "+f"(d[O + 100]), "+f"(d[O + 101]), "+f"(d[O + 102]), "+f"(d[O + 103]),
      "+f"(d[O + 104]), "+f"(d[O + 105]), "+f"(d[O + 106]), "+f"(d[O + 107]), "+f"(d[O + 108]), "+f"(d[O + 109]), "+f"(d[O + 110]), "+f"(d[O + 111]),
      "+f"(d[O + 112]), "+f"(d[O + 113]), "+f"(d[O + 114]), "+f"(d[O + 115]), "+f"(d[O + 116]), "+f"(d[O + 117]), "+f"(d[O + 118]), "+f"(d[O + 119]),
      "+f"(d[O + 120]), "+f"(d[O + 121]), "+f"(d[O + 122]), "+f"(d[O + 123]), "+f"(d[O + 124]), "+f"(d[O + 125]), "+f"(d[O + 126]), "+f"(d[O + 127])
    : "r"(a.x), "r"(a.y), "r"(a.z), "r"(a.w), "l"(db));
}
template <int O, int T> __device__ __forceinline__ void wgmma_rs_n256_init(float (&d)[T], const uint4& a, uint64_t db) {
  asm volatile("{\n.reg .pred p;\nsetp.ne.b32 p, 0, 0;\n"
    "wgmma.mma_async.sync.aligned.m64n256k16.f32.bf16.bf16 "
    "{%0, %1, %2, %3, %4, %5, %6, %7, %8, %9, %10, %11, %12, %13, %14, %15, "
    "%16, %17, %18, %19, %20, %21, %22, %23, %24, %25, %26, %27, %28, %29, %30, %31, "
    "%32, %33, %34, %35, %36, %37, %38, %39, %40, %41, %42, %43, %44, %45, %46, %47, "
    "%48, %49, %50, %51, %52, %53, %54, %55, %56, %57, %58, %59, %60, %61, %62, %63, "
    "%64, %65, %66, %67, %68, %69, %70, %71, %72, %73, %74, %75, %76, %77, %78, %79, "
    "%80, %81, %82, %83, %84, %85, %86, %87, %88, %89, %90, %91, %92, %93, %94, %95, "
    "%96, %97, %98, %99, %100, %101, %102, %103, %104, %105, %106, %107, %108, %109, %110, %111, "
    "%112, %113, %114, %115, %116, %117, %118, %119, %120, %121, %122, %123, %124, %125, %126, %127}, "
    "{%128, %129, %130, %131}, %132, p, 1, 1, 1;\n}\n"
    : "=f"(d[O + 0]), "=f"(d[O + 1]), "=f"(d[O + 2]), "=f"(d[O + 3]), "=f"(d[O + 4]), "=f"(d[O + 5]), "=f"(d[O + 6]), "=f"(d[O + 7]),
      "=f"(d[O + 8]), "=f"(d[O + 9]), "=f"(d[O + 10]), "=f"(d[O + 11]), "=f"(d[O + 12]), "=f"(d[O + 13]), "=f"(d[O + 14]), "=f"(d[O + 15]),
      "=f"(d[O + 16]), "=f"(d[O + 17]), "=f"(d[O + 18]), "=f"(d[O + 19]), "=f"(d[O + 20]), "=f"(d[O + 21]), "=f"(d[O + 22]), "=f"(d[O + 23]),
      "=f"(d[O + 24]), "=f"(d[O + 25]), "=f"(d[O + 26]), "=f"(d[O + 27]), "=f"(d[O + 28]), "=f"(d[O + 29]), "=f"(d[O + 30]), "=f"(d[O + 31]),
      "=f"(d[O + 32]), "=f"(d[O + 33]), "=f"(d[O + 34]), "=f"(d[O + 35]), "=f"(d[O + 36]), "=f"(d[O + 37]), "=f"(d[O + 38]), "=f"(d[O + 39]),
      "=f"(d[O + 40]), "=f"(d[O + 41]), "=f"(d[O + 42]), "=f"(d[O + 43]), "=f"(d[O + 44]), "=f"(d[O + 45]), "=f"(d[O + 46]), "=f"(d[O + 47]),
      "=f"(d[O + 48]), "=f"(d[O + 49]), "=f"(d[O + 50]), "=f"(d[O + 51]), "=f"(d[O + 52]), "=f"(d[O + 53]), "=f"(d[O + 54]), "=f"(d[O + 55]),
      "=f"(d[O + 56]), "=f"(d[O + 57]), "=f"(d[O + 58]), "=f"(d[O + 59]), "=f"(d[O + 60]), "=f"(d[O + 61]), "=f"(d[O + 62]), "=f"(d[O + 63]),
      "=f"(d[O + 64]), "=f"(d[O + 65]), "=f"(d[O + 66]), "=f"(d[O + 67]), "=f"(d[O + 68]), "=f"(d[O + 69]), "=f"(d[O + 70]), "=f"(d[O + 71]),
      "=f"(d[O + 72]), "=f"(d[O + 73]), "=f"(d[O + 74]), "=f"(d[O + 75]), "=f"(d[O + 76]), "=f"(d[O + 77]), "=f"(d[O + 78]), "=f"(d[O + 79]),
      "=f"(d[O + 80]), "=f"(d[O + 81]), "=f"(d[O + 82]), "=f"(d[O + 83]), "=f"(d[O + 84]), "=f"(d[O + 85]), "=f"(d[O + 86]), "=f"(d[O + 87]),
      "=f"(d[O + 88]), "=f"(d[O + 89]), "=f"(d[O + 90]), "=f"(d[O + 91]), "=f"(d[O + 92]), "=f"(d[O + 93]), "=f"(d[O + 94]), "=f"(d[O + 95]),
      "=f"(d[O + 96]), "=f"(d[O + 97]), "=f"(d[O + 98]), "=f"(d[O + 99]), "=f"(d[O + 100]), "=f"(d[O + 101]), "=f"(d[O + 102]), "=f"(d[O + 103]),
      "=f"(d[O + 104]), "=f"(d[O + 105]), "=f"(d[O + 106]), "=f"(d[O + 107]), "=f"(d[O + 108]), "=f"(d[O + 109]), "=f"(d[O + 110]), "=f"(d[O + 111]),
      "=f"(d[O + 112]), "=f"(d[O + 113]), "=f"(d[O + 114]), "=f"(d[O + 115]), "=f"(d[O + 116]), "=f"(d[O + 117]), "=f"(d[O + 118]), "=f"(d[O + 119]),
      "=f"(d[O + 120]), "=f"(d[O + 121]), "=f"(d[O + 122]), "=f"(d[O + 123]), "=f"(d[O + 124]), "=f"(d[O + 125]), "=f"(d[O + 126]), "=f"(d[O + 127])
    : "r"(a.x), "r"(a.y), "r"(a.z), "r"(a.w), "l"(db));
}
template <bool INIT, int O, int T> __device__ __forceinline__ void wgmma_n256(float (&d)[T], const uint4& a, uint64_t db) {
  if constexpr (INIT) wgmma_rs_n256_init<O>(d, a, db); else wgmma_rs_n256<O>(d, a, db);
}

template <int N> __device__ __forceinline__ void load_pk(uint4* a, const uint4* p) {
#pragma unroll
  for (int i = 0; i < N; i++) a[i] = ld_ll(p + i * 32);
}
__device__ __forceinline__ uint32_t xor_or(uint32_t a, uint32_t b, uint32_t t) {
  uint32_t r;
  asm("lop3.b32 %0, %1, %2, %3, 0x7E;" : "=r"(r) : "r"(a), "r"(b), "r"(t));
  return r;
}
template <int N> __device__ __forceinline__ bool ok_pk(const uint4* a, uint32_t tag) {
  static_assert(N % 2 == 0, "");
  uint32_t x = xor_or(a[0].x, a[1].x, tag);
#pragma unroll
  for (int i = 2; i < N; i += 2) x |= xor_or(a[i].x, a[i + 1].x, tag);
  return __all_sync(0xffffffffu, (x & 1u) == 0u);
}
template <int N> __device__ __forceinline__ void ensure_pk(uint4* a, const uint4* p, uint32_t tag) {
  if (ok_pk<N>(a, tag)) return;
  uint32_t n = 0;
  do { load_pk<N>(a, p); } while (!ok_pk<N>(a, tag) && ++n < SPIN_LIMIT);
}

constexpr int NSTAGE = 52;
constexpr int ST_WO = 8, ST_G1 = 12, ST_G2 = 28, ST_DN = 36;
__host__ __device__ constexpr int st_len(int s) { return s < ST_WO ? 3 : s < ST_G2 ? 2 : s < ST_DN ? 3 : 2; }
__host__ __device__ constexpr int st_g0(int s) {
  int pos = 0, g0 = 0;
  for (int i = 0; i <= s; i++) {
    if (pos + st_len(i) > NGRAN) pos = 0;
    g0 = pos;
    pos += st_len(i);
  }
  return g0;
}
__host__ __device__ constexpr int cnt_first(int g, int s) {
  int n = 0;
  for (int i = 0; i < s; i++) n += (st_g0(i) == g);
  return n;
}
__host__ __device__ constexpr int cnt_cover(int g, int s) {
  int n = 0;
  for (int i = 0; i < s; i++) n += (g >= st_g0(i) && g < st_g0(i) + st_len(i));
  return n;
}
__host__ __device__ constexpr uint32_t flip_mask(int s0, int s1) {
  uint32_t m = 0;
  for (int i = s0; i < s1; i++) m ^= ((1u << st_len(i)) - 1u) << st_g0(i);
  return m;
}
__host__ __device__ constexpr int dn_q(int i) { return i < 3 ? 0 : i < 6 ? 1 : i == 6 ? 0 : i == 7 ? 1 : i < 12 ? 2 : 3; }
__host__ __device__ constexpr int dn_par(int i) { return i < 8 ? (i == 2 || i == 4 || i >= 6) : (i & 1); }
__host__ __device__ constexpr int dn_kh(int i) { return i < 8 ? (i == 1 || i >= 5) : ((i & 3) >= 2); }
template <int I> struct IC { static constexpr int value = I; };
template <int B, int E, typename F> __device__ __forceinline__ void static_for(F&& f) {
  if constexpr (B < E) { f(IC<B>{}); static_for<B + 1, E>(f); }
}
template <int S> __device__ __forceinline__ void cons_acquire(uint32_t sbase, uint32_t L) {
  constexpr int g0 = st_g0(S);
  constexpr uint32_t p0 = cnt_first(g0, S) & 1, odd = cnt_first(g0, NSTAGE) & 1;
  mbar_wait(sbase + SM_MISC + BAR_FULL + 8 * g0, p0 ^ (L & odd));
}
template <int S> __device__ __forceinline__ void cons_release(uint32_t sbase, int lane) {
  if (lane < st_len(S)) mbar_arrive(sbase + SM_MISC + BAR_EMPTY + 8 * st_g0(S) + 8 * lane);
}
__device__ __forceinline__ bool elect_one() {
  uint32_t p;
  asm volatile("{\n.reg .pred P;\nelect.sync _|P, 0xffffffff;\nselp.u32 %0, 1, 0, P;\n}" : "=r"(p));
  return p != 0;
}
struct ProdRing { uint32_t pos, par; };
template <int N> __device__ __forceinline__ uint32_t prod_acquire(uint32_t sbase, ProdRing& r) {
  if (r.pos + N > NGRAN) r.pos = 0;
  const uint32_t g0 = r.pos;
#pragma unroll
  for (uint32_t i = 0; i < N; i++) mbar_wait(sbase + SM_MISC + BAR_EMPTY + 8 * (g0 + i), ((r.par >> (g0 + i)) & 1u) ^ 1u);
  r.par ^= ((1u << N) - 1u) << g0;
  r.pos = g0 + N;
  return g0;
}
template <int S> __device__ __forceinline__ void prod_acquire_static(uint32_t sbase, uint32_t L) {
  constexpr int g0 = st_g0(S);
  static_for<0, st_len(S)>([&](auto I) {
    constexpr int g = g0 + I.value;
    constexpr uint32_t p0 = cnt_cover(g, S) & 1, odd = cnt_cover(g, NSTAGE) & 1;
    mbar_wait(sbase + SM_MISC + BAR_EMPTY + 8 * g, p0 ^ (L & odd) ^ 1u);
  });
}
template <int S, int KSTEP_BYTES, int LBO, int SBO, int SWZ> __device__ __forceinline__ constexpr uint64_t st_desc(int k) {
  return (uint64_t)((SMEM_ORIGIN + st_g0(S) * GRAN + k * KSTEP_BYTES) >> 4) | ((uint64_t)(LBO >> 4) << 16) |
         ((uint64_t)(SBO >> 4) << 32) | ((uint64_t)SWZ << 62);
}

__device__ __forceinline__ void combine_stats(const uint4& p0, const uint4& p1, float& mean_lo, float& rstd_lo, float& mean_hi, float& rstd_hi) {
  float m0 = __uint_as_float(p0.x), q0 = __uint_as_float(p0.y), m0h = __uint_as_float(p0.z), q0h = __uint_as_float(p0.w);
  float m1 = __uint_as_float(p1.x), q1 = __uint_as_float(p1.y), m1h = __uint_as_float(p1.z), q1h = __uint_as_float(p1.w);
  float s = m0 + m1, sh = m0h + m1h;
  s += __shfl_xor_sync(0xffffffffu, s, 1); sh += __shfl_xor_sync(0xffffffffu, sh, 1);
  s += __shfl_xor_sync(0xffffffffu, s, 2); sh += __shfl_xor_sync(0xffffffffu, sh, 2);
  mean_lo = s * 0.125f; mean_hi = sh * 0.125f;
  float d0 = m0 - mean_lo, d1 = m1 - mean_lo, d0h = m0h - mean_hi, d1h = m1h - mean_hi;
  float t = q0 + q1 + 64.f * (d0 * d0 + d1 * d1), th = q0h + q1h + 64.f * (d0h * d0h + d1h * d1h);
  t += __shfl_xor_sync(0xffffffffu, t, 1); th += __shfl_xor_sync(0xffffffffu, th, 1);
  t += __shfl_xor_sync(0xffffffffu, t, 2); th += __shfl_xor_sync(0xffffffffu, th, 2);
  rstd_lo = rsqrtf(t * (1.f / 512.f) + 1e-5f);
  rstd_hi = rsqrtf(th * (1.f / 512.f) + 1e-5f);
}
__device__ __forceinline__ uint4 local_stats(const float (&v)[32]) {
  float s = 0.f, sh = 0.f;
#pragma unroll
  for (int i = 0; i < 4; i++) {
    s += (v[8 * i + 0] + v[8 * i + 1]) + (v[8 * i + 4] + v[8 * i + 5]);
    sh += (v[8 * i + 2] + v[8 * i + 3]) + (v[8 * i + 6] + v[8 * i + 7]);
  }
  s += __shfl_xor_sync(0xffffffffu, s, 1); sh += __shfl_xor_sync(0xffffffffu, sh, 1);
  s += __shfl_xor_sync(0xffffffffu, s, 2); sh += __shfl_xor_sync(0xffffffffu, sh, 2);
  float m = s * (1.f / 64.f), mh = sh * (1.f / 64.f);
  float q = 0.f, qh = 0.f;
#pragma unroll
  for (int i = 0; i < 4; i++) {
    float a = v[8 * i + 0] - m, b = v[8 * i + 1] - m, c = v[8 * i + 4] - m, d = v[8 * i + 5] - m;
    q += (a * a + b * b) + (c * c + d * d);
    float e = v[8 * i + 2] - mh, f = v[8 * i + 3] - mh, g = v[8 * i + 6] - mh, h = v[8 * i + 7] - mh;
    qh += (e * e + f * f) + (g * g + h * h);
  }
  q += __shfl_xor_sync(0xffffffffu, q, 1); qh += __shfl_xor_sync(0xffffffffu, qh, 1);
  q += __shfl_xor_sync(0xffffffffu, q, 2); qh += __shfl_xor_sync(0xffffffffu, qh, 2);
  return make_uint4(__float_as_uint(m), __float_as_uint(q), __float_as_uint(mh), __float_as_uint(qh));
}

__device__ __forceinline__ int slab_row0(int c, int g, int w) { return 1024 * g + 64 * c + 32 * (w >> 1) + (w & 1); }

__device__ __forceinline__ void owner_ln_publish(uint32_t sbase, const float (&v)[32], uint32_t tphase, uint32_t tag_xn, uint4 (&xraw)[4]) {
  PHASE_VARS;
  TS(40 + 4 * tphase);
  uint4 st = local_stats(v);
  if (qc == 0) sts128(sbase + SM_TSTAT + warp * 128 + qr * 16, st);
  uint4* xn = g_arena + c * ARENA + AR_XN + ((j) * 32 + 4 * warp) * 32 + lane;
  TS(41 + 4 * tphase);
  asm volatile("bar.sync 3, 256;" ::: "memory");
  TS(42 + 4 * tphase);
  const uint32_t rd = sbase + SM_TSTAT + qc * 256 + qr * 16;
  uint4 p0 = lds128(rd), p1 = lds128(rd + 128);
  float ml, rl, mh, rh;
  combine_stats(p0, p1, ml, rl, mh, rh);
  const float bl = -ml * rl, bh = -mh * rh;
#pragma unroll
  for (int i = 0; i < 4; i++) {
    uint4 o;
    o.x = set_tag(pack2(fmaf(v[8 * i + 0], rl, bl), fmaf(v[8 * i + 1], rl, bl)), tag_xn);
    o.y = pack2(fmaf(v[8 * i + 2], rh, bh), fmaf(v[8 * i + 3], rh, bh));
    o.z = pack2(fmaf(v[8 * i + 4], rl, bl), fmaf(v[8 * i + 5], rl, bl));
    o.w = pack2(fmaf(v[8 * i + 6], rh, bh), fmaf(v[8 * i + 7], rh, bh));
    st_ll(xn + i * 32, o);
  }
#pragma unroll
  for (int i = 0; i < 4; i++) {
    xraw[i].x = set_tag(pack2(v[8 * i + 0], v[8 * i + 1]), 1u);
    xraw[i].y = pack2(v[8 * i + 2], v[8 * i + 3]);
    xraw[i].z = pack2(v[8 * i + 4], v[8 * i + 5]);
    xraw[i].w = pack2(v[8 * i + 6], v[8 * i + 7]);
  }
}

__device__ __forceinline__ uint4 pack8(const float* a) {
  return make_uint4(pack2(a[0], a[1]), pack2(a[2], a[3]), pack2(a[4], a[5]), pack2(a[6], a[7]));
}
template <int U> __device__ __forceinline__ uint4 glu8(const float* g, float cl, float ch) {
  return make_uint4(pack2(g[0] * cl * g[U], g[1] * cl * g[U + 1]), pack2(g[2] * ch * g[U + 2], g[3] * ch * g[U + 3]),
                    pack2(g[4] * cl * g[U + 4], g[5] * cl * g[U + 5]), pack2(g[6] * ch * g[U + 6], g[7] * ch * g[U + 7]));
}
__device__ __forceinline__ uint32_t hfma2(uint32_t a, uint32_t b, uint32_t c) {
  uint32_t d;
  asm("fma.rn.bf16x2 %0, %1, %2, %3;" : "=r"(d) : "r"(a), "r"(b), "r"(c));
  return d;
}
__device__ __forceinline__ void keep4(const uint4 (&a)[4]) { keep(a[0]); keep(a[1]); keep(a[2]); keep(a[3]); }

#define STAGGER 0

__global__ void __launch_bounds__(NTHREADS, 1)
fused_kernel(const __grid_constant__ CUtensorMap m_qkv, const __grid_constant__ CUtensorMap m_wo,
             const __grid_constant__ CUtensorMap m_gu2, const __grid_constant__ CUtensorMap m_gu1,
             const __grid_constant__ CUtensorMap m_guh, const __grid_constant__ CUtensorMap m_wd112,
             const __grid_constant__ CUtensorMap m_wd80, const __grid_constant__ CUtensorMap m_wd32,
             const __nv_bfloat16* __restrict__ x_in,
             __nv_bfloat16* __restrict__ out
) {
  extern __shared__ __align__(1024) unsigned char smem_raw[];
  const uint32_t sbase = smem_u32(smem_raw);
  const uint32_t bars = sbase + SM_MISC;
  if ((sbase & 0xFFFFFFu) != SMEM_ORIGIN) return;
  TG(60);

  uint32_t xw[16];
  if (threadIdx.x < 256) {
    const int cc = blockIdx.x >> 3, jj = blockIdx.x & 7, ln = threadIdx.x & 31;
    const uint32_t* xp = reinterpret_cast<const uint32_t*>(x_in + (size_t)(slab_row0(cc, jj >> 2, jj & 3) + 2 * (ln >> 2)) * 512 + (threadIdx.x >> 5) * 64 + (ln & 3) * 2);
#pragma unroll
    for (int i = 0; i < 4; i++) {
      xw[4 * i] = __ldg(xp + i * 8); xw[4 * i + 1] = __ldg(xp + 16 * 256 + i * 8);
      xw[4 * i + 2] = __ldg(xp + i * 8 + 4); xw[4 * i + 3] = __ldg(xp + 16 * 256 + i * 8 + 4);
    }
  } else if (threadIdx.x == 256) {
    for (int i = 0; i < NGRAN; i++) { mbar_init(bars + BAR_FULL + 8 * i, 1); mbar_init(bars + BAR_EMPTY + 8 * i, 8); }
    for (int i = 0; i < 4; i++) mbar_init(bars + BAR_HRECV + 8 * i, 1);
    for (int i = 0; i < 2; i++) mbar_init(bars + BAR_HREADY + 8 * i, 4);
    asm volatile("fence.mbarrier_init.release.cluster;" ::: "memory");
  }
  TG(56);
  __syncthreads();
  TG(57);
  asm volatile("barrier.cluster.arrive.relaxed.aligned;" ::: "memory");

  if (threadIdx.x >= 256) {
    asm volatile("setmaxnreg.dec.sync.aligned.u32 40;");
    const int warp = threadIdx.x >> 5;
    const int j = blockIdx.x & 7, b = j & 1;
    if (warp == 8) {
      ProdRing r{0u, 0u};
      const int cb0 = 224 * j + 32 * b, hb0 = 224 * j + 192 * (b ^ 1);
      const int jp = j ^ 1, cbp = 224 * jp + 32 * (b ^ 1), hbp = 224 * jp + 192 * b;
#pragma unroll 1
      for (uint32_t L = 0; L < 2; L++) {
        r.pos = 0;
        PSTOP_AT(L == 0 ? 0 : 3);
#pragma unroll 1
        for (int kb = 0; kb < 8; kb++) {
          const uint32_t g0 = prod_acquire<3>(sbase, r);
          if (elect_one()) {
            mbar_expect_tx(bars + BAR_FULL + 8 * g0, 24576);
            tma_3d(sbase + g0 * GRAN, &m_qkv, bars + BAR_FULL + 8 * g0, 64 * j, 64 * kb, 0);
          }
        }
        PSTOP_AT(10 * L + 1);
#pragma unroll 1
        for (int i = 0; i < 4; i++) {
          const uint32_t g0 = prod_acquire<2>(sbase, r);
          if (elect_one()) {
            mbar_expect_tx(bars + BAR_FULL + 8 * g0, 16384);
            tma_2d(sbase + g0 * GRAN, &m_wo, bars + BAR_FULL + 8 * g0, 64 * j, 128 * i);
          }
        }
        PSTOP_AT(10 * L + 2);
#pragma unroll 1
        for (int hb = 0; hb < 16; hb++) {
          const uint32_t g0 = prod_acquire<2>(sbase, r);
          if (elect_one()) {
            mbar_expect_tx(bars + BAR_FULL + 8 * g0, 16384);
            tma_4d(sbase + g0 * GRAN, &m_gu2, bars + BAR_FULL + 8 * g0, cb0, 64 * ((j + (hb >> 1)) & 7) + 32 * (hb & 1), 0, 0);
          }
        }
#pragma unroll 1
        for (int kb = 0; kb < 8; kb++) {
          const uint32_t g0 = prod_acquire<3>(sbase, r);
          if (elect_one()) {
            mbar_expect_tx(bars + BAR_FULL + 8 * g0, 24576);
            tma_4d(sbase + g0 * GRAN, &m_gu1, bars + BAR_FULL + 8 * g0, cb0 + 128, 64 * ((j + kb) & 7), 0, 0);
            tma_3d(sbase + g0 * GRAN + 16384, &m_guh, bars + BAR_FULL + 8 * g0, hb0, 64 * ((j + kb) & 7), 0);
          }
        }
        static_for<0, 16>([&](auto I) {
          constexpr int i = I.value, g0 = st_g0(ST_DN + i);
          prod_acquire_static<ST_DN + i>(sbase, L);
          if (elect_one()) {
            const uint32_t dst = sbase + g0 * GRAN, fb = bars + BAR_FULL + 8 * g0;
            const int n0 = 256 * b + 64 * dn_q(i);
            mbar_expect_tx(fb, 14336);
            if constexpr (dn_kh(i) == 0) {
              tma_2d(dst, &m_wd112, fb, n0, dn_par(i) ? cbp : cb0);
            } else {
              tma_2d(dst, &m_wd80, fb, n0, (dn_par(i) ? cbp : cb0) + 112);
              tma_2d(dst + 10240, &m_wd32, fb, n0, dn_par(i) ? hbp : hb0);
            }
          }
        });
        r.par ^= flip_mask(ST_DN, NSTAGE);
      }
    }
    __syncwarp();
    asm volatile("barrier.cluster.wait.acquire.aligned; // producer" ::: "memory");
  } else {
    TG(58);
    asm volatile("setmaxnreg.inc.sync.aligned.u32 232;");
    TS(0);
    TG(61);

    uint4 xraw[4];
    {
      float v[32];
#pragma unroll
      for (int i = 0; i < 16; i++) { v[2 * i] = bf_lo(xw[i]); v[2 * i + 1] = bf_hi(xw[i]); }
      owner_ln_publish(sbase, v, 0u, 1u, xraw);
      asm volatile("barrier.cluster.wait.acquire.aligned; // consumer" ::: "memory");
    }
    STOP_AT(0);
    TS(1);

#pragma unroll 1
    for (uint32_t L = 0; L < 2; L++) {
      const uint32_t tag = L ^ 1;
      {
        PHASE_VARS;
        uint4 qf[4], kf[4], vf[4], pp[4];
        const int blk = 16 * g + c;
        const int pb = blk > 0 ? blk - 1 : 0;
        const uint4* halo_src = g_arena + (pb & 15) * ARENA + AR_HALO + (((((L * 2 + (pb >> 4)) * 8 + j) * 2 + (w & 1)) * 4) * 32) + lane;
        {
          float acc[96];
          uint4 A[3][4];
          const uint4* xs = g_arena + c * ARENA + AR_XN + ((slab) * 32) * 32 + lane;
          bar_wg(1 + g);
          spin_for(L ? D_XN1 : D_XN0);
          load_pk<4>(A[0], xs);
          ensure_pk<4>(A[0], xs, tag);
          TS(2 + 20 * L);
          load_pk<4>(A[1], xs + 128);
          static_for<0, 8>([&](auto I) {
            constexpr int kb = I.value;
            cons_acquire<kb>(sbase, L);
            wg_fence();
            static_for<0, 4>([&](auto K) { constexpr int k = K.value; wgmma_n192<kb == 0 && k == 0, 0>(acc, A[kb % 3][k], st_desc<kb, 2048, 8192, 1024, 1>(k)); });
            wg_commit();
            if constexpr (kb > 0) {
              wg_wait<1>();
              keep4(A[(kb + 2) % 3]);
              cons_release<kb - 1>(sbase, lane);
            }
            if constexpr (kb + 1 < 8) ensure_pk<4>(A[(kb + 1) % 3], xs + (kb + 1) * 128, tag);
            if constexpr (kb + 2 < 8) load_pk<4>(A[(kb + 2) % 3], xs + (kb + 2) * 128);
            if constexpr (kb == 2) {
              uint4* xr = g_arena + c * ARENA + AR_XRAW + ((j) * 32 + 4 * warp) * 32 + lane;
#pragma unroll
              for (int i = 0; i < 4; i++) st_ll(xr + i * 32, xraw[i]);
            }
          });
          wg_wait<0>();
          TS(3 + 20 * L);
          fence_acc(acc);
          keep4(A[1]);
          cons_release<7>(sbase, lane);
#pragma unroll
          for (int h = 0; h < 4; h++) {
            kf[h].y = pack2(acc[32 + 8 * h + 2], acc[32 + 8 * h + 3]); kf[h].w = pack2(acc[32 + 8 * h + 6], acc[32 + 8 * h + 7]);
            vf[h].y = movm(pack2(acc[64 + 8 * h + 2], acc[64 + 8 * h + 3])); vf[h].w = movm(pack2(acc[64 + 8 * h + 6], acc[64 + 8 * h + 7]));
            pp[h] = make_uint4(kf[h].y, kf[h].w, vf[h].y, vf[h].w);
          }
          if (w >= 2 && blk < 31) {
            uint4* hd = g_arena + c * ARENA + AR_HALO + (((((L * 2 + g) * 8 + j) * 2 + (w & 1)) * 4) * 32) + lane;
#pragma unroll
            for (int h = 0; h < 4; h++) { uint4 t = pp[h]; t.x |= 1u; st_ll(hd + h * 32, t); }
          }
#pragma unroll
          for (int h = 0; h < 4; h++) sts128(areg + (28 + h) * 2048 + t128 * 16, pp[h]);
#pragma unroll
          for (int h = 0; h < 4; h++) {
            kf[h].x = pack2(acc[32 + 8 * h], acc[32 + 8 * h + 1]); kf[h].z = pack2(acc[32 + 8 * h + 4], acc[32 + 8 * h + 5]);
            vf[h].x = movm(pack2(acc[64 + 8 * h], acc[64 + 8 * h + 1])); vf[h].z = movm(pack2(acc[64 + 8 * h + 4], acc[64 + 8 * h + 5]));
          }
#pragma unroll
          for (int h = 0; h < 4; h++) qf[h] = pack8(&acc[8 * h]);
        }
        bar_wg(1 + g);
        const bool first = (w < 2) && (blk == 0);
        if (w >= 2) {
#pragma unroll
          for (int h = 0; h < 4; h++) pp[h] = lds128(areg + (28 + h) * 2048 + (t128 - 64) * 16);
        }
        bar_wg(1 + g);
        if (w < 2 && blk > 0) {
          spin_for(L ? D_HALO1 : D_HALO0);
          load_pk<4>(pp, halo_src);
          ensure_pk<4>(pp, halo_src, 1u);
          uint4* hz = const_cast<uint4*>(halo_src);
#pragma unroll
          for (int h = 0; h < 4; h++) st_ll(hz + h * 32, make_uint4(0, 0, 0, 0));
        }
        TS(4 + 20 * L);
        const bool n0 = 2 * qc <= qr, n1 = 2 * qc + 1 <= qr;
        const uint32_t msk = (n0 ? 0xffffu : 0u) | (n1 ? 0xffff0000u : 0u);
        const float sc = 0.25f * 1.4426950408889634f;
        const float NEG = -1e30f;
        uint4* od = g_arena + c * ARENA + AR_O + ((slab) * 32 + 4 * j) * 32 + lane;
        float l0[4], l1[4], h0[4], h1[4], ml[4], mh[4];
#pragma unroll
        for (int h = 0; h < 4; h++) {
          float sp[4], s0[4], s1[4];
          mma16816_z(sp, qf[h], pp[h].x, pp[h].y);
          mma16816_z(s0, qf[h], kf[h].x, kf[h].z);
          mma16816_z(s1, qf[h], kf[h].y, kf[h].w);
          if (first) { sp[0] = NEG; sp[1] = NEG; }
          l0[h] = n0 ? s0[0] : sp[0]; l1[h] = n1 ? s0[1] : sp[1];
          h0[h] = n0 ? s1[2] : s0[2]; h1[h] = n1 ? s1[3] : s0[3];
          ml[h] = fmaxf(l0[h], l1[h]); mh[h] = fmaxf(h0[h], h1[h]);
        }
#pragma unroll
        for (int h = 0; h < 4; h++) { ml[h] = fmaxf(ml[h], __shfl_xor_sync(0xffffffffu, ml[h], 1)); mh[h] = fmaxf(mh[h], __shfl_xor_sync(0xffffffffu, mh[h], 1)); }
#pragma unroll
        for (int h = 0; h < 4; h++) { ml[h] = fmaxf(ml[h], __shfl_xor_sync(0xffffffffu, ml[h], 2)); mh[h] = fmaxf(mh[h], __shfl_xor_sync(0xffffffffu, mh[h], 2)); }
        float sl[4], sh[4];
#pragma unroll
        for (int h = 0; h < 4; h++) {
          const float bl = -ml[h] * sc, bh = -mh[h] * sc;
          l0[h] = ex2(fmaf(l0[h], sc, bl)); l1[h] = ex2(fmaf(l1[h], sc, bl));
          h0[h] = ex2(fmaf(h0[h], sc, bh)); h1[h] = ex2(fmaf(h1[h], sc, bh));
          sl[h] = l0[h] + l1[h]; sh[h] = h0[h] + h1[h];
        }
#pragma unroll
        for (int h = 0; h < 4; h++) { sl[h] += __shfl_xor_sync(0xffffffffu, sl[h], 1); sh[h] += __shfl_xor_sync(0xffffffffu, sh[h], 1); }
#pragma unroll
        for (int h = 0; h < 4; h++) { sl[h] += __shfl_xor_sync(0xffffffffu, sl[h], 2); sh[h] += __shfl_xor_sync(0xffffffffu, sh[h], 2); }
#pragma unroll
        for (int h = 0; h < 4; h++) {
          const float il = rcp(sl[h]), ih = rcp(sh[h]);
          const uint32_t pl = pack2(l0[h] * il, l1[h] * il), ph = pack2(h0[h] * ih, h1[h] * ih);
          const uint4 P = make_uint4(pl & msk, ph & ~msk, 0u, ph & msk);
          float o0[4], o1[4];
          mma16816_z(o0, P, vf[h].x, vf[h].y);
          mma16816_z(o1, P, vf[h].z, vf[h].w);
          mma1688(o0, pl & ~msk, 0u, pp[h].z);
          mma1688(o1, pl & ~msk, 0u, pp[h].w);
          st_ll(od + h * 32, make_uint4(set_tag(pack2(o0[0], o0[1]), tag), pack2(o0[2], o0[3]), pack2(o1[0], o1[1]), pack2(o1[2], o1[3])));
        }
      }
      TS(5 + 20 * L);
      if (L == 0) { STOP_AT(1); } else { STOP_AT(11); }
      uint4 x1own[4];
      {
        PHASE_VARS;
        float acc[32];
        uint4 A[32], xr[4];
        const uint4* os = g_arena + c * ARENA + AR_O + ((slab) * 32) * 32 + lane;
        uint4* xp = g_arena + c * ARENA + AR_XRAW + ((slab) * 32 + 4 * j) * 32 + lane;
        load_pk<4>(xr, xp);
        spin_for(L ? D_O1 : D_O0);
        load_pk<4>(A, os);
        ensure_pk<4>(A, os, tag);
        TS(6 + 20 * L);
        load_pk<28>(A + 4, os + 128);
        static_for<0, 8>([&](auto I) {
          constexpr int kb = I.value;
          if constexpr ((kb & 1) == 0) cons_acquire<ST_WO + kb / 2>(sbase, L);
          if constexpr (kb > 0) ensure_pk<4>(A + 4 * kb, os + kb * 128, tag);
          wg_fence();
          static_for<0, 4>([&](auto K) {
            constexpr int k = K.value;
            wgmma_n64<kb == 0 && k == 0, 0>(acc, A[4 * kb + k], st_desc<ST_WO + kb / 2, 2048, 8192, 1024, 1>(4 * (kb & 1) + k));
          });
          wg_commit();
          if constexpr ((kb & 1) == 0 && kb > 0) { wg_wait<1>(); cons_release<ST_WO + kb / 2 - 1>(sbase, lane); }
        });
        wg_wait<0>();
        TS(7 + 20 * L);
        fence_acc(acc);
#pragma unroll
        for (int k = 0; k < 32; k++) keep(A[k]);
        cons_release<ST_WO + 3>(sbase, lane);
        ensure_pk<4>(xr, xp, 1u);
#pragma unroll
        for (int i = 0; i < 4; i++) {
          acc[8 * i + 0] += bf_lo(xr[i].x); acc[8 * i + 1] += bf_hi(xr[i].x); acc[8 * i + 2] += bf_lo(xr[i].y); acc[8 * i + 3] += bf_hi(xr[i].y);
          acc[8 * i + 4] += bf_lo(xr[i].z); acc[8 * i + 5] += bf_hi(xr[i].z); acc[8 * i + 6] += bf_lo(xr[i].w); acc[8 * i + 7] += bf_hi(xr[i].w);
        }
        uint4 st = local_stats(acc);
        st.x = set_tag(st.x, tag);
        if (qc == 0) st_ll(g_arena + c * ARENA + AR_STATS + (slab * 8 + j) * 8 + qr, st);
#pragma unroll
        for (int i = 0; i < 4; i++) {
          x1own[i] = pack8(&acc[8 * i]);
          x1own[i].x = set_tag(x1own[i].x, 0u);
          st_ll(xp + i * 32, x1own[i]);
        }
      }
      TS(8 + 20 * L);
      if (L == 0) { STOP_AT(2); } else { STOP_AT(12); }
      uint4 hs[14];
      {
        PHASE_VARS;
        float acc[128];
        uint4 A[3][4];
        const uint4* xs = g_arena + c * ARENA + AR_XRAW + ((slab) * 32) * 32 + lane;
        const uint4* sp = g_arena + c * ARENA + AR_STATS + (slab * 8 + 2 * qc) * 8 + qr;
        const uint32_t sm = areg + t128 * 16;
        uint32_t rl2, rh2, bl2, bh2;
        float cl, ch;
        auto xsrc = [&](int p) { return xs + ((j + p) & 7) * 128; };
        {
          uint4 p[2];
#pragma unroll
          for (int k = 0; k < 4; k++) A[0][k] = x1own[k];
          spin_for(L ? D_ST1 : D_ST0);
          p[0] = ld_ll(sp); p[1] = ld_ll(sp + 8);
          load_pk<4>(A[1], xsrc(1));
          for (uint32_t n = 0; !ok_pk<2>(p, tag) && n < SPIN_LIMIT; n++) { p[0] = ld_ll(sp); p[1] = ld_ll(sp + 8); }
          TS(9 + 20 * L);
          float ml, rl, mh, rh;
          combine_stats(p[0], p[1], ml, rl, mh, rh);
          rl2 = pack2(rl, rl); rh2 = pack2(rh, rh);
          const float rlb = bf_lo(rl2), rhb = bf_lo(rh2);
          bl2 = pack2(-ml * rlb, -ml * rlb); bh2 = pack2(-mh * rhb, -mh * rhb);
          cl = rl / rlb; cl *= cl; ch = rh / rhb; ch *= ch;
        }
        auto normalise = [&](uint4 (&xb)[4], int kb) {
#pragma unroll
          for (int k = 0; k < 4; k++) {
            xb[k].x = hfma2(xb[k].x, rl2, bl2); xb[k].y = hfma2(xb[k].y, rh2, bh2);
            xb[k].z = hfma2(xb[k].z, rl2, bl2); xb[k].w = hfma2(xb[k].w, rh2, bh2);
            sts128(sm + (kb * 4 + k) * 2048, xb[k]);
          }
        };
        normalise(A[0], 0);
        static_for<0, 8>([&](auto I) {
          constexpr int kb = I.value;
          cons_acquire<ST_G1 + 2 * kb>(sbase, L);
          wg_fence();
          wgmma_n256<kb == 0, 0>(acc, A[kb % 3][0], st_desc<ST_G1 + 2 * kb, 2048, 4096, 1024, 1>(0));
          wgmma_n256<false, 0>(acc, A[kb % 3][1], st_desc<ST_G1 + 2 * kb, 2048, 4096, 1024, 1>(1));
          wg_commit();
          cons_acquire<ST_G1 + 2 * kb + 1>(sbase, L);
          __syncwarp();
          wg_fence();
          wgmma_n256<false, 0>(acc, A[kb % 3][2], st_desc<ST_G1 + 2 * kb + 1, 2048, 4096, 1024, 1>(0));
          wgmma_n256<false, 0>(acc, A[kb % 3][3], st_desc<ST_G1 + 2 * kb + 1, 2048, 4096, 1024, 1>(1));
          wg_commit();
          wg_wait<1>();
          if constexpr (kb > 0) {
            keep4(A[(kb + 2) % 3]);
            cons_release<ST_G1 + 2 * kb - 1>(sbase, lane);
          }
          cons_release<ST_G1 + 2 * kb>(sbase, lane);
          if constexpr (kb + 1 < 8) ensure_pk<4>(A[(kb + 1) % 3], xsrc(kb + 1), 0u);
          if constexpr (kb + 2 < 8) load_pk<4>(A[(kb + 2) % 3], xsrc(kb + 2));
          if constexpr (kb + 1 < 8) normalise(A[(kb + 1) % 3], kb + 1);
        });
        wg_wait<0>();
        TS(10 + 20 * L);
        fence_acc(acc);
        keep4(A[1]);
        cons_release<ST_G1 + 15>(sbase, lane);
        uint4 B[2][4];
#pragma unroll
        for (int k = 0; k < 4; k++) B[0][k] = lds128(sm + k * 2048);
#pragma unroll
        for (int s = 0; s < 8; s++) hs[s] = glu8<32>(&acc[64 * (s >> 2) + 8 * (s & 3)], cl, ch);
        float acc2[96];
        const uint32_t hdst = mapa(sm, cbit ^ 1);
        const uint32_t hbar1 = mapa(bars + BAR_HRECV + 16 * g, cbit ^ 1);
        if (t128 == 0) { mbar_expect_tx(bars + BAR_HRECV + 16 * g, 8 * 2048); mbar_expect_tx(bars + BAR_HRECV + 16 * g + 8, 6 * 2048); }
        static_for<0, 8>([&](auto I) {
          constexpr int kb = I.value;
          cons_acquire<ST_G2 + kb>(sbase, L);
          wg_fence();
          static_for<0, 4>([&](auto K) {
            constexpr int k = K.value;
            wgmma_n128<kb == 0 && k == 0, 0>(acc2, B[kb & 1][k], st_desc<ST_G2 + kb, 2048, 8192, 1024, 1>(k));
            wgmma_n64<kb == 0 && k == 0, 64>(acc2, B[kb & 1][k], st_desc<ST_G2 + kb, 1024, 4096, 512, 2>(k) + (16384 >> 4));
          });
          wg_commit();
          if constexpr (kb > 0) {
            wg_wait<1>();
            keep4(B[(kb + 1) & 1]);
            cons_release<ST_G2 + kb - 1>(sbase, lane);
          }
          if constexpr (kb + 1 < 8) {
#pragma unroll
            for (int k = 0; k < 4; k++) B[(kb + 1) & 1][k] = lds128(sm + ((kb + 1) * 4 + k) * 2048);
          }
          if constexpr (kb == 3) {
            __syncwarp();
            if (lane == 0) mbar_arrive_remote(mapa(bars + BAR_HREADY + 8 * g, cbit ^ 1));
          }
          if constexpr (kb >= 4) {
            if constexpr (kb == 4) mbar_wait(bars + BAR_HREADY + 8 * g, L);
            st_async128(hdst + (2 * kb - 8) * 2048, hs[2 * kb - 8], hbar1);
            st_async128(hdst + (2 * kb - 7) * 2048, hs[2 * kb - 7], hbar1);
          }
        });
        wg_wait<0>();
        TS(11 + 20 * L);
        fence_acc(acc2);
        keep4(B[1]);
        cons_release<ST_G2 + 7>(sbase, lane);
#pragma unroll
        for (int s = 0; s < 4; s++) hs[8 + s] = glu8<32>(&acc2[8 * s], cl, ch);
#pragma unroll
        for (int s = 0; s < 2; s++) hs[12 + s] = glu8<16>(&acc2[64 + 8 * s], cl, ch);
      }
      {
        PHASE_VARS;
        TS(12 + 20 * L);
        const uint32_t hdst = mapa(areg + t128 * 16, cbit ^ 1);
        const uint32_t hbar2 = mapa(bars + BAR_HRECV + 16 * g + 8, cbit ^ 1);
        uint4* pd = g_arena + c * ARENA + AR_PART + (((slab * 2 + cbit) * 4 + ca) * 16) * 32 + lane;
        const uint4* ps = g_arena + c * ARENA + AR_PART + (((j * 2 + g) * 4) * 16 + 4 * w) * 32 + lane;
        auto fetch_partials = [&]() {
#pragma unroll
          for (int src = 0; src < 4; src++)
#pragma unroll
            for (int k = 0; k < 4; k++) cp_async16(areg + t128 * 16 + (14 + 4 * src + k) * 2048, ps + src * (16 * 32) + k * 32);
        };
        uint4 hb[7];
        float a0[32], a1[32], a2[32], a3[32];
        auto publish = [&](float (&a)[32], int q, int s0, int s1) {
#pragma unroll
          for (int s = s0; s < s1; s++) {
            uint4 o = pack8(&a[8 * s]);
            o.x = set_tag(o.x, tag);
            st_ll(pd + (4 * q + s) * 32, o);
          }
        };
        static_for<0, 16>([&](auto I) {
          constexpr int i = I.value, q = dn_q(i), par = dn_par(i), kh = dn_kh(i);
          auto mm = [&](auto K) {
            constexpr int k = decltype(K)::value;
            constexpr bool init = (k == 0 && par == 0 && kh == 0);
            constexpr uint64_t db = st_desc<ST_DN + i, 2048, 8192, 1024, 1>(k);
            if constexpr (q == 0) { if constexpr (par) wgmma_n64<init, 0>(a0, hb[k], db); else wgmma_n64<init, 0>(a0, hs[7 * kh + k], db); }
            if constexpr (q == 1) { if constexpr (par) wgmma_n64<init, 0>(a1, hb[k], db); else wgmma_n64<init, 0>(a1, hs[7 * kh + k], db); }
            if constexpr (q == 2) { if constexpr (par) wgmma_n64<init, 0>(a2, hb[k], db); else wgmma_n64<init, 0>(a2, hs[7 * kh + k], db); }
            if constexpr (q == 3) { if constexpr (par) wgmma_n64<init, 0>(a3, hb[k], db); else wgmma_n64<init, 0>(a3, hs[7 * kh + k], db); }
          };
          cons_acquire<ST_DN + i>(sbase, L);
          wg_fence();
          mm(IC<0>{}); mm(IC<1>{}); mm(IC<2>{}); mm(IC<3>{}); mm(IC<4>{}); mm(IC<5>{}); mm(IC<6>{});
          wg_commit();
          if constexpr (i > 0) { wg_wait<1>(); cons_release<ST_DN + i - 1>(sbase, lane); }
          if constexpr (i < 3) {
            st_async128(hdst + (8 + 2 * i) * 2048, hs[8 + 2 * i], hbar2);
            st_async128(hdst + (9 + 2 * i) * 2048, hs[9 + 2 * i], hbar2);
          }
          constexpr int n = i + 1;
          if constexpr (n < 16 && dn_par(n) && n != 4 && n != 7) {
            if constexpr (n == 2) { mbar_wait(bars + BAR_HRECV + 16 * g, L); TS(13 + 20 * L); }
            if constexpr (n == 6) { mbar_wait(bars + BAR_HRECV + 16 * g + 8, L); TS(14 + 20 * L); }
#pragma unroll
            for (int k = 0; k < 7; k++) { if constexpr (n != 2) keep(hb[k]); hb[k] = lds128(areg + t128 * 16 + (7 * dn_kh(n) + k) * 2048); }
          }
          if constexpr (i == 7) { fence_acc(a0); publish(a0, 0, 0, 4); }
          if constexpr (i == 8) { fence_acc(a1); publish(a1, 1, 0, 2); }
          if constexpr (i == 9) publish(a1, 1, 2, 4);
          if constexpr (i == 12) { fence_acc(a2); publish(a2, 2, 0, 2); }
          if constexpr (i == 13) publish(a2, 2, 2, 4);
          if constexpr (i == 10) { if (w == 0) fetch_partials(); }
          if constexpr (i == 12) { if (w == 1) fetch_partials(); }
        });
        wg_wait<0>();
        TS(15 + 20 * L);
        fence_acc(a3);
#pragma unroll
        for (int k = 0; k < 7; k++) { keep(hb[k]); keep(hs[7 + k]); }
        cons_release<NSTAGE - 1>(sbase, lane);
        publish(a3, 3, 0, 4);
        if (w >= 2) { spin_for(L ? D_PT1 : D_PT0); fetch_partials(); }
      }
      {
        PHASE_VARS;
        const uint4* xq = g_arena + c * ARENA + AR_XRAW + ((j) * 32 + 4 * warp) * 32 + lane;
        const uint4* ps = g_arena + c * ARENA + AR_PART + (((j * 2 + g) * 4) * 16 + 4 * w) * 32 + lane;
        uint4 xr[4], P[4][4];
        float v[32];
        load_pk<4>(xr, xq);
        cp_wait_all();
#pragma unroll
        for (int k = 0; k < 16; k++) P[k >> 2][k & 3] = lds128(areg + t128 * 16 + (14 + k) * 2048);
        for (uint32_t n = 0; !ok_pk<16>(&P[0][0], tag) && n < SPIN_LIMIT; n++) {
#pragma unroll
          for (int src = 0; src < 4; src++) load_pk<4>(P[src], ps + src * (16 * 32));
        }
        TS(16 + 20 * L);
        ensure_pk<4>(xr, xq, 0u);
#pragma unroll
        for (int i = 0; i < 4; i++) {
          v[8 * i + 0] = bf_lo(xr[i].x); v[8 * i + 1] = bf_hi(xr[i].x); v[8 * i + 2] = bf_lo(xr[i].y); v[8 * i + 3] = bf_hi(xr[i].y);
          v[8 * i + 4] = bf_lo(xr[i].z); v[8 * i + 5] = bf_hi(xr[i].z); v[8 * i + 6] = bf_lo(xr[i].w); v[8 * i + 7] = bf_hi(xr[i].w);
          float d[8] = {0, 0, 0, 0, 0, 0, 0, 0};
#pragma unroll
          for (int src = 0; src < 4; src++) {
            const uint4 p = P[src][i];
            d[0] += bf_lo(p.x); d[1] += bf_hi(p.x); d[2] += bf_lo(p.y); d[3] += bf_hi(p.y);
            d[4] += bf_lo(p.z); d[5] += bf_hi(p.z); d[6] += bf_lo(p.w); d[7] += bf_hi(p.w);
          }
#pragma unroll
          for (int k = 0; k < 8; k++) v[8 * i + k] += d[k];
        }
        if (L == 0) {
          owner_ln_publish(sbase, v, 1u, 0u, xraw);
        } else {
#pragma unroll
          for (int i = 0; i < 4; i++) xraw[i] = make_uint4(0, 0, 0, 0);
          uint32_t* op = reinterpret_cast<uint32_t*>(out + (size_t)(slab_row0(c, j >> 2, j & 3) + 2 * qr) * 512 + warp * 64 + qc * 2);
#pragma unroll
          for (int i = 0; i < 4; i++) {
            op[i * 8] = pack2(v[8 * i], v[8 * i + 1]);
            op[16 * 256 + i * 8] = pack2(v[8 * i + 2], v[8 * i + 3]);
            op[i * 8 + 4] = pack2(v[8 * i + 4], v[8 * i + 5]);
            op[16 * 256 + i * 8 + 4] = pack2(v[8 * i + 6], v[8 * i + 7]);
          }
        }
      }
      TS(17 + 20 * L);
      if (L == 0) { STOP_AT(3); }
    }
    TG(62);
    TG(63);
  }
}

typedef CUresult (*EncodeFn)(CUtensorMap*, CUtensorMapDataType, cuuint32_t, void*, const cuuint64_t*, const cuuint64_t*,
                             const cuuint32_t*, const cuuint32_t*, CUtensorMapInterleave, CUtensorMapSwizzle,
                             CUtensorMapL2promotion, CUtensorMapFloatOOBfill);

void encode(EncodeFn fn, CUtensorMap* m, int rank, const void* base, const cuuint64_t* dims, const cuuint64_t* strides,
            const cuuint32_t* box, CUtensorMapSwizzle sw) {
  cuuint32_t es[5] = {1, 1, 1, 1, 1};
  fn(m, CU_TENSOR_MAP_DATA_TYPE_BFLOAT16, (cuuint32_t)rank, const_cast<void*>(base), dims, strides, box, es,
     CU_TENSOR_MAP_INTERLEAVE_NONE, sw, CU_TENSOR_MAP_L2_PROMOTION_L2_128B, CU_TENSOR_MAP_FLOAT_OOB_FILL_NONE);
}

}

extern "C" void kernel_launch(void* const* d_in, const int* in_sizes, int n_in, void* d_out, int out_size) {
  (void)in_sizes; (void)n_in; (void)out_size;
  const __nv_bfloat16* x = (const __nv_bfloat16*)d_in[0];
  const char* wqkv = (const char*)d_in[1];
  const char* wo = (const char*)d_in[2];
  const char* wg = (const char*)d_in[4];
  const char* wu = (const char*)d_in[5];
  const char* wd = (const char*)d_in[6];

  static EncodeFn fn = nullptr;
  if (!fn) {
    void* p = nullptr;
    cudaDriverEntryPointQueryResult st;
    cudaGetDriverEntryPoint("cuTensorMapEncodeTiled", &p, cudaEnableDefault, &st);
    fn = (EncodeFn)p;
    cudaFuncSetAttribute(fused_kernel, cudaFuncAttributeMaxDynamicSharedMemorySize, SMEM_BYTES);
  }
  CUtensorMap m_qkv, m_wo, m_gu2, m_gu1, m_guh, m_wd112, m_wd80, m_wd32;
  {
    cuuint64_t dims[3] = {512, 512, 3}, str[2] = {3072, 1024};
    cuuint32_t box[3] = {64, 64, 3};
    encode(fn, &m_qkv, 3, wqkv, dims, str, box, CU_TENSOR_MAP_SWIZZLE_128B);
  }
  {
    cuuint64_t dims[2] = {512, 512}, str[1] = {1024};
    cuuint32_t box[2] = {64, 128};
    encode(fn, &m_wo, 2, wo, dims, str, box, CU_TENSOR_MAP_SWIZZLE_128B);
  }
  {
    const char* lo = wg < wu ? wg : wu;
    cuuint64_t diff = (cuuint64_t)(wg < wu ? wu - wg : wg - wu);
    cuuint64_t dims[4] = {1792, 512, 2, 2}, str[3] = {3584, diff, 128};
    cuuint32_t box2[4] = {64, 32, 2, 2}, box1[4] = {64, 64, 2, 1}, boxh[3] = {32, 64, 2};
    encode(fn, &m_gu2, 4, lo, dims, str, box2, CU_TENSOR_MAP_SWIZZLE_128B);
    encode(fn, &m_gu1, 4, lo, dims, str, box1, CU_TENSOR_MAP_SWIZZLE_128B);
    encode(fn, &m_guh, 3, lo, dims, str, boxh, CU_TENSOR_MAP_SWIZZLE_64B);
  }
  {
    cuuint64_t dims[2] = {512, 1792}, str[1] = {1024};
    cuuint32_t b112[2] = {64, 112}, b80[2] = {64, 80}, b32[2] = {64, 32};
    encode(fn, &m_wd112, 2, wd, dims, str, b112, CU_TENSOR_MAP_SWIZZLE_128B);
    encode(fn, &m_wd80, 2, wd, dims, str, b80, CU_TENSOR_MAP_SWIZZLE_128B);
    encode(fn, &m_wd32, 2, wd, dims, str, b32, CU_TENSOR_MAP_SWIZZLE_128B);
  }
  cudaLaunchConfig_t cfg = {};
  cfg.gridDim = dim3(128);
  cfg.blockDim = dim3(NTHREADS);
  cfg.dynamicSmemBytes = SMEM_BYTES;
  cfg.stream = cudaStreamPerThread;
  cudaLaunchAttribute at[1];
  at[0].id = cudaLaunchAttributeClusterDimension;
  at[0].val.clusterDim.x = 2; at[0].val.clusterDim.y = 1; at[0].val.clusterDim.z = 1;
  cfg.attrs = at; cfg.numAttrs = 1;
  cudaLaunchKernelEx(&cfg, fused_kernel, m_qkv, m_wo, m_gu2, m_gu1, m_guh, m_wd112, m_wd80, m_wd32, x, (__nv_bfloat16*)d_out
  );
}
```

```cpp
#include <cuda_runtime.h>
#include <cuda_bf16.h>
#include <cuda.h>
#include <stdint.h>

namespace {

constexpr int NTHREADS = 384;
constexpr int GRAN = 8192;
constexpr int NGRAN = 12;
constexpr int SM_AREG = NGRAN * GRAN;
constexpr int SM_MISC = SM_AREG + 131072;
constexpr int SM_TSTAT = SM_MISC + 256;
constexpr int SMEM_BYTES = SM_TSTAT + 1024;
constexpr int BAR_FULL = 0, BAR_EMPTY = 96, BAR_HRECV = 192, BAR_HREADY = 224;

constexpr int AR_XN = 0, AR_XRAW = 8192, AR_O = 16384, AR_STATS = 24576, AR_HALO = 25088, AR_PART = 33280, ARENA = 66048;
__device__ __align__(1024) uint4 g_arena[16 * ARENA];

#define TS(n)
#define TG(n)
#define TF(cond, n)
#define TV(n, v)
#define OPAQUE(x) asm volatile("" : "+r"(x))
#define PHASE_VARS                                                                                   \
  int tid_ = threadIdx.x, bid_ = blockIdx.x;                                                         \
  OPAQUE(tid_); OPAQUE(bid_);                                                                        \
  const int lane = tid_ & 31, warp = tid_ >> 5, g = warp >> 2, w = warp & 3, t128 = tid_ & 127;      \
  const int qr = lane >> 2, qc = lane & 3, slab = warp;                                              \
  const int c = bid_ >> 3, j = bid_ & 7, ca = j >> 1, cbit = j & 1;                                  \
  const uint32_t areg = sbase + SM_AREG + g * 65536;                                                 \
  (void)g; (void)j; (void)w; (void)t128; (void)qr; (void)qc; (void)slab; (void)c; (void)ca; (void)cbit; (void)areg; (void)lane
#define STOP_AT(n)
#define PSTOP_AT(n)

__device__ __forceinline__ uint32_t smem_u32(const void* p) { return (uint32_t)__cvta_generic_to_shared(p); }
__device__ __forceinline__ void mbar_init(uint32_t bar, uint32_t cnt) {
  asm volatile("mbarrier.init.shared::cta.b64 [%0], %1;" ::"r"(bar), "r"(cnt) : "memory");
}
__device__ __forceinline__ void mbar_expect_tx(uint32_t bar, uint32_t bytes) {
  asm volatile("mbarrier.arrive.expect_tx.shared::cta.b64 _, [%0], %1;" ::"r"(bar), "r"(bytes) : "memory");
}
__device__ __forceinline__ void mbar_arrive(uint32_t bar) {
  asm volatile("mbarrier.arrive.shared::cta.b64 _, [%0];" ::"r"(bar) : "memory");
}
__device__ __forceinline__ void mbar_arrive_remote(uint32_t cluster_addr) {
  asm volatile("mbarrier.arrive.relaxed.cluster.shared::cluster.b64 _, [%0];" ::"r"(cluster_addr) : "memory");
}
__device__ __forceinline__ bool mbar_try(uint32_t bar, uint32_t parity) {
  uint32_t ok;
  asm volatile("{\n.reg .pred p;\nmbarrier.try_wait.parity.shared::cta.b64 p, [%1], %2;\nselp.u32 %0, 1, 0, p;\n}"
               : "=r"(ok) : "r"(bar), "r"(parity) : "memory");
  return ok != 0;
}
constexpr uint32_t SPIN_LIMIT = 1u << 16;
constexpr uint32_t SMEM_ORIGIN = 1024;
__device__ __forceinline__ void mbar_wait(uint32_t bar, uint32_t parity) {
  for (uint32_t n = 0; !mbar_try(bar, parity) && n < SPIN_LIMIT; n++) {}
}
__device__ __forceinline__ uint32_t mapa(uint32_t addr, uint32_t rank) {
  uint32_t r;
  asm volatile("mapa.shared::cluster.u32 %0, %1, %2;" : "=r"(r) : "r"(addr), "r"(rank));
  return r;
}

__device__ __forceinline__ void tma_2d(uint32_t dst, const CUtensorMap* m, uint32_t bar, int c0, int c1) {
  asm volatile("cp.async.bulk.tensor.2d.shared::cluster.global.mbarrier::complete_tx::bytes [%0], [%1, {%3, %4}], [%2];"
               ::"r"(dst), "l"(m), "r"(bar), "r"(c0), "r"(c1) : "memory");
}
__device__ __forceinline__ void tma_3d(uint32_t dst, const CUtensorMap* m, uint32_t bar, int c0, int c1, int c2) {
  asm volatile("cp.async.bulk.tensor.3d.shared::cluster.global.mbarrier::complete_tx::bytes [%0], [%1, {%3, %4, %5}], [%2];"
               ::"r"(dst), "l"(m), "r"(bar), "r"(c0), "r"(c1), "r"(c2) : "memory");
}
__device__ __forceinline__ void tma_4d(uint32_t dst, const CUtensorMap* m, uint32_t bar, int c0, int c1, int c2, int c3) {
  asm volatile("cp.async.bulk.tensor.4d.shared::cluster.global.mbarrier::complete_tx::bytes [%0], [%1, {%3, %4, %5, %6}], [%2];"
               ::"r"(dst), "l"(m), "r"(bar), "r"(c0), "r"(c1), "r"(c2), "r"(c3) : "memory");
}

__device__ __forceinline__ uint4 ld_ll(const uint4* p) {
  uint4 v;
  asm volatile("ld.relaxed.gpu.global.v4.u32 {%0,%1,%2,%3}, [%4];" : "=r"(v.x), "=r"(v.y), "=r"(v.z), "=r"(v.w) : "l"(p) : "memory");
  return v;
}
__device__ __forceinline__ void st_ll(uint4* p, uint4 v) {
  asm volatile("st.relaxed.gpu.global.v4.u32 [%0], {%1,%2,%3,%4};" ::"l"(p), "r"(v.x), "r"(v.y), "r"(v.z), "r"(v.w) : "memory");
}
__device__ __forceinline__ uint4 lds128(uint32_t a) {
  uint4 v;
  asm volatile("ld.shared.v4.u32 {%0,%1,%2,%3}, [%4];" : "=r"(v.x), "=r"(v.y), "=r"(v.z), "=r"(v.w) : "r"(a) : "memory");
  return v;
}
__device__ __forceinline__ void sts128(uint32_t a, uint4 v) {
  asm volatile("st.shared.v4.u32 [%0], {%1,%2,%3,%4};" ::"r"(a), "r"(v.x), "r"(v.y), "r"(v.z), "r"(v.w) : "memory");
}
__device__ __forceinline__ void st_async128(uint32_t cluster_addr, uint4 v, uint32_t cluster_bar) {
  asm volatile("st.async.weak.shared::cluster.mbarrier::complete_tx::bytes.v4.b32 [%0], {%1,%2,%3,%4}, [%5];"
               ::"r"(cluster_addr), "r"(v.x), "r"(v.y), "r"(v.z), "r"(v.w), "r"(cluster_bar) : "memory");
}
__device__ __forceinline__ uint32_t pack2(float lo, float hi) {
  uint32_t r;
  asm("cvt.rn.bf16x2.f32 %0, %1, %2;" : "=r"(r) : "f"(hi), "f"(lo));
  return r;
}
__device__ __forceinline__ float bf_lo(uint32_t w) { return __uint_as_float(w << 16); }
__device__ __forceinline__ float bf_hi(uint32_t w) { return __uint_as_float(w & 0xffff0000u); }
__device__ __forceinline__ uint32_t set_tag(uint32_t w, uint32_t tag) { return (w & ~1u) | tag; }
__device__ __forceinline__ uint32_t movm(uint32_t a) {
  uint32_t d;
  asm("movmatrix.sync.aligned.m8n8.trans.b16 %0, %1;" : "=r"(d) : "r"(a));
  return d;
}
__device__ __forceinline__ void mma1688(float (&d)[4], uint32_t a0, uint32_t a1, uint32_t b0) {
  asm("mma.sync.aligned.m16n8k8.row.col.f32.bf16.bf16.f32 {%0,%1,%2,%3}, {%4,%5}, {%6}, {%0,%1,%2,%3};"
      : "+f"(d[0]), "+f"(d[1]), "+f"(d[2]), "+f"(d[3])
      : "r"(a0), "r"(a1), "r"(b0));
}
__device__ __forceinline__ void mma16816_z(float (&d)[4], const uint4& a, uint32_t b0, uint32_t b1) {
  asm("mma.sync.aligned.m16n8k16.row.col.f32.bf16.bf16.f32 {%0,%1,%2,%3}, {%4,%5,%6,%7}, {%8,%9}, {%10,%10,%10,%10};"
      : "=f"(d[0]), "=f"(d[1]), "=f"(d[2]), "=f"(d[3])
      : "r"(a.x), "r"(a.y), "r"(a.z), "r"(a.w), "r"(b0), "r"(b1), "f"(0.f));
}
__device__ __forceinline__ float ex2(float x) {
  float y;
  asm("ex2.approx.ftz.f32 %0, %1;" : "=f"(y) : "f"(x));
  return y;
}
__device__ __forceinline__ float rcp(float x) {
  float y;
  asm("rcp.approx.ftz.f32 %0, %1;" : "=f"(y) : "f"(x));
  return y;
}
__device__ __forceinline__ void cp_async16(uint32_t dst, const void* src) {
  asm volatile("cp.async.cg.shared.global [%0], [%1], 16;" ::"r"(dst), "l"(src) : "memory");
}
__device__ __forceinline__ void cp_wait_all() { asm volatile("cp.async.wait_all;" ::: "memory"); }
template <int N> __device__ __forceinline__ void cp_wait() { asm volatile("cp.async.wait_group %0;" ::"n"(N) : "memory"); }
__device__ __forceinline__ void bar_wg(int id) { asm volatile("bar.sync %0, 128;" ::"r"(id) : "memory"); }
__device__ __forceinline__ void spin_for(uint32_t clks) {
  const uint32_t t0 = (uint32_t)clock();
  while ((uint32_t)clock() - t0 < clks) {}
}
#define D_XN0 1200
#define D_XN1 500
#define D_HALO0 1200
#define D_HALO1 500
#define D_O0 1200
#define D_O1 500
#define D_ST0 1200
#define D_ST1 500
#define D_PT0 0
#define D_PT1 0
__device__ __forceinline__ void wg_fence() { asm volatile("wgmma.fence.sync.aligned;" ::: "memory"); }
__device__ __forceinline__ void wg_commit() { asm volatile("wgmma.commit_group.sync.aligned;" ::: "memory"); }
template <int N> __device__ __forceinline__ void wg_wait() { asm volatile("wgmma.wait_group.sync.aligned %0;" ::"n"(N) : "memory"); }
__device__ __forceinline__ void keep(const uint4& a) { asm volatile("" ::"r"(a.x), "r"(a.y), "r"(a.z), "r"(a.w) : "memory"); }
template <int T> __device__ __forceinline__ void zero_acc(float (&d)[T]) {
#pragma unroll
  for (int i = 0; i < T; i++) d[i] = 0.f;
}
template <int T> __device__ __forceinline__ void fence_acc(float (&d)[T]) {
#pragma unroll
  for (int i = 0; i < T; i++) asm volatile("" : "+f"(d[i])::"memory");
}

template <int O, int T> __device__ __forceinline__ void wgmma_rs_n64(float (&d)[T], const uint4& a, uint64_t db) {
  asm volatile("{\n.reg .pred p;\nsetp.ne.b32 p, 1, 0;\n"
    "wgmma.mma_async.sync.aligned.m64n64k16.f32.bf16.bf16 "
    "{%0, %1, %2, %3, %4, %5, %6, %7, %8, %9, %10, %11, %12, %13, %14, %15, "
    "%16, %17, %18, %19, %20, %21, %22, %23, %24, %25, %26, %27, %28, %29, %30, %31}, "
    "{%32, %33, %34, %35}, %36, p, 1, 1, 1;\n}\n"
    : "+f"(d[O + 0]), "+f"(d[O + 1]), "+f"(d[O + 2]), "+f"(d[O + 3]), "+f"(d[O + 4]), "+f"(d[O + 5]), "+f"(d[O + 6]), "+f"(d[O + 7]),
      "+f"(d[O + 8]), "+f"(d[O + 9]), "+f"(d[O + 10]), "+f"(d[O + 11]), "+f"(d[O + 12]), "+f"(d[O + 13]), "+f"(d[O + 14]), "+f"(d[O + 15]),
      "+f"(d[O + 16]), "+f"(d[O + 17]), "+f"(d[O + 18]), "+f"(d[O + 19]), "+f"(d[O + 20]), "+f"(d[O + 21]), "+f"(d[O + 22]), "+f"(d[O + 23]),
      "+f"(d[O + 24]), "+f"(d[O + 25]), "+f"(d[O + 26]), "+f"(d[O + 27]), "+f"(d[O + 28]), "+f"(d[O + 29]), "+f"(d[O + 30]), "+f"(d[O + 31])
    : "r"(a.x), "r"(a.y), "r"(a.z), "r"(a.w), "l"(db));
}
template <int O, int T> __device__ __forceinline__ void wgmma_rs_n64_init(float (&d)[T], const uint4& a, uint64_t db) {
  asm volatile("{\n.reg .pred p;\nsetp.ne.b32 p, 0, 0;\n"
    "wgmma.mma_async.sync.aligned.m64n64k16.f32.bf16.bf16 "
    "{%0, %1, %2, %3, %4, %5, %6, %7, %8, %9, %10, %11, %12, %13, %14, %15, "
    "%16, %17, %18, %19, %20, %21, %22, %23, %24, %25, %26, %27, %28, %29, %30, %31}, "
    "{%32, %33, %34, %35}, %36, p, 1, 1, 1;\n}\n"
    : "=f"(d[O + 0]), "=f"(d[O + 1]), "=f"(d[O + 2]), "=f"(d[O + 3]), "=f"(d[O + 4]), "=f"(d[O + 5]), "=f"(d[O + 6]), "=f"(d[O + 7]),
      "=f"(d[O + 8]), "=f"(d[O + 9]), "=f"(d[O + 10]), "=f"(d[O + 11]), "=f"(d[O + 12]), "=f"(d[O + 13]), "=f"(d[O + 14]), "=f"(d[O + 15]),
      "=f"(d[O + 16]), "=f"(d[O + 17]), "=f"(d[O + 18]), "=f"(d[O + 19]), "=f"(d[O + 20]), "=f"(d[O + 21]), "=f"(d[O + 22]), "=f"(d[O + 23]),
      "=f"(d[O + 24]), "=f"(d[O + 25]), "=f"(d[O + 26]), "=f"(d[O + 27]), "=f"(d[O + 28]), "=f"(d[O + 29]), "=f"(d[O + 30]), "=f"(d[O + 31])
    : "r"(a.x), "r"(a.y), "r"(a.z), "r"(a.w), "l"(db));
}
template <bool INIT, int O, int T> __device__ __forceinline__ void wgmma_n64(float (&d)[T], const uint4& a, uint64_t db) {
  if constexpr (INIT) wgmma_rs_n64_init<O>(d, a, db); else wgmma_rs_n64<O>(d, a, db);
}
template <int O, int T> __device__ __forceinline__ void wgmma_rs_n128(float (&d)[T], const uint4& a, uint64_t db) {
  asm volatile("{\n.reg .pred p;\nsetp.ne.b32 p, 1, 0;\n"
    "wgmma.mma_async.sync.aligned.m64n128k16.f32.bf16.bf16 "
    "{%0, %1, %2, %3, %4, %5, %6, %7, %8, %9, %10, %11, %12, %13, %14, %15, "
    "%16, %17, %18, %19, %20, %21, %22, %23, %24, %25, %26, %27, %28, %29, %30, %31, "
    "%32, %33, %34, %35, %36, %37, %38, %39, %40, %41, %42, %43, %44, %45, %46, %47, "
    "%48, %49, %50, %51, %52, %53, %54, %55, %56, %57, %58, %59, %60, %61, %62, %63}, "
    "{%64, %65, %66, %67}, %68, p, 1, 1, 1;\n}\n"
    : "+f"(d[O + 0]), "+f"(d[O + 1]), "+f"(d[O + 2]), "+f"(d[O + 3]), "+f"(d[O + 4]), "+f"(d[O + 5]), "+f"(d[O + 6]), "+f"(d[O + 7]),
      "+f"(d[O + 8]), "+f"(d[O + 9]), "+f"(d[O + 10]), "+f"(d[O + 11]), "+f"(d[O + 12]), "+f"(d[O + 13]), "+f"(d[O + 14]), "+f"(d[O + 15]),
      "+f"(d[O + 16]), "+f"(d[O + 17]), "+f"(d[O + 18]), "+f"(d[O + 19]), "+f"(d[O + 20]), "+f"(d[O + 21]), "+f"(d[O + 22]), "+f"(d[O + 23]),
      "+f"(d[O + 24]), "+f"(d[O + 25]), "+f"(d[O + 26]), "+f"(d[O + 27]), "+f"(d[O + 28]), "+f"(d[O + 29]), "+f"(d[O + 30]), "+f"(d[O + 31]),
      "+f"(d[O + 32]), "+f"(d[O + 33]), "+f"(d[O + 34]), "+f"(d[O + 35]), "+f"(d[O + 36]), "+f"(d[O + 37]), "+f"(d[O + 38]), "+f"(d[O + 39]),
      "+f"(d[O + 40]), "+f"(d[O + 41]), "+f"(d[O + 42]), "+f"(d[O + 43]), "+f"(d[O + 44]), "+f"(d[O + 45]), "+f"(d[O + 46]), "+f"(d[O + 47]),
      "+f"(d[O + 48]), "+f"(d[O + 49]), "+f"(d[O + 50]), "+f"(d[O + 51]), "+f"(d[O + 52]), "+f"(d[O + 53]), "+f"(d[O + 54]), "+f"(d[O + 55]),
      "+f"(d[O + 56]), "+f"(d[O + 57]), "+f"(d[O + 58]), "+f"(d[O + 59]), "+f"(d[O + 60]), "+f"(d[O + 61]), "+f"(d[O + 62]), "+f"(d[O + 63])
    : "r"(a.x), "r"(a.y), "r"(a.z), "r"(a.w), "l"(db));
}
template <int O, int T> __device__ __forceinline__ void wgmma_rs_n128_init(float (&d)[T], const uint4& a, uint64_t db) {
  asm volatile("{\n.reg .pred p;\nsetp.ne.b32 p, 0, 0;\n"
    "wgmma.mma_async.sync.aligned.m64n128k16.f32.bf16.bf16 "
    "{%0, %1, %2, %3, %4, %5, %6, %7, %8, %9, %10, %11, %12, %13, %14, %15, "
    "%16, %17, %18, %19, %20, %21, %22, %23, %24, %25, %26, %27, %28, %29, %30, %31, "
    "%32, %33, %34, %35, %36, %37, %38, %39, %40, %41, %42, %43, %44, %45, %46, %47, "
    "%48, %49, %50, %51, %52, %53, %54, %55, %56, %57, %58, %59, %60, %61, %62, %63}, "
    "{%64, %65, %66, %67}, %68, p, 1, 1, 1;\n}\n"
    : "=f"(d[O + 0]), "=f"(d[O + 1]), "=f"(d[O + 2]), "=f"(d[O + 3]), "=f"(d[O + 4]), "=f"(d[O + 5]), "=f"(d[O + 6]), "=f"(d[O + 7]),
      "=f"(d[O + 8]), "=f"(d[O + 9]), "=f"(d[O + 10]), "=f"(d[O + 11]), "=f"(d[O + 12]), "=f"(d[O + 13]), "=f"(d[O + 14]), "=f"(d[O + 15]),
      "=f"(d[O + 16]), "=f"(d[O + 17]), "=f"(d[O + 18]), "=f"(d[O + 19]), "=f"(d[O + 20]), "=f"(d[O + 21]), "=f"(d[O + 22]), "=f"(d[O + 23]),
      "=f"(d[O + 24]), "=f"(d[O + 25]), "=f"(d[O + 26]), "=f"(d[O + 27]), "=f"(d[O + 28]), "=f"(d[O + 29]), "=f"(d[O + 30]), "=f"(d[O + 31]),
      "=f"(d[O + 32]), "=f"(d[O + 33]), "=f"(d[O + 34]), "=f"(d[O + 35]), "=f"(d[O + 36]), "=f"(d[O + 37]), "=f"(d[O + 38]), "=f"(d[O + 39]),
      "=f"(d[O + 40]), "=f"(d[O + 41]), "=f"(d[O + 42]), "=f"(d[O + 43]), "=f"(d[O + 44]), "=f"(d[O + 45]), "=f"(d[O + 46]), "=f"(d[O + 47]),
      "=f"(d[O + 48]), "=f"(d[O + 49]), "=f"(d[O + 50]), "=f"(d[O + 51]), "=f"(d[O + 52]), "=f"(d[O + 53]), "=f"(d[O + 54]), "=f"(d[O + 55]),
      "=f"(d[O + 56]), "=f"(d[O + 57]), "=f"(d[O + 58]), "=f"(d[O + 59]), "=f"(d[O + 60]), "=f"(d[O + 61]), "=f"(d[O + 62]), "=f"(d[O + 63])
    : "r"(a.x), "r"(a.y), "r"(a.z), "r"(a.w), "l"(db));
}
template <bool INIT, int O, int T> __device__ __forceinline__ void wgmma_n128(float (&d)[T], const uint4& a, uint64_t db) {
  if constexpr (INIT) wgmma_rs_n128_init<O>(d, a, db); else wgmma_rs_n128<O>(d, a, db);
}
template <int O, int T> __device__ __forceinline__ void wgmma_rs_n192(float (&d)[T], const uint4& a, uint64_t db) {
  asm volatile("{\n.reg .pred p;\nsetp.ne.b32 p, 1, 0;\n"
    "wgmma.mma_async.sync.aligned.m64n192k16.f32.bf16.bf16 "
    "{%0, %1, %2, %3, %4, %5, %6, %7, %8, %9, %10, %11, %12, %13, %14, %15, "
    "%16, %17, %18, %19, %20, %21, %22, %23, %24, %25, %26, %27, %28, %29, %30, %31, "
    "%32, %33, %34, %35, %36, %37, %38, %39, %40, %41, %42, %43, %44, %45, %46, %47, "
    "%48, %49, %50, %51, %52, %53, %54, %55, %56, %57, %58, %59, %60, %61, %62, %63, "
    "%64, %65, %66, %67, %68, %69, %70, %71, %72, %73, %74, %75, %76, %77, %78, %79, "
    "%80, %81, %82, %83, %84, %85, %86, %87, %88, %89, %90, %91, %92, %93, %94, %95}, "
    "{%96, %97, %98, %99}, %100, p, 1, 1, 1;\n}\n"
    : "+f"(d[O + 0]), "+f"(d[O + 1]), "+f"(d[O + 2]), "+f"(d[O + 3]), "+f"(d[O + 4]), "+f"(d[O + 5]), "+f"(d[O + 6]), "+f"(d[O + 7]),
      "+f"(d[O + 8]), "+f"(d[O + 9]), "+f"(d[O + 10]), "+f"(d[O + 11]), "+f"(d[O + 12]), "+f"(d[O + 13]), "+f"(d[O + 14]), "+f"(d[O + 15]),
      "+f"(d[O + 16]), "+f"(d[O + 17]), "+f"(d[O + 18]), "+f"(d[O + 19]), "+f"(d[O + 20]), "+f"(d[O + 21]), "+f"(d[O + 22]), "+f"(d[O + 23]),
      "+f"(d[O + 24]), "+f"(d[O + 25]), "+f"(d[O + 26]), "+f"(d[O + 27]), "+f"(d[O + 28]), "+f"(d[O + 29]), "+f"(d[O + 30]), "+f"(d[O + 31]),
      "+f"(d[O + 32]), "+f"(d[O + 33]), "+f"(d[O + 34]), "+f"(d[O + 35]), "+f"(d[O + 36]), "+f"(d[O + 37]), "+f"(d[O + 38]), "+f"(d[O + 39]),
      "+f"(d[O + 40]), "+f"(d[O + 41]), "+f"(d[O + 42]), "+f"(d[O + 43]), "+f"(d[O + 44]), "+f"(d[O + 45]), "+f"(d[O + 46]), "+f"(d[O + 47]),
      "+f"(d[O + 48]), "+f"(d[O + 49]), "+f"(d[O + 50]), "+f"(d[O + 51]), "+f"(d[O + 52]), "+f"(d[O + 53]), "+f"(d[O + 54]), "+f"(d[O + 55]),
      "+f"(d[O + 56]), "+f"(d[O + 57]), "+f"(d[O + 58]), "+f"(d[O + 59]), "+f"(d[O + 60]), "+f"(d[O + 61]), "+f"(d[O + 62]), "+f"(d[O + 63]),
      "+f"(d[O + 64]), "+f"(d[O + 65]), "+f"(d[O + 66]), "+f"(d[O + 67]), "+f"(d[O + 68]), "+f"(d[O + 69]), "+f"(d[O + 70]), "+f"(d[O + 71]),
      "+f"(d[O + 72]), "+f"(d[O + 73]), "+f"(d[O + 74]), "+f"(d[O + 75]), "+f"(d[O + 76]), "+f"(d[O + 77]), "+f"(d[O + 78]), "+f"(d[O + 79]),
      "+f"(d[O + 80]), "+f"(d[O + 81]), "+f"(d[O + 82]), "+f"(d[O + 83]), "+f"(d[O + 84]), "+f"(d[O + 85]), "+f"(d[O + 86]), "+f"(d[O + 87]),
      "+f"(d[O + 88]), "+f"(d[O + 89]), "+f"(d[O + 90]), "+f"(d[O + 91]), "+f"(d[O + 92]), "+f"(d[O + 93]), "+f"(d[O + 94]), "+f"(d[O + 95])
    : "r"(a.x), "r"(a.y), "r"(a.z), "r"(a.w), "l"(db));
}
template <int O, int T> __device__ __forceinline__ void wgmma_rs_n192_init(float (&d)[T], const uint4& a, uint64_t db) {
  asm volatile("{\n.reg .pred p;\nsetp.ne.b32 p, 0, 0;\n"
    "wgmma.mma_async.sync.aligned.m64n192k16.f32.bf16.bf16 "
    "{%0, %1, %2, %3, %4, %5, %6, %7, %8, %9, %10, %11, %12, %13, %14, %15, "
    "%16, %17, %18, %19, %20, %21, %22, %23, %24, %25, %26, %27, %28, %29, %30, %31, "
    "%32, %33, %34, %35, %36, %37, %38, %39, %40, %41, %42, %43, %44, %45, %46, %47, "
    "%48, %49, %50, %51, %52, %53, %54, %55, %56, %57, %58, %59, %60, %61, %62, %63, "
    "%64, %65, %66, %67, %68, %69, %70, %71, %72, %73, %74, %75, %76, %77, %78, %79, "
    "%80, %81, %82, %83, %84, %85, %86, %87, %88, %89, %90, %91, %92, %93, %94, %95}, "
    "{%96, %97, %98, %99}, %100, p, 1, 1, 1;\n}\n"
    : "=f"(d[O + 0]), "=f"(d[O + 1]), "=f"(d[O + 2]), "=f"(d[O + 3]), "=f"(d[O + 4]), "=f"(d[O + 5]), "=f"(d[O + 6]), "=f"(d[O + 7]),
      "=f"(d[O + 8]), "=f"(d[O + 9]), "=f"(d[O + 10]), "=f"(d[O + 11]), "=f"(d[O + 12]), "=f"(d[O + 13]), "=f"(d[O + 14]), "=f"(d[O + 15]),
      "=f"(d[O + 16]), "=f"(d[O + 17]), "=f"(d[O + 18]), "=f"(d[O + 19]), "=f"(d[O + 20]), "=f"(d[O + 21]), "=f"(d[O + 22]), "=f"(d[O + 23]),
      "=f"(d[O + 24]), "=f"(d[O + 25]), "=f"(d[O + 26]), "=f"(d[O + 27]), "=f"(d[O + 28]), "=f"(d[O + 29]), "=f"(d[O + 30]), "=f"(d[O + 31]),
      "=f"(d[O + 32]), "=f"(d[O + 33]), "=f"(d[O + 34]), "=f"(d[O + 35]), "=f"(d[O + 36]), "=f"(d[O + 37]), "=f"(d[O + 38]), "=f"(d[O + 39]),
      "=f"(d[O + 40]), "=f"(d[O + 41]), "=f"(d[O + 42]), "=f"(d[O + 43]), "=f"(d[O + 44]), "=f"(d[O + 45]), "=f"(d[O + 46]), "=f"(d[O + 47]),
      "=f"(d[O + 48]), "=f"(d[O + 49]), "=f"(d[O + 50]), "=f"(d[O + 51]), "=f"(d[O + 52]), "=f"(d[O + 53]), "=f"(d[O + 54]), "=f"(d[O + 55]),
      "=f"(d[O + 56]), "=f"(d[O + 57]), "=f"(d[O + 58]), "=f"(d[O + 59]), "=f"(d[O + 60]), "=f"(d[O + 61]), "=f"(d[O + 62]), "=f"(d[O + 63]),
      "=f"(d[O + 64]), "=f"(d[O + 65]), "=f"(d[O + 66]), "=f"(d[O + 67]), "=f"(d[O + 68]), "=f"(d[O + 69]), "=f"(d[O + 70]), "=f"(d[O + 71]),
      "=f"(d[O + 72]), "=f"(d[O + 73]), "=f"(d[O + 74]), "=f"(d[O + 75]), "=f"(d[O + 76]), "=f"(d[O + 77]), "=f"(d[O + 78]), "=f"(d[O + 79]),
      "=f"(d[O + 80]), "=f"(d[O + 81]), "=f"(d[O + 82]), "=f"(d[O + 83]), "=f"(d[O + 84]), "=f"(d[O + 85]), "=f"(d[O + 86]), "=f"(d[O + 87]),
      "=f"(d[O + 88]), "=f"(d[O + 89]), "=f"(d[O + 90]), "=f"(d[O + 91]), "=f"(d[O + 92]), "=f"(d[O + 93]), "=f"(d[O + 94]), "=f"(d[O + 95])
    : "r"(a.x), "r"(a.y), "r"(a.z), "r"(a.w), "l"(db));
}
template <bool INIT, int O, int T> __device__ __forceinline__ void wgmma_n192(float (&d)[T], const uint4& a, uint64_t db) {
  if constexpr (INIT) wgmma_rs_n192_init<O>(d, a, db); else wgmma_rs_n192<O>(d, a, db);
}
template <int O, int T> __device__ __forceinline__ void wgmma_rs_n256(float (&d)[T], const uint4& a, uint64_t db) {
  asm volatile("{\n.reg .pred p;\nsetp.ne.b32 p, 1, 0;\n"
    "wgmma.mma_async.sync.aligned.m64n256k16.f32.bf16.bf16 "
    "{%0, %1, %2, %3, %4, %5, %6, %7, %8, %9, %10, %11, %12, %13, %14, %15, "
    "%16, %17, %18, %19, %20, %21, %22, %23, %24, %25, %26, %27, %28, %29, %30, %31, "
    "%32, %33, %34, %35, %36, %37, %38, %39, %40, %41, %42, %43, %44, %45, %46, %47, "
    "%48, %49, %50, %51, %52, %53, %54, %55, %56, %57, %58, %59, %60, %61, %62, %63, "
    "%64, %65, %66, %67, %68, %69, %70, %71, %72, %73, %74, %75, %76, %77, %78, %79, "
    "%80, %81, %82, %83, %84, %85, %86, %87, %88, %89, %90, %91, %92, %93, %94, %95, "
    "%96, %97, %98, %99, %100, %101, %102, %103, %104, %105, %106, %107, %108, %109, %110, %111, "
    "%112, %113, %114, %115, %116, %117, %118, %119, %120, %121, %122, %123, %124, %125, %126, %127}, "
    "{%128, %129, %130, %131}, %132, p, 1, 1, 1;\n}\n"
    : "+f"(d[O + 0]), "+f"(d[O + 1]), "+f"(d[O + 2]), "+f"(d[O + 3]), "+f"(d[O + 4]), "+f"(d[O + 5]), "+f"(d[O + 6]), "+f"(d[O + 7]),
      "+f"(d[O + 8]), "+f"(d[O + 9]), "+f"(d[O + 10]), "+f"(d[O + 11]), "+f"(d[O + 12]), "+f"(d[O + 13]), "+f"(d[O + 14]), "+f"(d[O + 15]),
      "+f"(d[O + 16]), "+f"(d[O + 17]), "+f"(d[O + 18]), "+f"(d[O + 19]), "+f"(d[O + 20]), "+f"(d[O + 21]), "+f"(d[O + 22]), "+f"(d[O + 23]),
      "+f"(d[O + 24]), "+f"(d[O + 25]), "+f"(d[O + 26]), "+f"(d[O + 27]), "+f"(d[O + 28]), "+f"(d[O + 29]), "+f"(d[O + 30]), "+f"(d[O + 31]),
      "+f"(d[O + 32]), "+f"(d[O + 33]), "+f"(d[O + 34]), "+f"(d[O + 35]), "+f"(d[O + 36]), "+f"(d[O + 37]), "+f"(d[O + 38]), "+f"(d[O + 39]),
      "+f"(d[O + 40]), "+f"(d[O + 41]), "+f"(d[O + 42]), "+f"(d[O + 43]), "+f"(d[O + 44]), "+f"(d[O + 45]), "+f"(d[O + 46]), "+f"(d[O + 47]),
      "+f"(d[O + 48]), "+f"(d[O + 49]), "+f"(d[O + 50]), "+f"(d[O + 51]), "+f"(d[O + 52]), "+f"(d[O + 53]), "+f"(d[O + 54]), "+f"(d[O + 55]),
      "+f"(d[O + 56]), "+f"(d[O + 57]), "+f"(d[O + 58]), "+f"(d[O + 59]), "+f"(d[O + 60]), "+f"(d[O + 61]), "+f"(d[O + 62]), "+f"(d[O + 63]),
      "+f"(d[O + 64]), "+f"(d[O + 65]), "+f"(d[O + 66]), "+f"(d[O + 67]), "+f"(d[O + 68]), "+f"(d[O + 69]), "+f"(d[O + 70]), "+f"(d[O + 71]),
      "+f"(d[O + 72]), "+f"(d[O + 73]), "+f"(d[O + 74]), "+f"(d[O + 75]), "+f"(d[O + 76]), "+f"(d[O + 77]), "+f"(d[O + 78]), "+f"(d[O + 79]),
      "+f"(d[O + 80]), "+f"(d[O + 81]), "+f"(d[O + 82]), "+f"(d[O + 83]), "+f"(d[O + 84]), "+f"(d[O + 85]), "+f"(d[O + 86]), "+f"(d[O + 87]),
      "+f"(d[O + 88]), "+f"(d[O + 89]), "+f"(d[O + 90]), "+f"(d[O + 91]), "+f"(d[O + 92]), "+f"(d[O + 93]), "+f"(d[O + 94]), "+f"(d[O + 95]),
      "+f"(d[O + 96]), "+f"(d[O + 97]), "+f"(d[O + 98]), "+f"(d[O + 99]), "+f"(d[O + 100]), "+f"(d[O + 101]), "+f"(d[O + 102]), "+f"(d[O + 103]),
      "+f"(d[O + 104]), "+f"(d[O + 105]), "+f"(d[O + 106]), "+f"(d[O + 107]), "+f"(d[O + 108]), "+f"(d[O + 109]), "+f"(d[O + 110]), "+f"(d[O + 111]),
      "+f"(d[O + 112]), "+f"(d[O + 113]), "+f"(d[O + 114]), "+f"(d[O + 115]), "+f"(d[O + 116]), "+f"(d[O + 117]), "+f"(d[O + 118]), "+f"(d[O + 119]),
      "+f"(d[O + 120]), "+f"(d[O + 121]), "+f"(d[O + 122]), "+f"(d[O + 123]), "+f"(d[O + 124]), "+f"(d[O + 125]), "+f"(d[O + 126]), "+f"(d[O + 127])
    : "r"(a.x), "r"(a.y), "r"(a.z), "r"(a.w), "l"(db));
}
template <int O, int T> __device__ __forceinline__ void wgmma_rs_n256_init(float (&d)[T], const uint4& a, uint64_t db) {
  asm volatile("{\n.reg .pred p;\nsetp.ne.b32 p, 0, 0;\n"
    "wgmma.mma_async.sync.aligned.m64n256k16.f32.bf16.bf16 "
    "{%0, %1, %2, %3, %4, %5, %6, %7, %8, %9, %10, %11, %12, %13, %14, %15, "
    "%16, %17, %18, %19, %20, %21, %22, %23, %24, %25, %26, %27, %28, %29, %30, %31, "
    "%32, %33, %34, %35, %36, %37, %38, %39, %40, %41, %42, %43, %44, %45, %46, %47, "
    "%48, %49, %50, %51, %52, %53, %54, %55, %56, %57, %58, %59, %60, %61, %62, %63, "
    "%64, %65, %66, %67, %68, %69, %70, %71, %72, %73, %74, %75, %76, %77, %78, %79, "
    "%80, %81, %82, %83, %84, %85, %86, %87, %88, %89, %90, %91, %92, %93, %94, %95, "
    "%96, %97, %98, %99, %100, %101, %102, %103, %104, %105, %106, %107, %108, %109, %110, %111, "
    "%112, %113, %114, %115, %116, %117, %118, %119, %120, %121, %122, %123, %124, %125, %126, %127}, "
    "{%128, %129, %130, %131}, %132, p, 1, 1, 1;\n}\n"
    : "=f"(d[O + 0]), "=f"(d[O + 1]), "=f"(d[O + 2]), "=f"(d[O + 3]), "=f"(d[O + 4]), "=f"(d[O + 5]), "=f"(d[O + 6]), "=f"(d[O + 7]),
      "=f"(d[O + 8]), "=f"(d[O + 9]), "=f"(d[O + 10]), "=f"(d[O + 11]), "=f"(d[O + 12]), "=f"(d[O + 13]), "=f"(d[O + 14]), "=f"(d[O + 15]),
      "=f"(d[O + 16]), "=f"(d[O + 17]), "=f"(d[O + 18]), "=f"(d[O + 19]), "=f"(d[O + 20]), "=f"(d[O + 21]), "=f"(d[O + 22]), "=f"(d[O + 23]),
      "=f"(d[O + 24]), "=f"(d[O + 25]), "=f"(d[O + 26]), "=f"(d[O + 27]), "=f"(d[O + 28]), "=f"(d[O + 29]), "=f"(d[O + 30]), "=f"(d[O + 31]),
      "=f"(d[O + 32]), "=f"(d[O + 33]), "=f"(d[O + 34]), "=f"(d[O + 35]), "=f"(d[O + 36]), "=f"(d[O + 37]), "=f"(d[O + 38]), "=f"(d[O + 39]),
      "=f"(d[O + 40]), "=f"(d[O + 41]), "=f"(d[O + 42]), "=f"(d[O + 43]), "=f"(d[O + 44]), "=f"(d[O + 45]), "=f"(d[O + 46]), "=f"(d[O + 47]),
      "=f"(d[O + 48]), "=f"(d[O + 49]), "=f"(d[O + 50]), "=f"(d[O + 51]), "=f"(d[O + 52]), "=f"(d[O + 53]), "=f"(d[O + 54]), "=f"(d[O + 55]),
      "=f"(d[O + 56]), "=f"(d[O + 57]), "=f"(d[O + 58]), "=f"(d[O + 59]), "=f"(d[O + 60]), "=f"(d[O + 61]), "=f"(d[O + 62]), "=f"(d[O + 63]),
      "=f"(d[O + 64]), "=f"(d[O + 65]), "=f"(d[O + 66]), "=f"(d[O + 67]), "=f"(d[O + 68]), "=f"(d[O + 69]), "=f"(d[O + 70]), "=f"(d[O + 71]),
      "=f"(d[O + 72]), "=f"(d[O + 73]), "=f"(d[O + 74]), "=f"(d[O + 75]), "=f"(d[O + 76]), "=f"(d[O + 77]), "=f"(d[O + 78]), "=f"(d[O + 79]),
      "=f"(d[O + 80]), "=f"(d[O + 81]), "=f"(d[O + 82]), "=f"(d[O + 83]), "=f"(d[O + 84]), "=f"(d[O + 85]), "=f"(d[O + 86]), "=f"(d[O + 87]),
      "=f"(d[O + 88]), "=f"(d[O + 89]), "=f"(d[O + 90]), "=f"(d[O + 91]), "=f"(d[O + 92]), "=f"(d[O + 93]), "=f"(d[O + 94]), "=f"(d[O + 95]),
      "=f"(d[O + 96]), "=f"(d[O + 97]), "=f"(d[O + 98]), "=f"(d[O + 99]), "=f"(d[O + 100]), "=f"(d[O + 101]), "=f"(d[O + 102]), "=f"(d[O + 103]),
      "=f"(d[O + 104]), "=f"(d[O + 105]), "=f"(d[O + 106]), "=f"(d[O + 107]), "=f"(d[O + 108]), "=f"(d[O + 109]), "=f"(d[O + 110]), "=f"(d[O + 111]),
      "=f"(d[O + 112]), "=f"(d[O + 113]), "=f"(d[O + 114]), "=f"(d[O + 115]), "=f"(d[O + 116]), "=f"(d[O + 117]), "=f"(d[O + 118]), "=f"(d[O + 119]),
      "=f"(d[O + 120]), "=f"(d[O + 121]), "=f"(d[O + 122]), "=f"(d[O + 123]), "=f"(d[O + 124]), "=f"(d[O + 125]), "=f"(d[O + 126]), "=f"(d[O + 127])
    : "r"(a.x), "r"(a.y), "r"(a.z), "r"(a.w), "l"(db));
}
template <bool INIT, int O, int T> __device__ __forceinline__ void wgmma_n256(float (&d)[T], const uint4& a, uint64_t db) {
  if constexpr (INIT) wgmma_rs_n256_init<O>(d, a, db); else wgmma_rs_n256<O>(d, a, db);
}

template <int N> __device__ __forceinline__ void load_pk(uint4* a, const uint4* p) {
#pragma unroll
  for (int i = 0; i < N; i++) a[i] = ld_ll(p + i * 32);
}
__device__ __forceinline__ uint32_t xor_or(uint32_t a, uint32_t b, uint32_t t) {
  uint32_t r;
  asm("lop3.b32 %0, %1, %2, %3, 0x7E;" : "=r"(r) : "r"(a), "r"(b), "r"(t));
  return r;
}
template <int N> __device__ __forceinline__ bool ok_pk(const uint4* a, uint32_t tag) {
  static_assert(N % 2 == 0, "");
  uint32_t x = xor_or(a[0].x, a[1].x, tag);
#pragma unroll
  for (int i = 2; i < N; i += 2) x |= xor_or(a[i].x, a[i + 1].x, tag);
  return __all_sync(0xffffffffu, (x & 1u) == 0u);
}
template <int N> __device__ __forceinline__ void ensure_pk(uint4* a, const uint4* p, uint32_t tag) {
  if (ok_pk<N>(a, tag)) return;
  uint32_t n = 0;
  do { load_pk<N>(a, p); } while (!ok_pk<N>(a, tag) && ++n < SPIN_LIMIT);
}

constexpr int NSTAGE = 52;
constexpr int ST_WO = 8, ST_G1 = 12, ST_G2 = 28, ST_DN = 36;
__host__ __device__ constexpr int st_len(int s) { return s < ST_WO ? 3 : s < ST_G2 ? 2 : s < ST_DN ? 3 : 2; }
__host__ __device__ constexpr int st_g0(int s) {
  int pos = 0, g0 = 0;
  for (int i = 0; i <= s; i++) {
    if (pos + st_len(i) > NGRAN) pos = 0;
    g0 = pos;
    pos += st_len(i);
  }
  return g0;
}
__host__ __device__ constexpr int cnt_first(int g, int s) {
  int n = 0;
  for (int i = 0; i < s; i++) n += (st_g0(i) == g);
  return n;
}
__host__ __device__ constexpr int cnt_cover(int g, int s) {
  int n = 0;
  for (int i = 0; i < s; i++) n += (g >= st_g0(i) && g < st_g0(i) + st_len(i));
  return n;
}
__host__ __device__ constexpr uint32_t flip_mask(int s0, int s1) {
  uint32_t m = 0;
  for (int i = s0; i < s1; i++) m ^= ((1u << st_len(i)) - 1u) << st_g0(i);
  return m;
}
__host__ __device__ constexpr int dn_q(int i) { return i < 3 ? 0 : i < 6 ? 1 : i == 6 ? 0 : i == 7 ? 1 : i < 12 ? 2 : 3; }
__host__ __device__ constexpr int dn_par(int i) { return i < 8 ? (i == 2 || i == 4 || i >= 6) : (i & 1); }
__host__ __device__ constexpr int dn_kh(int i) { return i < 8 ? (i == 1 || i >= 5) : ((i & 3) >= 2); }
template <int I> struct IC { static constexpr int value = I; };
template <int B, int E, typename F> __device__ __forceinline__ void static_for(F&& f) {
  if constexpr (B < E) { f(IC<B>{}); static_for<B + 1, E>(f); }
}
template <int S> __device__ __forceinline__ void cons_acquire(uint32_t sbase, uint32_t L) {
  constexpr int g0 = st_g0(S);
  constexpr uint32_t p0 = cnt_first(g0, S) & 1, odd = cnt_first(g0, NSTAGE) & 1;
  mbar_wait(sbase + SM_MISC + BAR_FULL + 8 * g0, p0 ^ (L & odd));
}
template <int S> __device__ __forceinline__ void cons_release(uint32_t sbase, int lane) {
  if (lane < st_len(S)) mbar_arrive(sbase + SM_MISC + BAR_EMPTY + 8 * st_g0(S) + 8 * lane);
}
__device__ __forceinline__ bool elect_one() {
  uint32_t p;
  asm volatile("{\n.reg .pred P;\nelect.sync _|P, 0xffffffff;\nselp.u32 %0, 1, 0, P;\n}" : "=r"(p));
  return p != 0;
}
struct ProdRing { uint32_t pos, par; };
template <int N> __device__ __forceinline__ uint32_t prod_acquire(uint32_t sbase, ProdRing& r) {
  if (r.pos + N > NGRAN) r.pos = 0;
  const uint32_t g0 = r.pos;
#pragma unroll
  for (uint32_t i = 0; i < N; i++) mbar_wait(sbase + SM_MISC + BAR_EMPTY + 8 * (g0 + i), ((r.par >> (g0 + i)) & 1u) ^ 1u);
  r.par ^= ((1u << N) - 1u) << g0;
  r.pos = g0 + N;
  return g0;
}
template <int S> __device__ __forceinline__ void prod_acquire_static(uint32_t sbase, uint32_t L) {
  constexpr int g0 = st_g0(S);
  static_for<0, st_len(S)>([&](auto I) {
    constexpr int g = g0 + I.value;
    constexpr uint32_t p0 = cnt_cover(g, S) & 1, odd = cnt_cover(g, NSTAGE) & 1;
    mbar_wait(sbase + SM_MISC + BAR_EMPTY + 8 * g, p0 ^ (L & odd) ^ 1u);
  });
}
template <int S, int KSTEP_BYTES, int LBO, int SBO, int SWZ> __device__ __forceinline__ constexpr uint64_t st_desc(int k) {
  return (uint64_t)((SMEM_ORIGIN + st_g0(S) * GRAN + k * KSTEP_BYTES) >> 4) | ((uint64_t)(LBO >> 4) << 16) |
         ((uint64_t)(SBO >> 4) << 32) | ((uint64_t)SWZ << 62);
}

__device__ __forceinline__ void combine_stats(const uint4& p0, const uint4& p1, float& mean_lo, float& rstd_lo, float& mean_hi, float& rstd_hi) {
  float m0 = __uint_as_float(p0.x), q0 = __uint_as_float(p0.y), m0h = __uint_as_float(p0.z), q0h = __uint_as_float(p0.w);
  float m1 = __uint_as_float(p1.x), q1 = __uint_as_float(p1.y), m1h = __uint_as_float(p1.z), q1h = __uint_as_float(p1.w);
  float s = m0 + m1, sh = m0h + m1h;
  s += __shfl_xor_sync(0xffffffffu, s, 1); sh += __shfl_xor_sync(0xffffffffu, sh, 1);
  s += __shfl_xor_sync(0xffffffffu, s, 2); sh += __shfl_xor_sync(0xffffffffu, sh, 2);
  mean_lo = s * 0.125f; mean_hi = sh * 0.125f;
  float d0 = m0 - mean_lo, d1 = m1 - mean_lo, d0h = m0h - mean_hi, d1h = m1h - mean_hi;
  float t = q0 + q1 + 64.f * (d0 * d0 + d1 * d1), th = q0h + q1h + 64.f * (d0h * d0h + d1h * d1h);
  t += __shfl_xor_sync(0xffffffffu, t, 1); th += __shfl_xor_sync(0xffffffffu, th, 1);
  t += __shfl_xor_sync(0xffffffffu, t, 2); th += __shfl_xor_sync(0xffffffffu, th, 2);
  rstd_lo = rsqrtf(t * (1.f / 512.f) + 1e-5f);
  rstd_hi = rsqrtf(th * (1.f / 512.f) + 1e-5f);
}
__device__ __forceinline__ uint4 local_stats(const float (&v)[32]) {
  float s = 0.f, sh = 0.f;
#pragma unroll
  for (int i = 0; i < 4; i++) {
    s += (v[8 * i + 0] + v[8 * i + 1]) + (v[8 * i + 4] + v[8 * i + 5]);
    sh += (v[8 * i + 2] + v[8 * i + 3]) + (v[8 * i + 6] + v[8 * i + 7]);
  }
  s += __shfl_xor_sync(0xffffffffu, s, 1); sh += __shfl_xor_sync(0xffffffffu, sh, 1);
  s += __shfl_xor_sync(0xffffffffu, s, 2); sh += __shfl_xor_sync(0xffffffffu, sh, 2);
  float m = s * (1.f / 64.f), mh = sh * (1.f / 64.f);
  float q = 0.f, qh = 0.f;
#pragma unroll
  for (int i = 0; i < 4; i++) {
    float a = v[8 * i + 0] - m, b = v[8 * i + 1] - m, c = v[8 * i + 4] - m, d = v[8 * i + 5] - m;
    q += (a * a + b * b) + (c * c + d * d);
    float e = v[8 * i + 2] - mh, f = v[8 * i + 3] - mh, g = v[8 * i + 6] - mh, h = v[8 * i + 7] - mh;
    qh += (e * e + f * f) + (g * g + h * h);
  }
  q += __shfl_xor_sync(0xffffffffu, q, 1); qh += __shfl_xor_sync(0xffffffffu, qh, 1);
  q += __shfl_xor_sync(0xffffffffu, q, 2); qh += __shfl_xor_sync(0xffffffffu, qh, 2);
  return make_uint4(__float_as_uint(m), __float_as_uint(q), __float_as_uint(mh), __float_as_uint(qh));
}

__device__ __forceinline__ int slab_row0(int c, int g, int w) { return 1024 * g + 64 * c + 32 * (w >> 1) + (w & 1); }

__device__ __forceinline__ void owner_ln_publish(uint32_t sbase, const float (&v)[32], uint32_t tphase, uint32_t tag_xn, uint4 (&xraw)[4]) {
  PHASE_VARS;
  TS(40 + 4 * tphase);
  uint4 st = local_stats(v);
  if (qc == 0) sts128(sbase + SM_TSTAT + warp * 128 + qr * 16, st);
  uint4* xn = g_arena + c * ARENA + AR_XN + (j * 32 + 16 * g + w) * 32 + lane;
  TS(41 + 4 * tphase);
  asm volatile("bar.sync 3, 256;" ::: "memory");
  TS(42 + 4 * tphase);
  const uint32_t rd = sbase + SM_TSTAT + qc * 256 + qr * 16;
  uint4 p0 = lds128(rd), p1 = lds128(rd + 128);
  float ml, rl, mh, rh;
  combine_stats(p0, p1, ml, rl, mh, rh);
  const float bl = -ml * rl, bh = -mh * rh;
#pragma unroll
  for (int i = 0; i < 4; i++) {
    uint4 o;
    o.x = set_tag(pack2(fmaf(v[8 * i + 0], rl, bl), fmaf(v[8 * i + 1], rl, bl)), tag_xn);
    o.y = pack2(fmaf(v[8 * i + 2], rh, bh), fmaf(v[8 * i + 3], rh, bh));
    o.z = pack2(fmaf(v[8 * i + 4], rl, bl), fmaf(v[8 * i + 5], rl, bl));
    o.w = pack2(fmaf(v[8 * i + 6], rh, bh), fmaf(v[8 * i + 7], rh, bh));
    st_ll(xn + i * 128, o);
  }
#pragma unroll
  for (int i = 0; i < 4; i++) {
    xraw[i].x = set_tag(pack2(v[8 * i + 0], v[8 * i + 1]), 1u);
    xraw[i].y = pack2(v[8 * i + 2], v[8 * i + 3]);
    xraw[i].z = pack2(v[8 * i + 4], v[8 * i + 5]);
    xraw[i].w = pack2(v[8 * i + 6], v[8 * i + 7]);
  }
}

__device__ __forceinline__ uint4 pack8(const float* a) {
  return make_uint4(pack2(a[0], a[1]), pack2(a[2], a[3]), pack2(a[4], a[5]), pack2(a[6], a[7]));
}
template <int U> __device__ __forceinline__ uint4 glu8(const float* g, float cl, float ch) {
  return make_uint4(pack2(g[0] * cl * g[U], g[1] * cl * g[U + 1]), pack2(g[2] * ch * g[U + 2], g[3] * ch * g[U + 3]),
                    pack2(g[4] * cl * g[U + 4], g[5] * cl * g[U + 5]), pack2(g[6] * ch * g[U + 6], g[7] * ch * g[U + 7]));
}
__device__ __forceinline__ uint32_t hfma2(uint32_t a, uint32_t b, uint32_t c) {
  uint32_t d;
  asm("fma.rn.bf16x2 %0, %1, %2, %3;" : "=r"(d) : "r"(a), "r"(b), "r"(c));
  return d;
}
__device__ __forceinline__ void keep4(const uint4 (&a)[4]) { keep(a[0]); keep(a[1]); keep(a[2]); keep(a[3]); }

#define STAGGER 0

__global__ void __launch_bounds__(NTHREADS, 1)
fused_kernel(const __grid_constant__ CUtensorMap m_qkv, const __grid_constant__ CUtensorMap m_wo,
             const __grid_constant__ CUtensorMap m_gu2, const __grid_constant__ CUtensorMap m_gu1,
             const __grid_constant__ CUtensorMap m_guh, const __grid_constant__ CUtensorMap m_wd112,
             const __grid_constant__ CUtensorMap m_wd80, const __grid_constant__ CUtensorMap m_wd32,
             const __nv_bfloat16* __restrict__ x_in,
             __nv_bfloat16* __restrict__ out
) {
  extern __shared__ __align__(1024) unsigned char smem_raw[];
  const uint32_t sbase = smem_u32(smem_raw);
  const uint32_t bars = sbase + SM_MISC;
  if ((sbase & 0xFFFFFFu) != SMEM_ORIGIN) return;
  TG(60);

  uint32_t xw[16];
  if (threadIdx.x < 256) {
    const int cc = blockIdx.x >> 3, jj = blockIdx.x & 7, ln = threadIdx.x & 31;
    const int wp = threadIdx.x >> 5;
    const uint32_t* xp = reinterpret_cast<const uint32_t*>(x_in + (size_t)(slab_row0(cc, jj >> 2, jj & 3) + 2 * (ln >> 2)) * 512 + (16 * (wp >> 2) + (wp & 3)) * 16 + (ln & 3) * 2);
#pragma unroll
    for (int i = 0; i < 4; i++) {
      xw[4 * i] = __ldg(xp + i * 32); xw[4 * i + 1] = __ldg(xp + 16 * 256 + i * 32);
      xw[4 * i + 2] = __ldg(xp + i * 32 + 4); xw[4 * i + 3] = __ldg(xp + 16 * 256 + i * 32 + 4);
    }
  } else if (threadIdx.x == 256) {
    for (int i = 0; i < NGRAN; i++) { mbar_init(bars + BAR_FULL + 8 * i, 1); mbar_init(bars + BAR_EMPTY + 8 * i, 8); }
    for (int i = 0; i < 4; i++) mbar_init(bars + BAR_HRECV + 8 * i, 1);
    for (int i = 0; i < 2; i++) mbar_init(bars + BAR_HREADY + 8 * i, 4);
    asm volatile("fence.mbarrier_init.release.cluster;" ::: "memory");
  }
  TG(56);
  __syncthreads();
  TG(57);
  asm volatile("barrier.cluster.arrive.relaxed.aligned;" ::: "memory");

  if (threadIdx.x >= 256) {
    asm volatile("setmaxnreg.dec.sync.aligned.u32 40;");
    const int warp = threadIdx.x >> 5;
    const int j = blockIdx.x & 7, b = j & 1;
    if (warp == 8) {
      ProdRing r{0u, 0u};
      const int cb0 = 224 * j + 32 * b, hb0 = 224 * j + 192 * (b ^ 1);
      const int jp = j ^ 1, cbp = 224 * jp + 32 * (b ^ 1), hbp = 224 * jp + 192 * b;
#pragma unroll 1
      for (uint32_t L = 0; L < 2; L++) {
        r.pos = 0;
        PSTOP_AT(L == 0 ? 0 : 3);
#define D_NEXT 4500
        if (D_NEXT > 0 && L == 1) spin_for(D_NEXT);
#pragma unroll 1
        for (int kb = 0; kb < 8; kb++) {
          const uint32_t g0 = prod_acquire<3>(sbase, r);
          if (elect_one()) {
            mbar_expect_tx(bars + BAR_FULL + 8 * g0, 24576);
            tma_3d(sbase + g0 * GRAN, &m_qkv, bars + BAR_FULL + 8 * g0, 64 * j, 64 * kb, 0);
          }
        }
        PSTOP_AT(10 * L + 1);
#pragma unroll 1
        for (int i = 0; i < 4; i++) {
          const uint32_t g0 = prod_acquire<2>(sbase, r);
          if (elect_one()) {
            mbar_expect_tx(bars + BAR_FULL + 8 * g0, 16384);
            tma_2d(sbase + g0 * GRAN, &m_wo, bars + BAR_FULL + 8 * g0, 64 * j, 128 * i);
          }
        }
        PSTOP_AT(10 * L + 2);
#pragma unroll 1
        for (int hb = 0; hb < 16; hb++) {
          const uint32_t g0 = prod_acquire<2>(sbase, r);
          if (elect_one()) {
            mbar_expect_tx(bars + BAR_FULL + 8 * g0, 16384);
            tma_4d(sbase + g0 * GRAN, &m_gu2, bars + BAR_FULL + 8 * g0, cb0, 64 * ((j + (hb >> 1)) & 7) + 32 * (hb & 1), 0, 0);
          }
        }
#pragma unroll 1
        for (int kb = 0; kb < 8; kb++) {
          const uint32_t g0 = prod_acquire<3>(sbase, r);
          if (elect_one()) {
            mbar_expect_tx(bars + BAR_FULL + 8 * g0, 24576);
            tma_4d(sbase + g0 * GRAN, &m_gu1, bars + BAR_FULL + 8 * g0, cb0 + 128, 64 * ((j + kb) & 7), 0, 0);
            tma_3d(sbase + g0 * GRAN + 16384, &m_guh, bars + BAR_FULL + 8 * g0, hb0, 64 * ((j + kb) & 7), 0);
          }
        }
        static_for<0, 16>([&](auto I) {
          constexpr int i = I.value, g0 = st_g0(ST_DN + i);
          prod_acquire_static<ST_DN + i>(sbase, L);
          if (elect_one()) {
            const uint32_t dst = sbase + g0 * GRAN, fb = bars + BAR_FULL + 8 * g0;
            const int n0 = 256 * b + 64 * dn_q(i);
            mbar_expect_tx(fb, 14336);
            if constexpr (dn_kh(i) == 0) {
              tma_2d(dst, &m_wd112, fb, n0, dn_par(i) ? cbp : cb0);
            } else {
              tma_2d(dst, &m_wd80, fb, n0, (dn_par(i) ? cbp : cb0) + 112);
              tma_2d(dst + 10240, &m_wd32, fb, n0, dn_par(i) ? hbp : hb0);
            }
          }
        });
        r.par ^= flip_mask(ST_DN, NSTAGE);
      }
    }
    __syncwarp();
    asm volatile("barrier.cluster.wait.acquire.aligned; // producer" ::: "memory");
  } else {
    TG(58);
    asm volatile("setmaxnreg.inc.sync.aligned.u32 232;");
    TS(0);
    TG(61);

    float vres[32];
#pragma unroll
    for (int i = 0; i < 16; i++) { vres[2 * i] = bf_lo(xw[i]); vres[2 * i + 1] = bf_hi(xw[i]); }

#pragma unroll 1
    for (uint32_t L = 0; L < 2; L++) {
      const uint32_t tag = L ^ 1;
      uint4 xraw[4];
      owner_ln_publish(sbase, vres, L, tag, xraw);
      if (L == 0) asm volatile("barrier.cluster.wait.acquire.aligned; // consumer" ::: "memory");
      if (L == 0) { STOP_AT(0); TS(1); } else { TS(17); STOP_AT(3); }
      {
        PHASE_VARS;
        uint4 qf[4], kf[4], vf[4], pp[4];
        const int blk = 16 * g + c;
        const int pb = blk > 0 ? blk - 1 : 0;
        const uint4* halo_src = g_arena + (pb & 15) * ARENA + AR_HALO + (((((L * 2 + (pb >> 4)) * 8 + j) * 2 + (w & 1)) * 4) * 32) + lane;
        {
          float acc[96];
          uint4 A[3][4];
          const uint4* xs = g_arena + c * ARENA + AR_XN + ((slab) * 32) * 32 + lane;
          bar_wg(1 + g);
          spin_for(L ? D_XN1 : D_XN0);
          load_pk<4>(A[0], xs);
          ensure_pk<4>(A[0], xs, tag);
          TS(2 + 20 * L);
          load_pk<4>(A[1], xs + 128);
          static_for<0, 8>([&](auto I) {
            constexpr int kb = I.value;
            cons_acquire<kb>(sbase, L);
            wg_fence();
            static_for<0, 4>([&](auto K) { constexpr int k = K.value; wgmma_n192<kb == 0 && k == 0, 0>(acc, A[kb % 3][k], st_desc<kb, 2048, 8192, 1024, 1>(k)); });
            wg_commit();
            if constexpr (kb > 0) {
              wg_wait<1>();
              keep4(A[(kb + 2) % 3]);
              cons_release<kb - 1>(sbase, lane);
            }
            if constexpr (kb + 1 < 8) ensure_pk<4>(A[(kb + 1) % 3], xs + (kb + 1) * 128, tag);
            if constexpr (kb + 2 < 8) load_pk<4>(A[(kb + 2) % 3], xs + (kb + 2) * 128);
            if constexpr (kb == 2) {
              uint4* xr = g_arena + c * ARENA + AR_XRAW + (j * 32 + 16 * g + w) * 32 + lane;
#pragma unroll
              for (int i = 0; i < 4; i++) st_ll(xr + i * 128, xraw[i]);
            }
          });
          wg_wait<0>();
          TS(3 + 20 * L);
          fence_acc(acc);
          keep4(A[1]);
          cons_release<7>(sbase, lane);
#pragma unroll
          for (int h = 0; h < 4; h++) {
            kf[h].y = pack2(acc[32 + 8 * h + 2], acc[32 + 8 * h + 3]); kf[h].w = pack2(acc[32 + 8 * h + 6], acc[32 + 8 * h + 7]);
            vf[h].y = movm(pack2(acc[64 + 8 * h + 2], acc[64 + 8 * h + 3])); vf[h].w = movm(pack2(acc[64 + 8 * h + 6], acc[64 + 8 * h + 7]));
            pp[h] = make_uint4(kf[h].y, kf[h].w, vf[h].y, vf[h].w);
          }
          if (w >= 2 && blk < 31) {
            uint4* hd = g_arena + c * ARENA + AR_HALO + (((((L * 2 + g) * 8 + j) * 2 + (w & 1)) * 4) * 32) + lane;
#pragma unroll
            for (int h = 0; h < 4; h++) { uint4 t = pp[h]; t.x |= 1u; st_ll(hd + h * 32, t); }
          }
#pragma unroll
          for (int h = 0; h < 4; h++) sts128(areg + (28 + h) * 2048 + t128 * 16, pp[h]);
#pragma unroll
          for (int h = 0; h < 4; h++) {
            kf[h].x = pack2(acc[32 + 8 * h], acc[32 + 8 * h + 1]); kf[h].z = pack2(acc[32 + 8 * h + 4], acc[32 + 8 * h + 5]);
            vf[h].x = movm(pack2(acc[64 + 8 * h], acc[64 + 8 * h + 1])); vf[h].z = movm(pack2(acc[64 + 8 * h + 4], acc[64 + 8 * h + 5]));
          }
#pragma unroll
          for (int h = 0; h < 4; h++) qf[h] = pack8(&acc[8 * h]);
        }
        bar_wg(1 + g);
        const bool first = (w < 2) && (blk == 0);
        if (w >= 2) {
#pragma unroll
          for (int h = 0; h < 4; h++) pp[h] = lds128(areg + (28 + h) * 2048 + (t128 - 64) * 16);
        }
        bar_wg(1 + g);
        if (w < 2 && blk > 0) {
          spin_for(L ? D_HALO1 : D_HALO0);
          load_pk<4>(pp, halo_src);
          ensure_pk<4>(pp, halo_src, 1u);
          uint4* hz = const_cast<uint4*>(halo_src);
#pragma unroll
          for (int h = 0; h < 4; h++) st_ll(hz + h * 32, make_uint4(0, 0, 0, 0));
        }
        TS(4 + 20 * L);
        const bool n0 = 2 * qc <= qr, n1 = 2 * qc + 1 <= qr;
        const uint32_t msk = (n0 ? 0xffffu : 0u) | (n1 ? 0xffff0000u : 0u);
        const float sc = 0.25f * 1.4426950408889634f;
        const float NEG = -1e30f;
        uint4* od = g_arena + c * ARENA + AR_O + ((slab) * 32 + 4 * j) * 32 + lane;
        float l0[4], l1[4], h0[4], h1[4], ml[4], mh[4];
#pragma unroll
        for (int h = 0; h < 4; h++) {
          float sp[4], s0[4], s1[4];
          mma16816_z(sp, qf[h], pp[h].x, pp[h].y);
          mma16816_z(s0, qf[h], kf[h].x, kf[h].z);
          mma16816_z(s1, qf[h], kf[h].y, kf[h].w);
          if (first) { sp[0] = NEG; sp[1] = NEG; }
          l0[h] = n0 ? s0[0] : sp[0]; l1[h] = n1 ? s0[1] : sp[1];
          h0[h] = n0 ? s1[2] : s0[2]; h1[h] = n1 ? s1[3] : s0[3];
          ml[h] = fmaxf(l0[h], l1[h]); mh[h] = fmaxf(h0[h], h1[h]);
        }
#pragma unroll
        for (int h = 0; h < 4; h++) { ml[h] = fmaxf(ml[h], __shfl_xor_sync(0xffffffffu, ml[h], 1)); mh[h] = fmaxf(mh[h], __shfl_xor_sync(0xffffffffu, mh[h], 1)); }
#pragma unroll
        for (int h = 0; h < 4; h++) { ml[h] = fmaxf(ml[h], __shfl_xor_sync(0xffffffffu, ml[h], 2)); mh[h] = fmaxf(mh[h], __shfl_xor_sync(0xffffffffu, mh[h], 2)); }
        float sl[4], sh[4];
#pragma unroll
        for (int h = 0; h < 4; h++) {
          const float bl = -ml[h] * sc, bh = -mh[h] * sc;
          l0[h] = ex2(fmaf(l0[h], sc, bl)); l1[h] = ex2(fmaf(l1[h], sc, bl));
          h0[h] = ex2(fmaf(h0[h], sc, bh)); h1[h] = ex2(fmaf(h1[h], sc, bh));
          sl[h] = l0[h] + l1[h]; sh[h] = h0[h] + h1[h];
        }
#pragma unroll
        for (int h = 0; h < 4; h++) { sl[h] += __shfl_xor_sync(0xffffffffu, sl[h], 1); sh[h] += __shfl_xor_sync(0xffffffffu, sh[h], 1); }
#pragma unroll
        for (int h = 0; h < 4; h++) { sl[h] += __shfl_xor_sync(0xffffffffu, sl[h], 2); sh[h] += __shfl_xor_sync(0xffffffffu, sh[h], 2); }
#pragma unroll
        for (int h = 0; h < 4; h++) {
          const float il = rcp(sl[h]), ih = rcp(sh[h]);
          const uint32_t pl = pack2(l0[h] * il, l1[h] * il), ph = pack2(h0[h] * ih, h1[h] * ih);
          const uint4 P = make_uint4(pl & msk, ph & ~msk, 0u, ph & msk);
          float o0[4], o1[4];
          mma16816_z(o0, P, vf[h].x, vf[h].y);
          mma16816_z(o1, P, vf[h].z, vf[h].w);
          mma1688(o0, pl & ~msk, 0u, pp[h].z);
          mma1688(o1, pl & ~msk, 0u, pp[h].w);
          st_ll(od + h * 32, make_uint4(pack2(o0[0], o0[1]) | 1u, pack2(o0[2], o0[3]), pack2(o1[0], o1[1]), pack2(o1[2], o1[3])));
        }
      }
      TS(5 + 20 * L);
      if (L == 0) { STOP_AT(1); } else { STOP_AT(11); }
      uint4 x1own[4];
      {
        PHASE_VARS;
        float acc[32];
        uint4 A[32], xr[4];
        const uint4* os = g_arena + c * ARENA + AR_O + ((slab) * 32) * 32 + lane;
        uint4* xp = g_arena + c * ARENA + AR_XRAW + ((slab) * 32 + 4 * j) * 32 + lane;
        load_pk<4>(xr, xp);
        spin_for(L ? D_O1 : D_O0);
        load_pk<4>(A, os);
        ensure_pk<4>(A, os, 1u);
        TS(6 + 20 * L);
        load_pk<28>(A + 4, os + 128);
        static_for<0, 8>([&](auto I) {
          constexpr int kb = I.value;
          if constexpr ((kb & 1) == 0) cons_acquire<ST_WO + kb / 2>(sbase, L);
          if constexpr (kb > 0) ensure_pk<4>(A + 4 * kb, os + kb * 128, 1u);
          wg_fence();
          static_for<0, 4>([&](auto K) {
            constexpr int k = K.value;
            wgmma_n64<kb == 0 && k == 0, 0>(acc, A[4 * kb + k], st_desc<ST_WO + kb / 2, 2048, 8192, 1024, 1>(4 * (kb & 1) + k));
          });
          wg_commit();
          if constexpr ((kb & 1) == 0 && kb > 0) { wg_wait<1>(); cons_release<ST_WO + kb / 2 - 1>(sbase, lane); }
        });
        wg_wait<0>();
        TS(7 + 20 * L);
        fence_acc(acc);
#pragma unroll
        for (int k = 0; k < 32; k++) keep(A[k]);
        cons_release<ST_WO + 3>(sbase, lane);
        ensure_pk<4>(xr, xp, 1u);
#pragma unroll
        for (int i = 0; i < 4; i++) {
          acc[8 * i + 0] += bf_lo(xr[i].x); acc[8 * i + 1] += bf_hi(xr[i].x); acc[8 * i + 2] += bf_lo(xr[i].y); acc[8 * i + 3] += bf_hi(xr[i].y);
          acc[8 * i + 4] += bf_lo(xr[i].z); acc[8 * i + 5] += bf_hi(xr[i].z); acc[8 * i + 6] += bf_lo(xr[i].w); acc[8 * i + 7] += bf_hi(xr[i].w);
        }
        uint4 st = local_stats(acc);
        st.x = set_tag(st.x, tag);
        if (qc == 0) st_ll(g_arena + c * ARENA + AR_STATS + (slab * 8 + j) * 8 + qr, st);
#pragma unroll
        for (int i = 0; i < 4; i++) {
          x1own[i] = pack8(&acc[8 * i]);
          x1own[i].x = set_tag(x1own[i].x, 0u);
          st_ll(xp + i * 32, x1own[i]);
        }
      }
      TS(8 + 20 * L);
      if (L == 0) { STOP_AT(2); } else { STOP_AT(12); }
      uint4 hs[14];
      {
        PHASE_VARS;
        float acc[128];
        uint4 A[3][4];
        const uint4* xs = g_arena + c * ARENA + AR_XRAW + ((slab) * 32) * 32 + lane;
        const uint4* sp = g_arena + c * ARENA + AR_STATS + (slab * 8 + 2 * qc) * 8 + qr;
        const uint32_t sm = areg + t128 * 16;
        uint32_t rl2, rh2, bl2, bh2;
        float cl, ch;
        auto xsrc = [&](int p) { return xs + ((j + p) & 7) * 128; };
        {
          uint4 p[2];
#pragma unroll
          for (int k = 0; k < 4; k++) A[0][k] = x1own[k];
          spin_for(L ? D_ST1 : D_ST0);
          p[0] = ld_ll(sp); p[1] = ld_ll(sp + 8);
          load_pk<4>(A[1], xsrc(1));
          for (uint32_t n = 0; !ok_pk<2>(p, tag) && n < SPIN_LIMIT; n++) { p[0] = ld_ll(sp); p[1] = ld_ll(sp + 8); }
          TS(9 + 20 * L);
          float ml, rl, mh, rh;
          combine_stats(p[0], p[1], ml, rl, mh, rh);
          rl2 = pack2(rl, rl); rh2 = pack2(rh, rh);
          const float rlb = bf_lo(rl2), rhb = bf_lo(rh2);
          bl2 = pack2(-ml * rlb, -ml * rlb); bh2 = pack2(-mh * rhb, -mh * rhb);
          cl = rl / rlb; cl *= cl; ch = rh / rhb; ch *= ch;
        }
        auto normalise = [&](uint4 (&xb)[4], int kb) {
#pragma unroll
          for (int k = 0; k < 4; k++) {
            xb[k].x = hfma2(xb[k].x, rl2, bl2); xb[k].y = hfma2(xb[k].y, rh2, bh2);
            xb[k].z = hfma2(xb[k].z, rl2, bl2); xb[k].w = hfma2(xb[k].w, rh2, bh2);
            sts128(sm + (kb * 4 + k) * 2048, xb[k]);
          }
        };
        normalise(A[0], 0);
        static_for<0, 8>([&](auto I) {
          constexpr int kb = I.value;
          cons_acquire<ST_G1 + 2 * kb>(sbase, L);
          wg_fence();
          wgmma_n256<kb == 0, 0>(acc, A[kb % 3][0], st_desc<ST_G1 + 2 * kb, 2048, 4096, 1024, 1>(0));
          wgmma_n256<false, 0>(acc, A[kb % 3][1], st_desc<ST_G1 + 2 * kb, 2048, 4096, 1024, 1>(1));
          wg_commit();
          cons_acquire<ST_G1 + 2 * kb + 1>(sbase, L);
          __syncwarp();
          wg_fence();
          wgmma_n256<false, 0>(acc, A[kb % 3][2], st_desc<ST_G1 + 2 * kb + 1, 2048, 4096, 1024, 1>(0));
          wgmma_n256<false, 0>(acc, A[kb % 3][3], st_desc<ST_G1 + 2 * kb + 1, 2048, 4096, 1024, 1>(1));
          wg_commit();
          wg_wait<1>();
          if constexpr (kb > 0) {
            keep4(A[(kb + 2) % 3]);
            cons_release<ST_G1 + 2 * kb - 1>(sbase, lane);
          }
          cons_release<ST_G1 + 2 * kb>(sbase, lane);
          if constexpr (kb + 1 < 8) ensure_pk<4>(A[(kb + 1) % 3], xsrc(kb + 1), 0u);
          if constexpr (kb + 2 < 8) load_pk<4>(A[(kb + 2) % 3], xsrc(kb + 2));
          if constexpr (kb + 1 < 8) normalise(A[(kb + 1) % 3], kb + 1);
        });
        wg_wait<0>();
        TS(10 + 20 * L);
        fence_acc(acc);
        keep4(A[1]);
        cons_release<ST_G1 + 15>(sbase, lane);
        uint4 B[2][4];
#pragma unroll
        for (int k = 0; k < 4; k++) B[0][k] = lds128(sm + k * 2048);
#pragma unroll
        for (int s = 0; s < 8; s++) hs[s] = glu8<32>(&acc[64 * (s >> 2) + 8 * (s & 3)], cl, ch);
        float acc2[96];
        const uint32_t hdst = mapa(sm, cbit ^ 1);
        const uint32_t hbar1 = mapa(bars + BAR_HRECV + 16 * g, cbit ^ 1);
        if (t128 == 0) { mbar_expect_tx(bars + BAR_HRECV + 16 * g, 8 * 2048); mbar_expect_tx(bars + BAR_HRECV + 16 * g + 8, 6 * 2048); }
        static_for<0, 8>([&](auto I) {
          constexpr int kb = I.value;
          cons_acquire<ST_G2 + kb>(sbase, L);
          wg_fence();
          static_for<0, 4>([&](auto K) {
            constexpr int k = K.value;
            wgmma_n128<kb == 0 && k == 0, 0>(acc2, B[kb & 1][k], st_desc<ST_G2 + kb, 2048, 8192, 1024, 1>(k));
            wgmma_n64<kb == 0 && k == 0, 64>(acc2, B[kb & 1][k], st_desc<ST_G2 + kb, 1024, 4096, 512, 2>(k) + (16384 >> 4));
          });
          wg_commit();
          if constexpr (kb > 0) {
            wg_wait<1>();
            keep4(B[(kb + 1) & 1]);
            cons_release<ST_G2 + kb - 1>(sbase, lane);
          }
          if constexpr (kb + 1 < 8) {
#pragma unroll
            for (int k = 0; k < 4; k++) B[(kb + 1) & 1][k] = lds128(sm + ((kb + 1) * 4 + k) * 2048);
          }
          if constexpr (kb == 3) {
            __syncwarp();
            if (lane == 0) mbar_arrive_remote(mapa(bars + BAR_HREADY + 8 * g, cbit ^ 1));
          }
          if constexpr (kb >= 4) {
            if constexpr (kb == 4) mbar_wait(bars + BAR_HREADY + 8 * g, L);
            st_async128(hdst + (2 * kb - 8) * 2048, hs[2 * kb - 8], hbar1);
            st_async128(hdst + (2 * kb - 7) * 2048, hs[2 * kb - 7], hbar1);
          }
        });
        wg_wait<0>();
        TS(11 + 20 * L);
        fence_acc(acc2);
        keep4(B[1]);
        cons_release<ST_G2 + 7>(sbase, lane);
#pragma unroll
        for (int s = 0; s < 4; s++) hs[8 + s] = glu8<32>(&acc2[8 * s], cl, ch);
#pragma unroll
        for (int s = 0; s < 2; s++) hs[12 + s] = glu8<16>(&acc2[64 + 8 * s], cl, ch);
      }
      {
        PHASE_VARS;
        TS(12 + 20 * L);
        const uint32_t hdst = mapa(areg + t128 * 16, cbit ^ 1);
        const uint32_t hbar2 = mapa(bars + BAR_HRECV + 16 * g + 8, cbit ^ 1);
        uint4* pd = g_arena + c * ARENA + AR_PART + (((slab * 2 + cbit) * 4 + ca) * 16) * 32 + lane;
        const uint4* ps = g_arena + c * ARENA + AR_PART + (((j * 2 + g) * 4) * 16 + w) * 32 + lane;
        auto fetch_partials = [&](int q) {
#pragma unroll
          for (int src = 0; src < 4; src++) cp_async16(areg + t128 * 16 + (14 + 4 * q + src) * 2048, ps + src * (16 * 32) + q * 128);
        };
        uint4 hb[7];
        float a0[32], a1[32], a2[32], a3[32];
        auto publish = [&](float (&a)[32], int q, int s0, int s1) {
#pragma unroll
          for (int s = s0; s < s1; s++) {
            uint4 o = pack8(&a[8 * s]);
            o.x = set_tag(o.x, tag);
            st_ll(pd + (4 * q + s) * 32, o);
          }
        };
        static_for<0, 16>([&](auto I) {
          constexpr int i = I.value, q = dn_q(i), par = dn_par(i), kh = dn_kh(i);
          auto mm = [&](auto K) {
            constexpr int k = decltype(K)::value;
            constexpr bool init = (k == 0 && par == 0 && kh == 0);
            constexpr uint64_t db = st_desc<ST_DN + i, 2048, 8192, 1024, 1>(k);
            if constexpr (q == 0) { if constexpr (par) wgmma_n64<init, 0>(a0, hb[k], db); else wgmma_n64<init, 0>(a0, hs[7 * kh + k], db); }
            if constexpr (q == 1) { if constexpr (par) wgmma_n64<init, 0>(a1, hb[k], db); else wgmma_n64<init, 0>(a1, hs[7 * kh + k], db); }
            if constexpr (q == 2) { if constexpr (par) wgmma_n64<init, 0>(a2, hb[k], db); else wgmma_n64<init, 0>(a2, hs[7 * kh + k], db); }
            if constexpr (q == 3) { if constexpr (par) wgmma_n64<init, 0>(a3, hb[k], db); else wgmma_n64<init, 0>(a3, hs[7 * kh + k], db); }
          };
          cons_acquire<ST_DN + i>(sbase, L);
          wg_fence();
          mm(IC<0>{}); mm(IC<1>{}); mm(IC<2>{}); mm(IC<3>{}); mm(IC<4>{}); mm(IC<5>{}); mm(IC<6>{});
          wg_commit();
          if constexpr (i > 0) { wg_wait<1>(); cons_release<ST_DN + i - 1>(sbase, lane); }
          if constexpr (i < 3) {
            st_async128(hdst + (8 + 2 * i) * 2048, hs[8 + 2 * i], hbar2);
            st_async128(hdst + (9 + 2 * i) * 2048, hs[9 + 2 * i], hbar2);
          }
          constexpr int n = i + 1;
          if constexpr (n < 16 && dn_par(n) && n != 4 && n != 7) {
            if constexpr (n == 2) { mbar_wait(bars + BAR_HRECV + 16 * g, L); TS(13 + 20 * L); }
            if constexpr (n == 6) { mbar_wait(bars + BAR_HRECV + 16 * g + 8, L); TS(14 + 20 * L); }
#pragma unroll
            for (int k = 0; k < 7; k++) { if constexpr (n != 2) keep(hb[k]); hb[k] = lds128(areg + t128 * 16 + (7 * dn_kh(n) + k) * 2048); }
          }
          if constexpr (i == 7) { fence_acc(a0); publish(a0, 0, 0, 4); }
          if constexpr (i == 8) { fence_acc(a1); publish(a1, 1, 0, 2); }
          if constexpr (i == 9) publish(a1, 1, 2, 4);
          if constexpr (i == 12) { fence_acc(a2); publish(a2, 2, 0, 2); }
          if constexpr (i == 13) publish(a2, 2, 2, 4);
#define FQ0 11
#define FQ1 12
#define FQ2 15
          if constexpr (i == FQ0) fetch_partials(0);
          if constexpr (i == FQ1) fetch_partials(1);
          if constexpr (i == FQ2) fetch_partials(2);
        });
        wg_wait<0>();
        TS(15 + 20 * L);
        fence_acc(a3);
#pragma unroll
        for (int k = 0; k < 7; k++) { keep(hb[k]); keep(hs[7 + k]); }
        cons_release<NSTAGE - 1>(sbase, lane);
        {
          uint4* p3 = g_arena + c * ARENA + AR_O + (slab * 32 + (cbit * 4 + ca) * 4) * 32 + lane;
#pragma unroll
          for (int s = 0; s < 4; s++) { uint4 o = pack8(&a3[8 * s]); o.x &= ~1u; st_ll(p3 + s * 32, o); }
        }
      }
      {
        PHASE_VARS;
        const uint4* xq = g_arena + c * ARENA + AR_XRAW + (j * 32 + 16 * g + w) * 32 + lane;
        const uint4* ps = g_arena + c * ARENA + AR_PART + (((j * 2 + g) * 4) * 16 + w) * 32 + lane;
        const uint32_t sm = areg + t128 * 16;
        uint4 xr[4];
        float v[32];
#pragma unroll
        for (int i = 0; i < 4; i++) xr[i] = ld_ll(xq + i * 128);
        auto add_group = [&](uint4 (&P)[4], int i) {
          float d[8] = {0, 0, 0, 0, 0, 0, 0, 0};
#pragma unroll
          for (int src = 0; src < 4; src++) {
            const uint4 p = P[src];
            d[0] += bf_lo(p.x); d[1] += bf_hi(p.x); d[2] += bf_lo(p.y); d[3] += bf_hi(p.y);
            d[4] += bf_lo(p.z); d[5] += bf_hi(p.z); d[6] += bf_lo(p.w); d[7] += bf_hi(p.w);
          }
#pragma unroll
          for (int k = 0; k < 8; k++) v[8 * i + k] = d[k];
        };
        TF(true, 0 + 8 * L);
        cp_wait_all();
        TF(true, 1 + 8 * L);
        uint32_t r1 = 0, r2 = 0, r3 = 0;
        {
          uint4 P[3][4];
#pragma unroll
          for (int k = 0; k < 12; k++) P[k >> 2][k & 3] = lds128(sm + (14 + k) * 2048);
          for (uint32_t n = 0; !ok_pk<12>(&P[0][0], tag) && n < SPIN_LIMIT; n++) {
            r1++;
#pragma unroll
            for (int k = 0; k < 12; k++) P[k >> 2][k & 3] = ld_ll(ps + (k & 3) * (16 * 32) + (k >> 2) * 128);
          }
          TF(true, 2 + 8 * L);
          add_group(P[0], 0); add_group(P[1], 1); add_group(P[2], 2);
        }
        TF(true, 3 + 8 * L);
        for (uint32_t n = 0; !ok_pk<4>(xr, 0u) && n < SPIN_LIMIT; n++) {
          r2++;
#pragma unroll
          for (int i = 0; i < 4; i++) xr[i] = ld_ll(xq + i * 128);
        }
        TF(true, 4 + 8 * L);
        spin_for(L ? D_PT1 : D_PT0);
        {
          uint4 P[4];
          const uint4* p3 = g_arena + c * ARENA + AR_O + (j * 32 + 16 * g + w) * 32 + lane;
          uint32_t n = 0;
          do {
#pragma unroll
            for (int k = 0; k < 4; k++) P[k] = ld_ll(p3 + k * 128);
          } while (!ok_pk<4>(P, 0u) && ++n < SPIN_LIMIT);
          r3 = n;
          TV(5 + 8 * L, r1); TV(6 + 8 * L, r2); TV(7 + 8 * L, r3);
          TS(16 + 20 * L);
          add_group(P, 3);
        }
#pragma unroll
        for (int i = 0; i < 4; i++) {
          v[8 * i + 0] += bf_lo(xr[i].x); v[8 * i + 1] += bf_hi(xr[i].x); v[8 * i + 2] += bf_lo(xr[i].y); v[8 * i + 3] += bf_hi(xr[i].y);
          v[8 * i + 4] += bf_lo(xr[i].z); v[8 * i + 5] += bf_hi(xr[i].z); v[8 * i + 6] += bf_lo(xr[i].w); v[8 * i + 7] += bf_hi(xr[i].w);
        }
        if (L == 1) {
          uint32_t* op = reinterpret_cast<uint32_t*>(out + (size_t)(slab_row0(c, j >> 2, j & 3) + 2 * qr) * 512 + (16 * g + w) * 16 + qc * 2);
#pragma unroll
          for (int i = 0; i < 4; i++) {
            op[i * 32] = pack2(v[8 * i], v[8 * i + 1]);
            op[16 * 256 + i * 32] = pack2(v[8 * i + 2], v[8 * i + 3]);
            op[i * 32 + 4] = pack2(v[8 * i + 4], v[8 * i + 5]);
            op[16 * 256 + i * 32 + 4] = pack2(v[8 * i + 6], v[8 * i + 7]);
          }
          TS(37);
        }
#pragma unroll
        for (int i = 0; i < 32; i++) vres[i] = v[i];
      }
    }
    TG(62);
    TG(63);
  }
}

typedef CUresult (*EncodeFn)(CUtensorMap*, CUtensorMapDataType, cuuint32_t, void*, const cuuint64_t*, const cuuint64_t*,
                             const cuuint32_t*, const cuuint32_t*, CUtensorMapInterleave, CUtensorMapSwizzle,
                             CUtensorMapL2promotion, CUtensorMapFloatOOBfill);

void encode(EncodeFn fn, CUtensorMap* m, int rank, const void* base, const cuuint64_t* dims, const cuuint64_t* strides,
            const cuuint32_t* box, CUtensorMapSwizzle sw) {
  cuuint32_t es[5] = {1, 1, 1, 1, 1};
  fn(m, CU_TENSOR_MAP_DATA_TYPE_BFLOAT16, (cuuint32_t)rank, const_cast<void*>(base), dims, strides, box, es,
     CU_TENSOR_MAP_INTERLEAVE_NONE, sw, CU_TENSOR_MAP_L2_PROMOTION_L2_128B, CU_TENSOR_MAP_FLOAT_OOB_FILL_NONE);
}

}

extern "C" void kernel_launch(void* const* d_in, const int* in_sizes, int n_in, void* d_out, int out_size) {
  (void)in_sizes; (void)n_in; (void)out_size;
  const __nv_bfloat16* x = (const __nv_bfloat16*)d_in[0];
  const char* wqkv = (const char*)d_in[1];
  const char* wo = (const char*)d_in[2];
  const char* wg = (const char*)d_in[4];
  const char* wu = (const char*)d_in[5];
  const char* wd = (const char*)d_in[6];

  static EncodeFn fn = nullptr;
  if (!fn) {
    void* p = nullptr;
    cudaDriverEntryPointQueryResult st;
    cudaGetDriverEntryPoint("cuTensorMapEncodeTiled", &p, cudaEnableDefault, &st);
    fn = (EncodeFn)p;
    cudaFuncSetAttribute(fused_kernel, cudaFuncAttributeMaxDynamicSharedMemorySize, SMEM_BYTES);
  }
  CUtensorMap m_qkv, m_wo, m_gu2, m_gu1, m_guh, m_wd112, m_wd80, m_wd32;
  {
    cuuint64_t dims[3] = {512, 512, 3}, str[2] = {3072, 1024};
    cuuint32_t box[3] = {64, 64, 3};
    encode(fn, &m_qkv, 3, wqkv, dims, str, box, CU_TENSOR_MAP_SWIZZLE_128B);
  }
  {
    cuuint64_t dims[2] = {512, 512}, str[1] = {1024};
    cuuint32_t box[2] = {64, 128};
    encode(fn, &m_wo, 2, wo, dims, str, box, CU_TENSOR_MAP_SWIZZLE_128B);
  }
  {
    const char* lo = wg < wu ? wg : wu;
    cuuint64_t diff = (cuuint64_t)(wg < wu ? wu - wg : wg - wu);
    cuuint64_t dims[4] = {1792, 512, 2, 2}, str[3] = {3584, diff, 128};
    cuuint32_t box2[4] = {64, 32, 2, 2}, box1[4] = {64, 64, 2, 1}, boxh[3] = {32, 64, 2};
    encode(fn, &m_gu2, 4, lo, dims, str, box2, CU_TENSOR_MAP_SWIZZLE_128B);
    encode(fn, &m_gu1, 4, lo, dims, str, box1, CU_TENSOR_MAP_SWIZZLE_128B);
    encode(fn, &m_guh, 3, lo, dims, str, boxh, CU_TENSOR_MAP_SWIZZLE_64B);
  }
  {
    cuuint64_t dims[2] = {512, 1792}, str[1] = {1024};
    cuuint32_t b112[2] = {64, 112}, b80[2] = {64, 80}, b32[2] = {64, 32};
    encode(fn, &m_wd112, 2, wd, dims, str, b112, CU_TENSOR_MAP_SWIZZLE_128B);
    encode(fn, &m_wd80, 2, wd, dims, str, b80, CU_TENSOR_MAP_SWIZZLE_128B);
    encode(fn, &m_wd32, 2, wd, dims, str, b32, CU_TENSOR_MAP_SWIZZLE_128B);
  }
  cudaLaunchConfig_t cfg = {};
  cfg.gridDim = dim3(128);
  cfg.blockDim = dim3(NTHREADS);
  cfg.dynamicSmemBytes = SMEM_BYTES;
  cfg.stream = cudaStreamPerThread;
  cudaLaunchAttribute at[1];
  at[0].id = cudaLaunchAttributeClusterDimension;
  at[0].val.clusterDim.x = 2; at[0].val.clusterDim.y = 1; at[0].val.clusterDim.z = 1;
  cfg.attrs = at; cfg.numAttrs = 1;
  cudaLaunchKernelEx(&cfg, fused_kernel, m_qkv, m_wo, m_gu2, m_gu1, m_guh, m_wd112, m_wd80, m_wd32, x, (__nv_bfloat16*)d_out
  );
}
```

```cpp
#include <cuda_runtime.h>
#include <cuda_bf16.h>
#include <cuda.h>
#include <stdint.h>

namespace {

constexpr int NTHREADS = 384;
constexpr int GRAN = 8192;
constexpr int NGRAN = 12;
constexpr int SM_AREG = NGRAN * GRAN;
constexpr int SM_MISC = SM_AREG + 131072;
constexpr int SM_TSTAT = SM_MISC + 256;
constexpr int SMEM_BYTES = SM_TSTAT + 1024;
constexpr int BAR_FULL = 0, BAR_EMPTY = 96, BAR_HRECV = 192, BAR_HREADY = 224;

constexpr int AR_XN = 0, AR_XRAW = 8192, AR_O = 16384, AR_STATS = 24576, AR_HALO = 25088, AR_PART = 33280, ARENA = 66048;
__device__ __align__(1024) uint4 g_arena[16 * ARENA];

#define OPAQUE(x) asm volatile("" : "+r"(x))
#define PHASE_VARS                                                                                   \
  int tid_ = threadIdx.x, bid_ = blockIdx.x;                                                         \
  OPAQUE(tid_); OPAQUE(bid_);                                                                        \
  const int lane = tid_ & 31, warp = tid_ >> 5, g = warp >> 2, w = warp & 3, t128 = tid_ & 127;      \
  const int qr = lane >> 2, qc = lane & 3, slab = warp;                                              \
  const int c = bid_ >> 3, j = bid_ & 7, ca = j >> 1, cbit = j & 1;                                  \
  const uint32_t areg = sbase + SM_AREG + g * 65536;                                                 \
  (void)g; (void)j; (void)w; (void)t128; (void)qr; (void)qc; (void)slab; (void)c; (void)ca; (void)cbit; (void)areg; (void)lane

__device__ __forceinline__ uint32_t smem_u32(const void* p) { return (uint32_t)__cvta_generic_to_shared(p); }
__device__ __forceinline__ void mbar_init(uint32_t bar, uint32_t cnt) {
  asm volatile("mbarrier.init.shared::cta.b64 [%0], %1;" ::"r"(bar), "r"(cnt) : "memory");
}
__device__ __forceinline__ void mbar_expect_tx(uint32_t bar, uint32_t bytes) {
  asm volatile("mbarrier.arrive.expect_tx.shared::cta.b64 _, [%0], %1;" ::"r"(bar), "r"(bytes) : "memory");
}
__device__ __forceinline__ void mbar_arrive(uint32_t bar) {
  asm volatile("mbarrier.arrive.shared::cta.b64 _, [%0];" ::"r"(bar) : "memory");
}
__device__ __forceinline__ void mbar_arrive_remote(uint32_t cluster_addr) {
  asm volatile("mbarrier.arrive.relaxed.cluster.shared::cluster.b64 _, [%0];" ::"r"(cluster_addr) : "memory");
}
__device__ __forceinline__ bool mbar_try(uint32_t bar, uint32_t parity) {
  uint32_t ok;
  asm volatile("{\n.reg .pred p;\nmbarrier.try_wait.parity.shared::cta.b64 p, [%1], %2;\nselp.u32 %0, 1, 0, p;\n}"
               : "=r"(ok) : "r"(bar), "r"(parity) : "memory");
  return ok != 0;
}
constexpr uint32_t SPIN_LIMIT = 1u << 16;
constexpr uint32_t MBAR_LIMIT = 1u << 20;
constexpr uint32_t SMEM_ORIGIN = 1024;
__device__ __forceinline__ void mbar_wait(uint32_t bar, uint32_t parity) {
  for (uint32_t n = 0; !mbar_try(bar, parity) && n < MBAR_LIMIT; n++) {}
}
__device__ __forceinline__ uint32_t mapa(uint32_t addr, uint32_t rank) {
  uint32_t r;
  asm volatile("mapa.shared::cluster.u32 %0, %1, %2;" : "=r"(r) : "r"(addr), "r"(rank));
  return r;
}

__device__ __forceinline__ void tma_2d(uint32_t dst, const CUtensorMap* m, uint32_t bar, int c0, int c1) {
  asm volatile("cp.async.bulk.tensor.2d.shared::cluster.global.mbarrier::complete_tx::bytes [%0], [%1, {%3, %4}], [%2];"
               ::"r"(dst), "l"(m), "r"(bar), "r"(c0), "r"(c1) : "memory");
}
__device__ __forceinline__ void tma_3d(uint32_t dst, const CUtensorMap* m, uint32_t bar, int c0, int c1, int c2) {
  asm volatile("cp.async.bulk.tensor.3d.shared::cluster.global.mbarrier::complete_tx::bytes [%0], [%1, {%3, %4, %5}], [%2];"
               ::"r"(dst), "l"(m), "r"(bar), "r"(c0), "r"(c1), "r"(c2) : "memory");
}
__device__ __forceinline__ void tma_4d(uint32_t dst, const CUtensorMap* m, uint32_t bar, int c0, int c1, int c2, int c3) {
  asm volatile("cp.async.bulk.tensor.4d.shared::cluster.global.mbarrier::complete_tx::bytes [%0], [%1, {%3, %4, %5, %6}], [%2];"
               ::"r"(dst), "l"(m), "r"(bar), "r"(c0), "r"(c1), "r"(c2), "r"(c3) : "memory");
}

__device__ __forceinline__ uint4 ld_ll(const uint4* p) {
  uint4 v;
  asm volatile("ld.relaxed.gpu.global.v4.u32 {%0,%1,%2,%3}, [%4];" : "=r"(v.x), "=r"(v.y), "=r"(v.z), "=r"(v.w) : "l"(p) : "memory");
  return v;
}
__device__ __forceinline__ void st_ll(uint4* p, uint4 v) {
  asm volatile("st.relaxed.gpu.global.v4.u32 [%0], {%1,%2,%3,%4};" ::"l"(p), "r"(v.x), "r"(v.y), "r"(v.z), "r"(v.w) : "memory");
}
__device__ __forceinline__ uint4 lds128(uint32_t a) {
  uint4 v;
  asm volatile("ld.shared.v4.u32 {%0,%1,%2,%3}, [%4];" : "=r"(v.x), "=r"(v.y), "=r"(v.z), "=r"(v.w) : "r"(a) : "memory");
  return v;
}
__device__ __forceinline__ void sts128(uint32_t a, uint4 v) {
  asm volatile("st.shared.v4.u32 [%0], {%1,%2,%3,%4};" ::"r"(a), "r"(v.x), "r"(v.y), "r"(v.z), "r"(v.w) : "memory");
}
__device__ __forceinline__ void st_async128(uint32_t cluster_addr, uint4 v, uint32_t cluster_bar) {
  asm volatile("st.async.weak.shared::cluster.mbarrier::complete_tx::bytes.v4.b32 [%0], {%1,%2,%3,%4}, [%5];"
               ::"r"(cluster_addr), "r"(v.x), "r"(v.y), "r"(v.z), "r"(v.w), "r"(cluster_bar) : "memory");
}
__device__ __forceinline__ uint32_t pack2(float lo, float hi) {
  uint32_t r;
  asm("cvt.rn.bf16x2.f32 %0, %1, %2;" : "=r"(r) : "f"(hi), "f"(lo));
  return r;
}
__device__ __forceinline__ float bf_lo(uint32_t w) { return __uint_as_float(w << 16); }
__device__ __forceinline__ float bf_hi(uint32_t w) { return __uint_as_float(w & 0xffff0000u); }
__device__ __forceinline__ uint32_t set_tag(uint32_t w, uint32_t tag) { return (w & ~1u) | tag; }
__device__ __forceinline__ uint32_t movm(uint32_t a) {
  uint32_t d;
  asm("movmatrix.sync.aligned.m8n8.trans.b16 %0, %1;" : "=r"(d) : "r"(a));
  return d;
}
__device__ __forceinline__ void mma1688(float (&d)[4], uint32_t a0, uint32_t a1, uint32_t b0) {
  asm("mma.sync.aligned.m16n8k8.row.col.f32.bf16.bf16.f32 {%0,%1,%2,%3}, {%4,%5}, {%6}, {%0,%1,%2,%3};"
      : "+f"(d[0]), "+f"(d[1]), "+f"(d[2]), "+f"(d[3])
      : "r"(a0), "r"(a1), "r"(b0));
}
__device__ __forceinline__ void mma16816_z(float (&d)[4], const uint4& a, uint32_t b0, uint32_t b1) {
  asm("mma.sync.aligned.m16n8k16.row.col.f32.bf16.bf16.f32 {%0,%1,%2,%3}, {%4,%5,%6,%7}, {%8,%9}, {%10,%10,%10,%10};"
      : "=f"(d[0]), "=f"(d[1]), "=f"(d[2]), "=f"(d[3])
      : "r"(a.x), "r"(a.y), "r"(a.z), "r"(a.w), "r"(b0), "r"(b1), "f"(0.f));
}
__device__ __forceinline__ float ex2(float x) {
  float y;
  asm("ex2.approx.ftz.f32 %0, %1;" : "=f"(y) : "f"(x));
  return y;
}
__device__ __forceinline__ float rcp(float x) {
  float y;
  asm("rcp.approx.ftz.f32 %0, %1;" : "=f"(y) : "f"(x));
  return y;
}
__device__ __forceinline__ void cp_async16(uint32_t dst, const void* src) {
  asm volatile("cp.async.cg.shared.global [%0], [%1], 16;" ::"r"(dst), "l"(src) : "memory");
}
__device__ __forceinline__ void cp_wait_all() { asm volatile("cp.async.wait_all;" ::: "memory"); }
template <int N> __device__ __forceinline__ void cp_wait() { asm volatile("cp.async.wait_group %0;" ::"n"(N) : "memory"); }
__device__ __forceinline__ void bar_wg(int id) { asm volatile("bar.sync %0, 128;" ::"r"(id) : "memory"); }
__device__ __forceinline__ void spin_for(uint32_t clks) {
  const uint32_t t0 = (uint32_t)clock();
  while ((uint32_t)clock() - t0 < clks) {}
}
constexpr uint32_t D_XN0 = 900;
constexpr uint32_t D_XN1 = 300;
constexpr uint32_t D_HALO0 = 1200;
constexpr uint32_t D_HALO1 = 800;
constexpr uint32_t D_O0 = 1200;
constexpr uint32_t D_O1 = 800;
constexpr uint32_t D_ST0 = 1200;
constexpr uint32_t D_ST1 = 500;
constexpr uint32_t D_PT0 = 0;
constexpr uint32_t D_PT1 = 0;
__device__ __forceinline__ void wg_fence() { asm volatile("wgmma.fence.sync.aligned;" ::: "memory"); }
__device__ __forceinline__ void wg_commit() { asm volatile("wgmma.commit_group.sync.aligned;" ::: "memory"); }
template <int N> __device__ __forceinline__ void wg_wait() { asm volatile("wgmma.wait_group.sync.aligned %0;" ::"n"(N) : "memory"); }
__device__ __forceinline__ void keep(const uint4& a) { asm volatile("" ::"r"(a.x), "r"(a.y), "r"(a.z), "r"(a.w) : "memory"); }
template <int T> __device__ __forceinline__ void zero_acc(float (&d)[T]) {
#pragma unroll
  for (int i = 0; i < T; i++) d[i] = 0.f;
}
template <int T> __device__ __forceinline__ void fence_acc(float (&d)[T]) {
#pragma unroll
  for (int i = 0; i < T; i++) asm volatile("" : "+f"(d[i])::"memory");
}

template <int O, int T> __device__ __forceinline__ void wgmma_rs_n64(float (&d)[T], const uint4& a, uint64_t db) {
  asm volatile("{\n.reg .pred p;\nsetp.ne.b32 p, 1, 0;\n"
    "wgmma.mma_async.sync.aligned.m64n64k16.f32.bf16.bf16 "
    "{%0, %1, %2, %3, %4, %5, %6, %7, %8, %9, %10, %11, %12, %13, %14, %15, "
    "%16, %17, %18, %19, %20, %21, %22, %23, %24, %25, %26, %27, %28, %29, %30, %31}, "
    "{%32, %33, %34, %35}, %36, p, 1, 1, 1;\n}\n"
    : "+f"(d[O + 0]), "+f"(d[O + 1]), "+f"(d[O + 2]), "+f"(d[O + 3]), "+f"(d[O + 4]), "+f"(d[O + 5]), "+f"(d[O + 6]), "+f"(d[O + 7]),
      "+f"(d[O + 8]), "+f"(d[O + 9]), "+f"(d[O + 10]), "+f"(d[O + 11]), "+f"(d[O + 12]), "+f"(d[O + 13]), "+f"(d[O + 14]), "+f"(d[O + 15]),
      "+f"(d[O + 16]), "+f"(d[O + 17]), "+f"(d[O + 18]), "+f"(d[O + 19]), "+f"(d[O + 20]), "+f"(d[O + 21]), "+f"(d[O + 22]), "+f"(d[O + 23]),
      "+f"(d[O + 24]), "+f"(d[O + 25]), "+f"(d[O + 26]), "+f"(d[O + 27]), "+f"(d[O + 28]), "+f"(d[O + 29]), "+f"(d[O + 30]), "+f"(d[O + 31])
    : "r"(a.x), "r"(a.y), "r"(a.z), "r"(a.w), "l"(db));
}
template <int O, int T> __device__ __forceinline__ void wgmma_rs_n64_init(float (&d)[T], const uint4& a, uint64_t db) {
  asm volatile("{\n.reg .pred p;\nsetp.ne.b32 p, 0, 0;\n"
    "wgmma.mma_async.sync.aligned.m64n64k16.f32.bf16.bf16 "
    "{%0, %1, %2, %3, %4, %5, %6, %7, %8, %9, %10, %11, %12, %13, %14, %15, "
    "%16, %17, %18, %19, %20, %21, %22, %23, %24, %25, %26, %27, %28, %29, %30, %31}, "
    "{%32, %33, %34, %35}, %36, p, 1, 1, 1;\n}\n"
    : "=f"(d[O + 0]), "=f"(d[O + 1]), "=f"(d[O + 2]), "=f"(d[O + 3]), "=f"(d[O + 4]), "=f"(d[O + 5]), "=f"(d[O + 6]), "=f"(d[O + 7]),
      "=f"(d[O + 8]), "=f"(d[O + 9]), "=f"(d[O + 10]), "=f"(d[O + 11]), "=f"(d[O + 12]), "=f"(d[O + 13]), "=f"(d[O + 14]), "=f"(d[O + 15]),
      "=f"(d[O + 16]), "=f"(d[O + 17]), "=f"(d[O + 18]), "=f"(d[O + 19]), "=f"(d[O + 20]), "=f"(d[O + 21]), "=f"(d[O + 22]), "=f"(d[O + 23]),
      "=f"(d[O + 24]), "=f"(d[O + 25]), "=f"(d[O + 26]), "=f"(d[O + 27]), "=f"(d[O + 28]), "=f"(d[O + 29]), "=f"(d[O + 30]), "=f"(d[O + 31])
    : "r"(a.x), "r"(a.y), "r"(a.z), "r"(a.w), "l"(db));
}
template <bool INIT, int O, int T> __device__ __forceinline__ void wgmma_n64(float (&d)[T], const uint4& a, uint64_t db) {
  if constexpr (INIT) wgmma_rs_n64_init<O>(d, a, db); else wgmma_rs_n64<O>(d, a, db);
}
template <int O, int T> __device__ __forceinline__ void wgmma_rs_n128(float (&d)[T], const uint4& a, uint64_t db) {
  asm volatile("{\n.reg .pred p;\nsetp.ne.b32 p, 1, 0;\n"
    "wgmma.mma_async.sync.aligned.m64n128k16.f32.bf16.bf16 "
    "{%0, %1, %2, %3, %4, %5, %6, %7, %8, %9, %10, %11, %12, %13, %14, %15, "
    "%16, %17, %18, %19, %20, %21, %22, %23, %24, %25, %26, %27, %28, %29, %30, %31, "
    "%32, %33, %34, %35, %36, %37, %38, %39, %40, %41, %42, %43, %44, %45, %46, %47, "
    "%48, %49, %50, %51, %52, %53, %54, %55, %56, %57, %58, %59, %60, %61, %62, %63}, "
    "{%64, %65, %66, %67}, %68, p, 1, 1, 1;\n}\n"
    : "+f"(d[O + 0]), "+f"(d[O + 1]), "+f"(d[O + 2]), "+f"(d[O + 3]), "+f"(d[O + 4]), "+f"(d[O + 5]), "+f"(d[O + 6]), "+f"(d[O + 7]),
      "+f"(d[O + 8]), "+f"(d[O + 9]), "+f"(d[O + 10]), "+f"(d[O + 11]), "+f"(d[O + 12]), "+f"(d[O + 13]), "+f"(d[O + 14]), "+f"(d[O + 15]),
      "+f"(d[O + 16]), "+f"(d[O + 17]), "+f"(d[O + 18]), "+f"(d[O + 19]), "+f"(d[O + 20]), "+f"(d[O + 21]), "+f"(d[O + 22]), "+f"(d[O + 23]),
      "+f"(d[O + 24]), "+f"(d[O + 25]), "+f"(d[O + 26]), "+f"(d[O + 27]), "+f"(d[O + 28]), "+f"(d[O + 29]), "+f"(d[O + 30]), "+f"(d[O + 31]),
      "+f"(d[O + 32]), "+f"(d[O + 33]), "+f"(d[O + 34]), "+f"(d[O + 35]), "+f"(d[O + 36]), "+f"(d[O + 37]), "+f"(d[O + 38]), "+f"(d[O + 39]),
      "+f"(d[O + 40]), "+f"(d[O + 41]), "+f"(d[O + 42]), "+f"(d[O + 43]), "+f"(d[O + 44]), "+f"(d[O + 45]), "+f"(d[O + 46]), "+f"(d[O + 47]),
      "+f"(d[O + 48]), "+f"(d[O + 49]), "+f"(d[O + 50]), "+f"(d[O + 51]), "+f"(d[O + 52]), "+f"(d[O + 53]), "+f"(d[O + 54]), "+f"(d[O + 55]),
      "+f"(d[O + 56]), "+f"(d[O + 57]), "+f"(d[O + 58]), "+f"(d[O + 59]), "+f"(d[O + 60]), "+f"(d[O + 61]), "+f"(d[O + 62]), "+f"(d[O + 63])
    : "r"(a.x), "r"(a.y), "r"(a.z), "r"(a.w), "l"(db));
}
template <int O, int T> __device__ __forceinline__ void wgmma_rs_n128_init(float (&d)[T], const uint4& a, uint64_t db) {
  asm volatile("{\n.reg .pred p;\nsetp.ne.b32 p, 0, 0;\n"
    "wgmma.mma_async.sync.aligned.m64n128k16.f32.bf16.bf16 "
    "{%0, %1, %2, %3, %4, %5, %6, %7, %8, %9, %10, %11, %12, %13, %14, %15, "
    "%16, %17, %18, %19, %20, %21, %22, %23, %24, %25, %26, %27, %28, %29, %30, %31, "
    "%32, %33, %34, %35, %36, %37, %38, %39, %40, %41, %42, %43, %44, %45, %46, %47, "
    "%48, %49, %50, %51, %52, %53, %54, %55, %56, %57, %58, %59, %60, %61, %62, %63}, "
    "{%64, %65, %66, %67}, %68, p, 1, 1, 1;\n}\n"
    : "=f"(d[O + 0]), "=f"(d[O + 1]), "=f"(d[O + 2]), "=f"(d[O + 3]), "=f"(d[O + 4]), "=f"(d[O + 5]), "=f"(d[O + 6]), "=f"(d[O + 7]),
      "=f"(d[O + 8]), "=f"(d[O + 9]), "=f"(d[O + 10]), "=f"(d[O + 11]), "=f"(d[O + 12]), "=f"(d[O + 13]), "=f"(d[O + 14]), "=f"(d[O + 15]),
      "=f"(d[O + 16]), "=f"(d[O + 17]), "=f"(d[O + 18]), "=f"(d[O + 19]), "=f"(d[O + 20]), "=f"(d[O + 21]), "=f"(d[O + 22]), "=f"(d[O + 23]),
      "=f"(d[O + 24]), "=f"(d[O + 25]), "=f"(d[O + 26]), "=f"(d[O + 27]), "=f"(d[O + 28]), "=f"(d[O + 29]), "=f"(d[O + 30]), "=f"(d[O + 31]),
      "=f"(d[O + 32]), "=f"(d[O + 33]), "=f"(d[O + 34]), "=f"(d[O + 35]), "=f"(d[O + 36]), "=f"(d[O + 37]), "=f"(d[O + 38]), "=f"(d[O + 39]),
      "=f"(d[O + 40]), "=f"(d[O + 41]), "=f"(d[O + 42]), "=f"(d[O + 43]), "=f"(d[O + 44]), "=f"(d[O + 45]), "=f"(d[O + 46]), "=f"(d[O + 47]),
      "=f"(d[O + 48]), "=f"(d[O + 49]), "=f"(d[O + 50]), "=f"(d[O + 51]), "=f"(d[O + 52]), "=f"(d[O + 53]), "=f"(d[O + 54]), "=f"(d[O + 55]),
      "=f"(d[O + 56]), "=f"(d[O + 57]), "=f"(d[O + 58]), "=f"(d[O + 59]), "=f"(d[O + 60]), "=f"(d[O + 61]), "=f"(d[O + 62]), "=f"(d[O + 63])
    : "r"(a.x), "r"(a.y), "r"(a.z), "r"(a.w), "l"(db));
}
template <bool INIT, int O, int T> __device__ __forceinline__ void wgmma_n128(float (&d)[T], const uint4& a, uint64_t db) {
  if constexpr (INIT) wgmma_rs_n128_init<O>(d, a, db); else wgmma_rs_n128<O>(d, a, db);
}
template <int O, int T> __device__ __forceinline__ void wgmma_rs_n192(float (&d)[T], const uint4& a, uint64_t db) {
  asm volatile("{\n.reg .pred p;\nsetp.ne.b32 p, 1, 0;\n"
    "wgmma.mma_async.sync.aligned.m64n192k16.f32.bf16.bf16 "
    "{%0, %1, %2, %3, %4, %5, %6, %7, %8, %9, %10, %11, %12, %13, %14, %15, "
    "%16, %17, %18, %19, %20, %21, %22, %23, %24, %25, %26, %27, %28, %29, %30, %31, "
    "%32, %33, %34, %35, %36, %37, %38, %39, %40, %41, %42, %43, %44, %45, %46, %47, "
    "%48, %49, %50, %51, %52, %53, %54, %55, %56, %57, %58, %59, %60, %61, %62, %63, "
    "%64, %65, %66, %67, %68, %69, %70, %71, %72, %73, %74, %75, %76, %77, %78, %79, "
    "%80, %81, %82, %83, %84, %85, %86, %87, %88, %89, %90, %91, %92, %93, %94, %95}, "
    "{%96, %97, %98, %99}, %100, p, 1, 1, 1;\n}\n"
    : "+f"(d[O + 0]), "+f"(d[O + 1]), "+f"(d[O + 2]), "+f"(d[O + 3]), "+f"(d[O + 4]), "+f"(d[O + 5]), "+f"(d[O + 6]), "+f"(d[O + 7]),
      "+f"(d[O + 8]), "+f"(d[O + 9]), "+f"(d[O + 10]), "+f"(d[O + 11]), "+f"(d[O + 12]), "+f"(d[O + 13]), "+f"(d[O + 14]), "+f"(d[O + 15]),
      "+f"(d[O + 16]), "+f"(d[O + 17]), "+f"(d[O + 18]), "+f"(d[O + 19]), "+f"(d[O + 20]), "+f"(d[O + 21]), "+f"(d[O + 22]), "+f"(d[O + 23]),
      "+f"(d[O + 24]), "+f"(d[O + 25]), "+f"(d[O + 26]), "+f"(d[O + 27]), "+f"(d[O + 28]), "+f"(d[O + 29]), "+f"(d[O + 30]), "+f"(d[O + 31]),
      "+f"(d[O + 32]), "+f"(d[O + 33]), "+f"(d[O + 34]), "+f"(d[O + 35]), "+f"(d[O + 36]), "+f"(d[O + 37]), "+f"(d[O + 38]), "+f"(d[O + 39]),
      "+f"(d[O + 40]), "+f"(d[O + 41]), "+f"(d[O + 42]), "+f"(d[O + 43]), "+f"(d[O + 44]), "+f"(d[O + 45]), "+f"(d[O + 46]), "+f"(d[O + 47]),
      "+f"(d[O + 48]), "+f"(d[O + 49]), "+f"(d[O + 50]), "+f"(d[O + 51]), "+f"(d[O + 52]), "+f"(d[O + 53]), "+f"(d[O + 54]), "+f"(d[O + 55]),
      "+f"(d[O + 56]), "+f"(d[O + 57]), "+f"(d[O + 58]), "+f"(d[O + 59]), "+f"(d[O + 60]), "+f"(d[O + 61]), "+f"(d[O + 62]), "+f"(d[O + 63]),
      "+f"(d[O + 64]), "+f"(d[O + 65]), "+f"(d[O + 66]), "+f"(d[O + 67]), "+f"(d[O + 68]), "+f"(d[O + 69]), "+f"(d[O + 70]), "+f"(d[O + 71]),
      "+f"(d[O + 72]), "+f"(d[O + 73]), "+f"(d[O + 74]), "+f"(d[O + 75]), "+f"(d[O + 76]), "+f"(d[O + 77]), "+f"(d[O + 78]), "+f"(d[O + 79]),
      "+f"(d[O + 80]), "+f"(d[O + 81]), "+f"(d[O + 82]), "+f"(d[O + 83]), "+f"(d[O + 84]), "+f"(d[O + 85]), "+f"(d[O + 86]), "+f"(d[O + 87]),
      "+f"(d[O + 88]), "+f"(d[O + 89]), "+f"(d[O + 90]), "+f"(d[O + 91]), "+f"(d[O + 92]), "+f"(d[O + 93]), "+f"(d[O + 94]), "+f"(d[O + 95])
    : "r"(a.x), "r"(a.y), "r"(a.z), "r"(a.w), "l"(db));
}
template <int O, int T> __device__ __forceinline__ void wgmma_rs_n192_init(float (&d)[T], const uint4& a, uint64_t db) {
  asm volatile("{\n.reg .pred p;\nsetp.ne.b32 p, 0, 0;\n"
    "wgmma.mma_async.sync.aligned.m64n192k16.f32.bf16.bf16 "
    "{%0, %1, %2, %3, %4, %5, %6, %7, %8, %9, %10, %11, %12, %13, %14, %15, "
    "%16, %17, %18, %19, %20, %21, %22, %23, %24, %25, %26, %27, %28, %29, %30, %31, "
    "%32, %33, %34, %35, %36, %37, %38, %39, %40, %41, %42, %43, %44, %45, %46, %47, "
    "%48, %49, %50, %51, %52, %53, %54, %55, %56, %57, %58, %59, %60, %61, %62, %63, "
    "%64, %65, %66, %67, %68, %69, %70, %71, %72, %73, %74, %75, %76, %77, %78, %79, "
    "%80, %81, %82, %83, %84, %85, %86, %87, %88, %89, %90, %91, %92, %93, %94, %95}, "
    "{%96, %97, %98, %99}, %100, p, 1, 1, 1;\n}\n"
    : "=f"(d[O + 0]), "=f"(d[O + 1]), "=f"(d[O + 2]), "=f"(d[O + 3]), "=f"(d[O + 4]), "=f"(d[O + 5]), "=f"(d[O + 6]), "=f"(d[O + 7]),
      "=f"(d[O + 8]), "=f"(d[O + 9]), "=f"(d[O + 10]), "=f"(d[O + 11]), "=f"(d[O + 12]), "=f"(d[O + 13]), "=f"(d[O + 14]), "=f"(d[O + 15]),
      "=f"(d[O + 16]), "=f"(d[O + 17]), "=f"(d[O + 18]), "=f"(d[O + 19]), "=f"(d[O + 20]), "=f"(d[O + 21]), "=f"(d[O + 22]), "=f"(d[O + 23]),
      "=f"(d[O + 24]), "=f"(d[O + 25]), "=f"(d[O + 26]), "=f"(d[O + 27]), "=f"(d[O + 28]), "=f"(d[O + 29]), "=f"(d[O + 30]), "=f"(d[O + 31]),
      "=f"(d[O + 32]), "=f"(d[O + 33]), "=f"(d[O + 34]), "=f"(d[O + 35]), "=f"(d[O + 36]), "=f"(d[O + 37]), "=f"(d[O + 38]), "=f"(d[O + 39]),
      "=f"(d[O + 40]), "=f"(d[O + 41]), "=f"(d[O + 42]), "=f"(d[O + 43]), "=f"(d[O + 44]), "=f"(d[O + 45]), "=f"(d[O + 46]), "=f"(d[O + 47]),
      "=f"(d[O + 48]), "=f"(d[O + 49]), "=f"(d[O + 50]), "=f"(d[O + 51]), "=f"(d[O + 52]), "=f"(d[O + 53]), "=f"(d[O + 54]), "=f"(d[O + 55]),
      "=f"(d[O + 56]), "=f"(d[O + 57]), "=f"(d[O + 58]), "=f"(d[O + 59]), "=f"(d[O + 60]), "=f"(d[O + 61]), "=f"(d[O + 62]), "=f"(d[O + 63]),
      "=f"(d[O + 64]), "=f"(d[O + 65]), "=f"(d[O + 66]), "=f"(d[O + 67]), "=f"(d[O + 68]), "=f"(d[O + 69]), "=f"(d[O + 70]), "=f"(d[O + 71]),
      "=f"(d[O + 72]), "=f"(d[O + 73]), "=f"(d[O + 74]), "=f"(d[O + 75]), "=f"(d[O + 76]), "=f"(d[O + 77]), "=f"(d[O + 78]), "=f"(d[O + 79]),
      "=f"(d[O + 80]), "=f"(d[O + 81]), "=f"(d[O + 82]), "=f"(d[O + 83]), "=f"(d[O + 84]), "=f"(d[O + 85]), "=f"(d[O + 86]), "=f"(d[O + 87]),
      "=f"(d[O + 88]), "=f"(d[O + 89]), "=f"(d[O + 90]), "=f"(d[O + 91]), "=f"(d[O + 92]), "=f"(d[O + 93]), "=f"(d[O + 94]), "=f"(d[O + 95])
    : "r"(a.x), "r"(a.y), "r"(a.z), "r"(a.w), "l"(db));
}
template <bool INIT, int O, int T> __device__ __forceinline__ void wgmma_n192(float (&d)[T], const uint4& a, uint64_t db) {
  if constexpr (INIT) wgmma_rs_n192_init<O>(d, a, db); else wgmma_rs_n192<O>(d, a, db);
}
template <int O, int T> __device__ __forceinline__ void wgmma_rs_n256(float (&d)[T], const uint4& a, uint64_t db) {
  asm volatile("{\n.reg .pred p;\nsetp.ne.b32 p, 1, 0;\n"
    "wgmma.mma_async.sync.aligned.m64n256k16.f32.bf16.bf16 "
    "{%0, %1, %2, %3, %4, %5, %6, %7, %8, %9, %10, %11, %12, %13, %14, %15, "
    "%16, %17, %18, %19, %20, %21, %22, %23, %24, %25, %26, %27, %28, %29, %30, %31, "
    "%32, %33, %34, %35, %36, %37, %38, %39, %40, %41, %42, %43, %44, %45, %46, %47, "
    "%48, %49, %50, %51, %52, %53, %54, %55, %56, %57, %58, %59, %60, %61, %62, %63, "
    "%64, %65, %66, %67, %68, %69, %70, %71, %72, %73, %74, %75, %76, %77, %78, %79, "
    "%80, %81, %82, %83, %84, %85, %86, %87, %88, %89, %90, %91, %92, %93, %94, %95, "
    "%96, %97, %98, %99, %100, %101, %102, %103, %104, %105, %106, %107, %108, %109, %110, %111, "
    "%112, %113, %114, %115, %116, %117, %118, %119, %120, %121, %122, %123, %124, %125, %126, %127}, "
    "{%128, %129, %130, %131}, %132, p, 1, 1, 1;\n}\n"
    : "+f"(d[O + 0]), "+f"(d[O + 1]), "+f"(d[O + 2]), "+f"(d[O + 3]), "+f"(d[O + 4]), "+f"(d[O + 5]), "+f"(d[O + 6]), "+f"(d[O + 7]),
      "+f"(d[O + 8]), "+f"(d[O + 9]), "+f"(d[O + 10]), "+f"(d[O + 11]), "+f"(d[O + 12]), "+f"(d[O + 13]), "+f"(d[O + 14]), "+f"(d[O + 15]),
      "+f"(d[O + 16]), "+f"(d[O + 17]), "+f"(d[O + 18]), "+f"(d[O + 19]), "+f"(d[O + 20]), "+f"(d[O + 21]), "+f"(d[O + 22]), "+f"(d[O + 23]),
      "+f"(d[O + 24]), "+f"(d[O + 25]), "+f"(d[O + 26]), "+f"(d[O + 27]), "+f"(d[O + 28]), "+f"(d[O + 29]), "+f"(d[O + 30]), "+f"(d[O + 31]),
      "+f"(d[O + 32]), "+f"(d[O + 33]), "+f"(d[O + 34]), "+f"(d[O + 35]), "+f"(d[O + 36]), "+f"(d[O + 37]), "+f"(d[O + 38]), "+f"(d[O + 39]),
      "+f"(d[O + 40]), "+f"(d[O + 41]), "+f"(d[O + 42]), "+f"(d[O + 43]), "+f"(d[O + 44]), "+f"(d[O + 45]), "+f"(d[O + 46]), "+f"(d[O + 47]),
      "+f"(d[O + 48]), "+f"(d[O + 49]), "+f"(d[O + 50]), "+f"(d[O + 51]), "+f"(d[O + 52]), "+f"(d[O + 53]), "+f"(d[O + 54]), "+f"(d[O + 55]),
      "+f"(d[O + 56]), "+f"(d[O + 57]), "+f"(d[O + 58]), "+f"(d[O + 59]), "+f"(d[O + 60]), "+f"(d[O + 61]), "+f"(d[O + 62]), "+f"(d[O + 63]),
      "+f"(d[O + 64]), "+f"(d[O + 65]), "+f"(d[O + 66]), "+f"(d[O + 67]), "+f"(d[O + 68]), "+f"(d[O + 69]), "+f"(d[O + 70]), "+f"(d[O + 71]),
      "+f"(d[O + 72]), "+f"(d[O + 73]), "+f"(d[O + 74]), "+f"(d[O + 75]), "+f"(d[O + 76]), "+f"(d[O + 77]), "+f"(d[O + 78]), "+f"(d[O + 79]),
      "+f"(d[O + 80]), "+f"(d[O + 81]), "+f"(d[O + 82]), "+f"(d[O + 83]), "+f"(d[O + 84]), "+f"(d[O + 85]), "+f"(d[O + 86]), "+f"(d[O + 87]),
      "+f"(d[O + 88]), "+f"(d[O + 89]), "+f"(d[O + 90]), "+f"(d[O + 91]), "+f"(d[O + 92]), "+f"(d[O + 93]), "+f"(d[O + 94]), "+f"(d[O + 95]),
      "+f"(d[O + 96]), "+f"(d[O + 97]), "+f"(d[O + 98]), "+f"(d[O + 99]), "+f"(d[O + 100]), "+f"(d[O + 101]), "+f"(d[O + 102]), "+f"(d[O + 103]),
      "+f"(d[O + 104]), "+f"(d[O + 105]), "+f"(d[O + 106]), "+f"(d[O + 107]), "+f"(d[O + 108]), "+f"(d[O + 109]), "+f"(d[O + 110]), "+f"(d[O + 111]),
      "+f"(d[O + 112]), "+f"(d[O + 113]), "+f"(d[O + 114]), "+f"(d[O + 115]), "+f"(d[O + 116]), "+f"(d[O + 117]), "+f"(d[O + 118]), "+f"(d[O + 119]),
      "+f"(d[O + 120]), "+f"(d[O + 121]), "+f"(d[O + 122]), "+f"(d[O + 123]), "+f"(d[O + 124]), "+f"(d[O + 125]), "+f"(d[O + 126]), "+f"(d[O + 127])
    : "r"(a.x), "r"(a.y), "r"(a.z), "r"(a.w), "l"(db));
}
template <int O, int T> __device__ __forceinline__ void wgmma_rs_n256_init(float (&d)[T], const uint4& a, uint64_t db) {
  asm volatile("{\n.reg .pred p;\nsetp.ne.b32 p, 0, 0;\n"
    "wgmma.mma_async.sync.aligned.m64n256k16.f32.bf16.bf16 "
    "{%0, %1, %2, %3, %4, %5, %6, %7, %8, %9, %10, %11, %12, %13, %14, %15, "
    "%16, %17, %18, %19, %20, %21, %22, %23, %24, %25, %26, %27, %28, %29, %30, %31, "
    "%32, %33, %34, %35, %36, %37, %38, %39, %40, %41, %42, %43, %44, %45, %46, %47, "
    "%48, %49, %50, %51, %52, %53, %54, %55, %56, %57, %58, %59, %60, %61, %62, %63, "
    "%64, %65, %66, %67, %68, %69, %70, %71, %72, %73, %74, %75, %76, %77, %78, %79, "
    "%80, %81, %82, %83, %84, %85, %86, %87, %88, %89, %90, %91, %92, %93, %94, %95, "
    "%96, %97, %98, %99, %100, %101, %102, %103, %104, %105, %106, %107, %108, %109, %110, %111, "
    "%112, %113, %114, %115, %116, %117, %118, %119, %120, %121, %122, %123, %124, %125, %126, %127}, "
    "{%128, %129, %130, %131}, %132, p, 1, 1, 1;\n}\n"
    : "=f"(d[O + 0]), "=f"(d[O + 1]), "=f"(d[O + 2]), "=f"(d[O + 3]), "=f"(d[O + 4]), "=f"(d[O + 5]), "=f"(d[O + 6]), "=f"(d[O + 7]),
      "=f"(d[O + 8]), "=f"(d[O + 9]), "=f"(d[O + 10]), "=f"(d[O + 11]), "=f"(d[O + 12]), "=f"(d[O + 13]), "=f"(d[O + 14]), "=f"(d[O + 15]),
      "=f"(d[O + 16]), "=f"(d[O + 17]), "=f"(d[O + 18]), "=f"(d[O + 19]), "=f"(d[O + 20]), "=f"(d[O + 21]), "=f"(d[O + 22]), "=f"(d[O + 23]),
      "=f"(d[O + 24]), "=f"(d[O + 25]), "=f"(d[O + 26]), "=f"(d[O + 27]), "=f"(d[O + 28]), "=f"(d[O + 29]), "=f"(d[O + 30]), "=f"(d[O + 31]),
      "=f"(d[O + 32]), "=f"(d[O + 33]), "=f"(d[O + 34]), "=f"(d[O + 35]), "=f"(d[O + 36]), "=f"(d[O + 37]), "=f"(d[O + 38]), "=f"(d[O + 39]),
      "=f"(d[O + 40]), "=f"(d[O + 41]), "=f"(d[O + 42]), "=f"(d[O + 43]), "=f"(d[O + 44]), "=f"(d[O + 45]), "=f"(d[O + 46]), "=f"(d[O + 47]),
      "=f"(d[O + 48]), "=f"(d[O + 49]), "=f"(d[O + 50]), "=f"(d[O + 51]), "=f"(d[O + 52]), "=f"(d[O + 53]), "=f"(d[O + 54]), "=f"(d[O + 55]),
      "=f"(d[O + 56]), "=f"(d[O + 57]), "=f"(d[O + 58]), "=f"(d[O + 59]), "=f"(d[O + 60]), "=f"(d[O + 61]), "=f"(d[O + 62]), "=f"(d[O + 63]),
      "=f"(d[O + 64]), "=f"(d[O + 65]), "=f"(d[O + 66]), "=f"(d[O + 67]), "=f"(d[O + 68]), "=f"(d[O + 69]), "=f"(d[O + 70]), "=f"(d[O + 71]),
      "=f"(d[O + 72]), "=f"(d[O + 73]), "=f"(d[O + 74]), "=f"(d[O + 75]), "=f"(d[O + 76]), "=f"(d[O + 77]), "=f"(d[O + 78]), "=f"(d[O + 79]),
      "=f"(d[O + 80]), "=f"(d[O + 81]), "=f"(d[O + 82]), "=f"(d[O + 83]), "=f"(d[O + 84]), "=f"(d[O + 85]), "=f"(d[O + 86]), "=f"(d[O + 87]),
      "=f"(d[O + 88]), "=f"(d[O + 89]), "=f"(d[O + 90]), "=f"(d[O + 91]), "=f"(d[O + 92]), "=f"(d[O + 93]), "=f"(d[O + 94]), "=f"(d[O + 95]),
      "=f"(d[O + 96]), "=f"(d[O + 97]), "=f"(d[O + 98]), "=f"(d[O + 99]), "=f"(d[O + 100]), "=f"(d[O + 101]), "=f"(d[O + 102]), "=f"(d[O + 103]),
      "=f"(d[O + 104]), "=f"(d[O + 105]), "=f"(d[O + 106]), "=f"(d[O + 107]), "=f"(d[O + 108]), "=f"(d[O + 109]), "=f"(d[O + 110]), "=f"(d[O + 111]),
      "=f"(d[O + 112]), "=f"(d[O + 113]), "=f"(d[O + 114]), "=f"(d[O + 115]), "=f"(d[O + 116]), "=f"(d[O + 117]), "=f"(d[O + 118]), "=f"(d[O + 119]),
      "=f"(d[O + 120]), "=f"(d[O + 121]), "=f"(d[O + 122]), "=f"(d[O + 123]), "=f"(d[O + 124]), "=f"(d[O + 125]), "=f"(d[O + 126]), "=f"(d[O + 127])
    : "r"(a.x), "r"(a.y), "r"(a.z), "r"(a.w), "l"(db));
}
template <bool INIT, int O, int T> __device__ __forceinline__ void wgmma_n256(float (&d)[T], const uint4& a, uint64_t db) {
  if constexpr (INIT) wgmma_rs_n256_init<O>(d, a, db); else wgmma_rs_n256<O>(d, a, db);
}


template <int N> __device__ __forceinline__ void load_pk(uint4* a, const uint4* p) {
#pragma unroll
  for (int i = 0; i < N; i++) a[i] = ld_ll(p + i * 32);
}
__device__ __forceinline__ uint32_t xor_or(uint32_t a, uint32_t b, uint32_t t) {
  uint32_t r;
  asm("lop3.b32 %0, %1, %2, %3, 0x7E;" : "=r"(r) : "r"(a), "r"(b), "r"(t));
  return r;
}
template <int N> __device__ __forceinline__ bool ok_pk(const uint4* a, uint32_t tag) {
  static_assert(N % 2 == 0, "");
  uint32_t x = xor_or(a[0].x, a[1].x, tag);
#pragma unroll
  for (int i = 2; i < N; i += 2) x |= xor_or(a[i].x, a[i + 1].x, tag);
  return __all_sync(0xffffffffu, (x & 1u) == 0u);
}
template <int N> __device__ __forceinline__ void ensure_pk(uint4* a, const uint4* p, uint32_t tag) {
  if (ok_pk<N>(a, tag)) return;
  uint32_t n = 0;
  do { load_pk<N>(a, p); } while (!ok_pk<N>(a, tag) && ++n < SPIN_LIMIT);
}

constexpr int NSTAGE = 52;
constexpr int ST_WO = 8, ST_G1 = 12, ST_G2 = 28, ST_DN = 36;
__host__ __device__ constexpr int st_len(int s) { return s < ST_WO ? 3 : s < ST_G2 ? 2 : s < ST_DN ? 3 : 2; }
__host__ __device__ constexpr int st_g0(int s) {
  int pos = 0, g0 = 0;
  for (int i = 0; i <= s; i++) {
    if (pos + st_len(i) > NGRAN) pos = 0;
    g0 = pos;
    pos += st_len(i);
  }
  return g0;
}
__host__ __device__ constexpr int cnt_first(int g, int s) {
  int n = 0;
  for (int i = 0; i < s; i++) n += (st_g0(i) == g);
  return n;
}
__host__ __device__ constexpr int cnt_cover(int g, int s) {
  int n = 0;
  for (int i = 0; i < s; i++) n += (g >= st_g0(i) && g < st_g0(i) + st_len(i));
  return n;
}
__host__ __device__ constexpr uint32_t flip_mask(int s0, int s1) {
  uint32_t m = 0;
  for (int i = s0; i < s1; i++) m ^= ((1u << st_len(i)) - 1u) << st_g0(i);
  return m;
}
__host__ __device__ constexpr int dn_q(int i) { return i < 3 ? 0 : i < 6 ? 1 : i == 6 ? 0 : i == 7 ? 1 : i < 12 ? 2 : 3; }
__host__ __device__ constexpr int dn_par(int i) { return i < 8 ? (i == 2 || i == 4 || i >= 6) : (i & 1); }
__host__ __device__ constexpr int dn_kh(int i) { return i < 8 ? (i == 1 || i >= 5) : ((i & 3) >= 2); }
template <int I> struct IC { static constexpr int value = I; };
template <int B, int E, typename F> __device__ __forceinline__ void static_for(F&& f) {
  if constexpr (B < E) { f(IC<B>{}); static_for<B + 1, E>(f); }
}
template <int S> __device__ __forceinline__ void cons_acquire(uint32_t sbase, uint32_t L) {
  constexpr int g0 = st_g0(S);
  constexpr uint32_t p0 = cnt_first(g0, S) & 1, odd = cnt_first(g0, NSTAGE) & 1;
  mbar_wait(sbase + SM_MISC + BAR_FULL + 8 * g0, p0 ^ (L & odd));
}
template <int S> __device__ __forceinline__ void cons_release(uint32_t sbase, int lane) {
  if (lane < st_len(S)) mbar_arrive(sbase + SM_MISC + BAR_EMPTY + 8 * st_g0(S) + 8 * lane);
}
__device__ __forceinline__ bool elect_one() {
  uint32_t p;
  asm volatile("{\n.reg .pred P;\nelect.sync _|P, 0xffffffff;\nselp.u32 %0, 1, 0, P;\n}" : "=r"(p));
  return p != 0;
}
struct ProdRing { uint32_t pos, par; };
template <int N> __device__ __forceinline__ uint32_t prod_acquire(uint32_t sbase, ProdRing& r) {
  if (r.pos + N > NGRAN) r.pos = 0;
  const uint32_t g0 = r.pos;
#pragma unroll
  for (uint32_t i = 0; i < N; i++) mbar_wait(sbase + SM_MISC + BAR_EMPTY + 8 * (g0 + i), ((r.par >> (g0 + i)) & 1u) ^ 1u);
  r.par ^= ((1u << N) - 1u) << g0;
  r.pos = g0 + N;
  return g0;
}
template <int S> __device__ __forceinline__ void prod_acquire_static(uint32_t sbase, uint32_t L) {
  constexpr int g0 = st_g0(S);
  static_for<0, st_len(S)>([&](auto I) {
    constexpr int g = g0 + I.value;
    constexpr uint32_t p0 = cnt_cover(g, S) & 1, odd = cnt_cover(g, NSTAGE) & 1;
    mbar_wait(sbase + SM_MISC + BAR_EMPTY + 8 * g, p0 ^ (L & odd) ^ 1u);
  });
}
template <int S, int KSTEP_BYTES, int LBO, int SBO, int SWZ> __device__ __forceinline__ constexpr uint64_t st_desc(int k) {
  return (uint64_t)((SMEM_ORIGIN + st_g0(S) * GRAN + k * KSTEP_BYTES) >> 4) | ((uint64_t)(LBO >> 4) << 16) |
         ((uint64_t)(SBO >> 4) << 32) | ((uint64_t)SWZ << 62);
}

__device__ __forceinline__ void combine_stats(const uint4& p0, const uint4& p1, float& mean_lo, float& rstd_lo, float& mean_hi, float& rstd_hi) {
  float m0 = __uint_as_float(p0.x), q0 = __uint_as_float(p0.y), m0h = __uint_as_float(p0.z), q0h = __uint_as_float(p0.w);
  float m1 = __uint_as_float(p1.x), q1 = __uint_as_float(p1.y), m1h = __uint_as_float(p1.z), q1h = __uint_as_float(p1.w);
  float s = m0 + m1, sh = m0h + m1h;
  s += __shfl_xor_sync(0xffffffffu, s, 1); sh += __shfl_xor_sync(0xffffffffu, sh, 1);
  s += __shfl_xor_sync(0xffffffffu, s, 2); sh += __shfl_xor_sync(0xffffffffu, sh, 2);
  mean_lo = s * 0.125f; mean_hi = sh * 0.125f;
  float d0 = m0 - mean_lo, d1 = m1 - mean_lo, d0h = m0h - mean_hi, d1h = m1h - mean_hi;
  float t = q0 + q1 + 64.f * (d0 * d0 + d1 * d1), th = q0h + q1h + 64.f * (d0h * d0h + d1h * d1h);
  t += __shfl_xor_sync(0xffffffffu, t, 1); th += __shfl_xor_sync(0xffffffffu, th, 1);
  t += __shfl_xor_sync(0xffffffffu, t, 2); th += __shfl_xor_sync(0xffffffffu, th, 2);
  rstd_lo = rsqrtf(t * (1.f / 512.f) + 1e-5f);
  rstd_hi = rsqrtf(th * (1.f / 512.f) + 1e-5f);
}
__device__ __forceinline__ uint4 local_stats(const float (&v)[32]) {
  float s = 0.f, sh = 0.f;
#pragma unroll
  for (int i = 0; i < 4; i++) {
    s += (v[8 * i + 0] + v[8 * i + 1]) + (v[8 * i + 4] + v[8 * i + 5]);
    sh += (v[8 * i + 2] + v[8 * i + 3]) + (v[8 * i + 6] + v[8 * i + 7]);
  }
  s += __shfl_xor_sync(0xffffffffu, s, 1); sh += __shfl_xor_sync(0xffffffffu, sh, 1);
  s += __shfl_xor_sync(0xffffffffu, s, 2); sh += __shfl_xor_sync(0xffffffffu, sh, 2);
  float m = s * (1.f / 64.f), mh = sh * (1.f / 64.f);
  float q = 0.f, qh = 0.f;
#pragma unroll
  for (int i = 0; i < 4; i++) {
    float a = v[8 * i + 0] - m, b = v[8 * i + 1] - m, c = v[8 * i + 4] - m, d = v[8 * i + 5] - m;
    q += (a * a + b * b) + (c * c + d * d);
    float e = v[8 * i + 2] - mh, f = v[8 * i + 3] - mh, g = v[8 * i + 6] - mh, h = v[8 * i + 7] - mh;
    qh += (e * e + f * f) + (g * g + h * h);
  }
  q += __shfl_xor_sync(0xffffffffu, q, 1); qh += __shfl_xor_sync(0xffffffffu, qh, 1);
  q += __shfl_xor_sync(0xffffffffu, q, 2); qh += __shfl_xor_sync(0xffffffffu, qh, 2);
  return make_uint4(__float_as_uint(m), __float_as_uint(q), __float_as_uint(mh), __float_as_uint(qh));
}


__device__ __forceinline__ int slab_row0(int c, int g, int w) { return 1024 * g + 64 * c + 32 * (w >> 1) + (w & 1); }

__device__ __forceinline__ void owner_ln_publish(uint32_t sbase, const float (&v)[32], uint32_t tphase, uint32_t tag_xn, uint4 (&xraw)[4]) {
  PHASE_VARS;
  uint4 st = local_stats(v);
  if (qc == 0) sts128(sbase + SM_TSTAT + warp * 128 + qr * 16, st);
  uint4* xn = g_arena + c * ARENA + AR_XN + (j * 32 + 16 * g + w) * 32 + lane;
  asm volatile("bar.sync 3, 256;" ::: "memory");
  const uint32_t rd = sbase + SM_TSTAT + qc * 256 + qr * 16;
  uint4 p0 = lds128(rd), p1 = lds128(rd + 128);
  float ml, rl, mh, rh;
  combine_stats(p0, p1, ml, rl, mh, rh);
  const float bl = -ml * rl, bh = -mh * rh;
#pragma unroll
  for (int i = 0; i < 4; i++) {
    uint4 o;
    o.x = set_tag(pack2(fmaf(v[8 * i + 0], rl, bl), fmaf(v[8 * i + 1], rl, bl)), tag_xn);
    o.y = pack2(fmaf(v[8 * i + 2], rh, bh), fmaf(v[8 * i + 3], rh, bh));
    o.z = pack2(fmaf(v[8 * i + 4], rl, bl), fmaf(v[8 * i + 5], rl, bl));
    o.w = pack2(fmaf(v[8 * i + 6], rh, bh), fmaf(v[8 * i + 7], rh, bh));
    st_ll(xn + i * 128, o);
  }
#pragma unroll
  for (int i = 0; i < 4; i++) {
    xraw[i].x = set_tag(pack2(v[8 * i + 0], v[8 * i + 1]), 1u);
    xraw[i].y = pack2(v[8 * i + 2], v[8 * i + 3]);
    xraw[i].z = pack2(v[8 * i + 4], v[8 * i + 5]);
    xraw[i].w = pack2(v[8 * i + 6], v[8 * i + 7]);
  }
}

__device__ __forceinline__ uint4 pack8(const float* a) {
  return make_uint4(pack2(a[0], a[1]), pack2(a[2], a[3]), pack2(a[4], a[5]), pack2(a[6], a[7]));
}
template <int U> __device__ __forceinline__ uint4 glu8(const float* g, float cl, float ch) {
  return make_uint4(pack2(g[0] * cl * g[U], g[1] * cl * g[U + 1]), pack2(g[2] * ch * g[U + 2], g[3] * ch * g[U + 3]),
                    pack2(g[4] * cl * g[U + 4], g[5] * cl * g[U + 5]), pack2(g[6] * ch * g[U + 6], g[7] * ch * g[U + 7]));
}
__device__ __forceinline__ uint32_t hfma2(uint32_t a, uint32_t b, uint32_t c) {
  uint32_t d;
  asm("fma.rn.bf16x2 %0, %1, %2, %3;" : "=r"(d) : "r"(a), "r"(b), "r"(c));
  return d;
}
__device__ __forceinline__ void keep4(const uint4 (&a)[4]) { keep(a[0]); keep(a[1]); keep(a[2]); keep(a[3]); }

__global__ void __launch_bounds__(NTHREADS, 1)
fused_kernel(const __grid_constant__ CUtensorMap m_qkv, const __grid_constant__ CUtensorMap m_wo,
             const __grid_constant__ CUtensorMap m_gu2, const __grid_constant__ CUtensorMap m_gu1,
             const __grid_constant__ CUtensorMap m_guh, const __grid_constant__ CUtensorMap m_wd112,
             const __grid_constant__ CUtensorMap m_wd80, const __grid_constant__ CUtensorMap m_wd32,
             const __nv_bfloat16* __restrict__ x_in,
             __nv_bfloat16* __restrict__ out
) {
  extern __shared__ __align__(1024) unsigned char smem_raw[];
  const uint32_t sbase = smem_u32(smem_raw);
  const uint32_t bars = sbase + SM_MISC;
  if ((sbase & 0xFFFFFFu) != SMEM_ORIGIN) return;

  uint4 xw[4];
  if (threadIdx.x < 256) {
    const int cc = blockIdx.x >> 3, jj = blockIdx.x & 7, ln = threadIdx.x & 31, wp = threadIdx.x >> 5;
    const uint4* xp = reinterpret_cast<const uint4*>(x_in + (size_t)(slab_row0(cc, jj >> 2, jj & 3) + 2 * (ln >> 1)) * 512 + (16 * (wp >> 2) + (wp & 3)) * 16 + (ln & 1) * 8);
#pragma unroll
    for (int i = 0; i < 4; i++) xw[i] = __ldg(xp + i * 8);
  } else if (threadIdx.x == 256) {
    for (int i = 0; i < NGRAN; i++) { mbar_init(bars + BAR_FULL + 8 * i, 1); mbar_init(bars + BAR_EMPTY + 8 * i, 8); }
    for (int i = 0; i < 4; i++) mbar_init(bars + BAR_HRECV + 8 * i, 1);
    for (int i = 0; i < 2; i++) mbar_init(bars + BAR_HREADY + 8 * i, 4);
    asm volatile("fence.mbarrier_init.release.cluster;" ::: "memory");
  }
  __syncthreads();
  asm volatile("barrier.cluster.arrive.relaxed.aligned;" ::: "memory");

  if (threadIdx.x >= 256) {
    asm volatile("setmaxnreg.dec.sync.aligned.u32 40;");
    const int warp = threadIdx.x >> 5;
    const int j = blockIdx.x & 7, b = j & 1;
    if (warp == 8) {
      ProdRing r{0u, 0u};
      const int cb0 = 224 * j + 32 * b, hb0 = 224 * j + 192 * (b ^ 1);
      const int jp = j ^ 1, cbp = 224 * jp + 32 * (b ^ 1), hbp = 224 * jp + 192 * b;
#pragma unroll 1
      for (uint32_t L = 0; L < 2; L++) {
        r.pos = 0;
constexpr uint32_t D_NEXT = 3500;
        if (D_NEXT > 0 && L == 1) spin_for(D_NEXT);
#pragma unroll 1
        for (int kb = 0; kb < 8; kb++) {
          const uint32_t g0 = prod_acquire<3>(sbase, r);
          if (elect_one()) {
            mbar_expect_tx(bars + BAR_FULL + 8 * g0, 24576);
            tma_3d(sbase + g0 * GRAN, &m_qkv, bars + BAR_FULL + 8 * g0, 64 * j, 64 * kb, 0);
          }
        }
#pragma unroll 1
        for (int i = 0; i < 4; i++) {
          const uint32_t g0 = prod_acquire<2>(sbase, r);
          if (elect_one()) {
            mbar_expect_tx(bars + BAR_FULL + 8 * g0, 16384);
            tma_2d(sbase + g0 * GRAN, &m_wo, bars + BAR_FULL + 8 * g0, 64 * j, 128 * i);
          }
        }
#pragma unroll 1
        for (int hb = 0; hb < 16; hb++) {
          const uint32_t g0 = prod_acquire<2>(sbase, r);
          if (elect_one()) {
            mbar_expect_tx(bars + BAR_FULL + 8 * g0, 16384);
            tma_4d(sbase + g0 * GRAN, &m_gu2, bars + BAR_FULL + 8 * g0, cb0, 64 * ((j + (hb >> 1)) & 7) + 32 * (hb & 1), 0, 0);
          }
        }
#pragma unroll 1
        for (int kb = 0; kb < 8; kb++) {
          const uint32_t g0 = prod_acquire<3>(sbase, r);
          if (elect_one()) {
            mbar_expect_tx(bars + BAR_FULL + 8 * g0, 24576);
            tma_4d(sbase + g0 * GRAN, &m_gu1, bars + BAR_FULL + 8 * g0, cb0 + 128, 64 * ((j + kb) & 7), 0, 0);
            tma_3d(sbase + g0 * GRAN + 16384, &m_guh, bars + BAR_FULL + 8 * g0, hb0, 64 * ((j + kb) & 7), 0);
          }
        }
        static_for<0, 16>([&](auto I) {
          constexpr int i = I.value, g0 = st_g0(ST_DN + i);
          prod_acquire_static<ST_DN + i>(sbase, L);
          if (elect_one()) {
            const uint32_t dst = sbase + g0 * GRAN, fb = bars + BAR_FULL + 8 * g0;
            const int n0 = 256 * b + 64 * dn_q(i);
            mbar_expect_tx(fb, 14336);
            if constexpr (dn_kh(i) == 0) {
              tma_2d(dst, &m_wd112, fb, n0, dn_par(i) ? cbp : cb0);
            } else {
              tma_2d(dst, &m_wd80, fb, n0, (dn_par(i) ? cbp : cb0) + 112);
              tma_2d(dst + 10240, &m_wd32, fb, n0, dn_par(i) ? hbp : hb0);
            }
          }
        });
        r.par ^= flip_mask(ST_DN, NSTAGE);
      }
    }
    __syncwarp();
    asm volatile("barrier.cluster.wait.acquire.aligned; // producer" ::: "memory");
  } else {
    asm volatile("setmaxnreg.inc.sync.aligned.u32 232;");

    float vres[32];
    {
      PHASE_VARS;
      const uint32_t tr = areg + w * 512 + ((lane & 7) + 8 * ((lane >> 3) & 1)) * 32 + (lane >> 4) * 16;
#pragma unroll
      for (int i = 0; i < 4; i++) sts128(areg + t128 * 16 + i * 2048, xw[i]);
      __syncwarp();
#pragma unroll
      for (int i = 0; i < 4; i++) {
        uint4 f;
        asm volatile("ldmatrix.sync.aligned.m8n8.x4.shared.b16 {%0,%1,%2,%3}, [%4];" : "=r"(f.x), "=r"(f.y), "=r"(f.z), "=r"(f.w) : "r"(tr + i * 2048) : "memory");
        vres[8 * i + 0] = bf_lo(f.x); vres[8 * i + 1] = bf_hi(f.x); vres[8 * i + 2] = bf_lo(f.y); vres[8 * i + 3] = bf_hi(f.y);
        vres[8 * i + 4] = bf_lo(f.z); vres[8 * i + 5] = bf_hi(f.z); vres[8 * i + 6] = bf_lo(f.w); vres[8 * i + 7] = bf_hi(f.w);
      }
    }

#pragma unroll 1
    for (uint32_t L = 0; L < 2; L++) {
      const uint32_t tag = L ^ 1;
      uint4 xraw[4];
      owner_ln_publish(sbase, vres, L, tag, xraw);
      if (L == 0) asm volatile("barrier.cluster.wait.acquire.aligned; // consumer" ::: "memory");
      {
        PHASE_VARS;
        uint4 qf[4], kf[4], vf[4], pp[4];
        const int blk = 16 * g + c;
        const int pb = blk > 0 ? blk - 1 : 0;
        const uint4* halo_src = g_arena + (pb & 15) * ARENA + AR_HALO + (((((L * 2 + (pb >> 4)) * 8 + j) * 2 + (w & 1)) * 4) * 32) + lane;
        {
          float acc[96];
          uint4 A[3][4];
          const uint4* xs = g_arena + c * ARENA + AR_XN + ((slab) * 32) * 32 + lane;
          bar_wg(1 + g);
          spin_for(L ? D_XN1 : D_XN0);
          load_pk<4>(A[0], xs);
          ensure_pk<4>(A[0], xs, tag);
          load_pk<4>(A[1], xs + 128);
          static_for<0, 8>([&](auto I) {
            constexpr int kb = I.value;
            cons_acquire<kb>(sbase, L);
            wg_fence();
            static_for<0, 4>([&](auto K) { constexpr int k = K.value; wgmma_n192<kb == 0 && k == 0, 0>(acc, A[kb % 3][k], st_desc<kb, 2048, 8192, 1024, 1>(k)); });
            wg_commit();
            if constexpr (kb > 0) {
              wg_wait<1>();
              keep4(A[(kb + 2) % 3]);
              cons_release<kb - 1>(sbase, lane);
            }
            if constexpr (kb + 1 < 8) ensure_pk<4>(A[(kb + 1) % 3], xs + (kb + 1) * 128, tag);
            if constexpr (kb + 2 < 8) load_pk<4>(A[(kb + 2) % 3], xs + (kb + 2) * 128);
            if constexpr (kb == 2) {
              uint4* xr = g_arena + c * ARENA + AR_XRAW + (j * 32 + 16 * g + w) * 32 + lane;
#pragma unroll
              for (int i = 0; i < 4; i++) st_ll(xr + i * 128, xraw[i]);
            }
          });
          wg_wait<0>();
          fence_acc(acc);
          keep4(A[1]);
          cons_release<7>(sbase, lane);
#pragma unroll
          for (int h = 0; h < 4; h++) {
            kf[h].y = pack2(acc[32 + 8 * h + 2], acc[32 + 8 * h + 3]); kf[h].w = pack2(acc[32 + 8 * h + 6], acc[32 + 8 * h + 7]);
            vf[h].y = movm(pack2(acc[64 + 8 * h + 2], acc[64 + 8 * h + 3])); vf[h].w = movm(pack2(acc[64 + 8 * h + 6], acc[64 + 8 * h + 7]));
            pp[h] = make_uint4(kf[h].y, kf[h].w, vf[h].y, vf[h].w);
          }
          if (w >= 2 && blk < 31) {
            uint4* hd = g_arena + c * ARENA + AR_HALO + (((((L * 2 + g) * 8 + j) * 2 + (w & 1)) * 4) * 32) + lane;
#pragma unroll
            for (int h = 0; h < 4; h++) { uint4 t = pp[h]; t.x |= 1u; st_ll(hd + h * 32, t); }
          }
#pragma unroll
          for (int h = 0; h < 4; h++) sts128(areg + (28 + h) * 2048 + t128 * 16, pp[h]);
#pragma unroll
          for (int h = 0; h < 4; h++) {
            kf[h].x = pack2(acc[32 + 8 * h], acc[32 + 8 * h + 1]); kf[h].z = pack2(acc[32 + 8 * h + 4], acc[32 + 8 * h + 5]);
            vf[h].x = movm(pack2(acc[64 + 8 * h], acc[64 + 8 * h + 1])); vf[h].z = movm(pack2(acc[64 + 8 * h + 4], acc[64 + 8 * h + 5]));
          }
#pragma unroll
          for (int h = 0; h < 4; h++) qf[h] = pack8(&acc[8 * h]);
        }
        bar_wg(1 + g);
        const bool first = (w < 2) && (blk == 0);
        if (w >= 2) {
#pragma unroll
          for (int h = 0; h < 4; h++) pp[h] = lds128(areg + (28 + h) * 2048 + (t128 - 64) * 16);
        }
        bar_wg(1 + g);
        if (w < 2 && blk > 0) {
          spin_for(L ? D_HALO1 : D_HALO0);
          load_pk<4>(pp, halo_src);
          ensure_pk<4>(pp, halo_src, 1u);
          uint4* hz = const_cast<uint4*>(halo_src);
#pragma unroll
          for (int h = 0; h < 4; h++) st_ll(hz + h * 32, make_uint4(0, 0, 0, 0));
        }
        const bool n0 = 2 * qc <= qr, n1 = 2 * qc + 1 <= qr;
        const uint32_t msk = (n0 ? 0xffffu : 0u) | (n1 ? 0xffff0000u : 0u);
        const float sc = 0.25f * 1.4426950408889634f;
        const float NEG = -1e30f;
        uint4* od = g_arena + c * ARENA + AR_O + ((slab) * 32 + 4 * j) * 32 + lane;
        float l0[4], l1[4], h0[4], h1[4], ml[4], mh[4];
#pragma unroll
        for (int h = 0; h < 4; h++) {
          float sp[4], s0[4], s1[4];
          mma16816_z(sp, qf[h], pp[h].x, pp[h].y);
          mma16816_z(s0, qf[h], kf[h].x, kf[h].z);
          mma16816_z(s1, qf[h], kf[h].y, kf[h].w);
          if (first) { sp[0] = NEG; sp[1] = NEG; }
          l0[h] = n0 ? s0[0] : sp[0]; l1[h] = n1 ? s0[1] : sp[1];
          h0[h] = n0 ? s1[2] : s0[2]; h1[h] = n1 ? s1[3] : s0[3];
          ml[h] = fmaxf(l0[h], l1[h]); mh[h] = fmaxf(h0[h], h1[h]);
        }
#pragma unroll
        for (int h = 0; h < 4; h++) { ml[h] = fmaxf(ml[h], __shfl_xor_sync(0xffffffffu, ml[h], 1)); mh[h] = fmaxf(mh[h], __shfl_xor_sync(0xffffffffu, mh[h], 1)); }
#pragma unroll
        for (int h = 0; h < 4; h++) { ml[h] = fmaxf(ml[h], __shfl_xor_sync(0xffffffffu, ml[h], 2)); mh[h] = fmaxf(mh[h], __shfl_xor_sync(0xffffffffu, mh[h], 2)); }
        float sl[4], sh[4];
#pragma unroll
        for (int h = 0; h < 4; h++) {
          const float bl = -ml[h] * sc, bh = -mh[h] * sc;
          l0[h] = ex2(fmaf(l0[h], sc, bl)); l1[h] = ex2(fmaf(l1[h], sc, bl));
          h0[h] = ex2(fmaf(h0[h], sc, bh)); h1[h] = ex2(fmaf(h1[h], sc, bh));
          sl[h] = l0[h] + l1[h]; sh[h] = h0[h] + h1[h];
        }
#pragma unroll
        for (int h = 0; h < 4; h++) { sl[h] += __shfl_xor_sync(0xffffffffu, sl[h], 1); sh[h] += __shfl_xor_sync(0xffffffffu, sh[h], 1); }
#pragma unroll
        for (int h = 0; h < 4; h++) { sl[h] += __shfl_xor_sync(0xffffffffu, sl[h], 2); sh[h] += __shfl_xor_sync(0xffffffffu, sh[h], 2); }
#pragma unroll
        for (int h = 0; h < 4; h++) {
          const float il = rcp(sl[h]), ih = rcp(sh[h]);
          const uint32_t pl = pack2(l0[h] * il, l1[h] * il), ph = pack2(h0[h] * ih, h1[h] * ih);
          const uint4 P = make_uint4(pl & msk, ph & ~msk, 0u, ph & msk);
          float o0[4], o1[4];
          mma16816_z(o0, P, vf[h].x, vf[h].y);
          mma16816_z(o1, P, vf[h].z, vf[h].w);
          mma1688(o0, pl & ~msk, 0u, pp[h].z);
          mma1688(o1, pl & ~msk, 0u, pp[h].w);
          st_ll(od + h * 32, make_uint4(pack2(o0[0], o0[1]) | 1u, pack2(o0[2], o0[3]), pack2(o1[0], o1[1]), pack2(o1[2], o1[3])));
        }
      }
      uint4 x1own[4];
      {
        PHASE_VARS;
        float acc[32];
        uint4 A[32], xr[4];
        const uint4* os = g_arena + c * ARENA + AR_O + ((slab) * 32) * 32 + lane;
        uint4* xp = g_arena + c * ARENA + AR_XRAW + ((slab) * 32 + 4 * j) * 32 + lane;
        load_pk<4>(xr, xp);
        spin_for(L ? D_O1 : D_O0);
        load_pk<4>(A, os);
        ensure_pk<4>(A, os, 1u);
        load_pk<28>(A + 4, os + 128);
        static_for<0, 8>([&](auto I) {
          constexpr int kb = I.value;
          if constexpr ((kb & 1) == 0) cons_acquire<ST_WO + kb / 2>(sbase, L);
          if constexpr (kb > 0) ensure_pk<4>(A + 4 * kb, os + kb * 128, 1u);
          wg_fence();
          static_for<0, 4>([&](auto K) {
            constexpr int k = K.value;
            wgmma_n64<kb == 0 && k == 0, 0>(acc, A[4 * kb + k], st_desc<ST_WO + kb / 2, 2048, 8192, 1024, 1>(4 * (kb & 1) + k));
          });
          wg_commit();
          if constexpr ((kb & 1) == 0 && kb > 0) { wg_wait<1>(); cons_release<ST_WO + kb / 2 - 1>(sbase, lane); }
        });
        wg_wait<0>();
        fence_acc(acc);
#pragma unroll
        for (int k = 0; k < 32; k++) keep(A[k]);
        cons_release<ST_WO + 3>(sbase, lane);
        ensure_pk<4>(xr, xp, 1u);
#pragma unroll
        for (int i = 0; i < 4; i++) {
          acc[8 * i + 0] += bf_lo(xr[i].x); acc[8 * i + 1] += bf_hi(xr[i].x); acc[8 * i + 2] += bf_lo(xr[i].y); acc[8 * i + 3] += bf_hi(xr[i].y);
          acc[8 * i + 4] += bf_lo(xr[i].z); acc[8 * i + 5] += bf_hi(xr[i].z); acc[8 * i + 6] += bf_lo(xr[i].w); acc[8 * i + 7] += bf_hi(xr[i].w);
        }
        uint4 st = local_stats(acc);
        st.x = set_tag(st.x, tag);
        if (qc == 0) st_ll(g_arena + c * ARENA + AR_STATS + (slab * 8 + j) * 8 + qr, st);
#pragma unroll
        for (int i = 0; i < 4; i++) {
          x1own[i] = pack8(&acc[8 * i]);
          x1own[i].x = set_tag(x1own[i].x, 0u);
          st_ll(xp + i * 32, x1own[i]);
        }
      }
      uint4 hs[14];
      {
        PHASE_VARS;
        float acc[128];
        uint4 A[3][4];
        const uint4* xs = g_arena + c * ARENA + AR_XRAW + ((slab) * 32) * 32 + lane;
        const uint4* sp = g_arena + c * ARENA + AR_STATS + (slab * 8 + 2 * qc) * 8 + qr;
        const uint32_t sm = areg + t128 * 16;
        uint32_t rl2, rh2, bl2, bh2;
        float cl, ch;
        auto xsrc = [&](int p) { return xs + ((j + p) & 7) * 128; };
        {
          uint4 p[2];
#pragma unroll
          for (int k = 0; k < 4; k++) A[0][k] = x1own[k];
          spin_for(L ? D_ST1 : D_ST0);
          p[0] = ld_ll(sp); p[1] = ld_ll(sp + 8);
          load_pk<4>(A[1], xsrc(1));
          for (uint32_t n = 0; !ok_pk<2>(p, tag) && n < SPIN_LIMIT; n++) { p[0] = ld_ll(sp); p[1] = ld_ll(sp + 8); }
          float ml, rl, mh, rh;
          combine_stats(p[0], p[1], ml, rl, mh, rh);
          rl2 = pack2(rl, rl); rh2 = pack2(rh, rh);
          const float rlb = bf_lo(rl2), rhb = bf_lo(rh2);
          bl2 = pack2(-ml * rlb, -ml * rlb); bh2 = pack2(-mh * rhb, -mh * rhb);
          cl = rl / rlb; cl *= cl; ch = rh / rhb; ch *= ch;
        }
        auto normalise = [&](uint4 (&xb)[4], int kb) {
#pragma unroll
          for (int k = 0; k < 4; k++) {
            xb[k].x = hfma2(xb[k].x, rl2, bl2); xb[k].y = hfma2(xb[k].y, rh2, bh2);
            xb[k].z = hfma2(xb[k].z, rl2, bl2); xb[k].w = hfma2(xb[k].w, rh2, bh2);
            sts128(sm + (kb * 4 + k) * 2048, xb[k]);
          }
        };
        normalise(A[0], 0);
        static_for<0, 8>([&](auto I) {
          constexpr int kb = I.value;
          cons_acquire<ST_G1 + 2 * kb>(sbase, L);
          wg_fence();
          wgmma_n256<kb == 0, 0>(acc, A[kb % 3][0], st_desc<ST_G1 + 2 * kb, 2048, 4096, 1024, 1>(0));
          wgmma_n256<false, 0>(acc, A[kb % 3][1], st_desc<ST_G1 + 2 * kb, 2048, 4096, 1024, 1>(1));
          wg_commit();
          cons_acquire<ST_G1 + 2 * kb + 1>(sbase, L);
          __syncwarp();
          wg_fence();
          wgmma_n256<false, 0>(acc, A[kb % 3][2], st_desc<ST_G1 + 2 * kb + 1, 2048, 4096, 1024, 1>(0));
          wgmma_n256<false, 0>(acc, A[kb % 3][3], st_desc<ST_G1 + 2 * kb + 1, 2048, 4096, 1024, 1>(1));
          wg_commit();
          wg_wait<1>();
          if constexpr (kb > 0) {
            keep4(A[(kb + 2) % 3]);
            cons_release<ST_G1 + 2 * kb - 1>(sbase, lane);
          }
          cons_release<ST_G1 + 2 * kb>(sbase, lane);
          if constexpr (kb + 1 < 8) ensure_pk<4>(A[(kb + 1) % 3], xsrc(kb + 1), 0u);
          if constexpr (kb + 2 < 8) load_pk<4>(A[(kb + 2) % 3], xsrc(kb + 2));
          if constexpr (kb + 1 < 8) normalise(A[(kb + 1) % 3], kb + 1);
        });
        wg_wait<0>();
        fence_acc(acc);
        keep4(A[1]);
        cons_release<ST_G1 + 15>(sbase, lane);
        uint4 B[3][4];
#pragma unroll
        for (int k = 0; k < 4; k++) { B[0][k] = lds128(sm + k * 2048); B[1][k] = lds128(sm + (4 + k) * 2048); }
#pragma unroll
        for (int s = 0; s < 8; s++) hs[s] = glu8<32>(&acc[64 * (s >> 2) + 8 * (s & 3)], cl, ch);
        float acc2[96];
        const uint32_t hdst = mapa(sm, cbit ^ 1);
        const uint32_t hbar1 = mapa(bars + BAR_HRECV + 16 * g, cbit ^ 1);
        if (t128 == 0) { mbar_expect_tx(bars + BAR_HRECV + 16 * g, 8 * 2048); mbar_expect_tx(bars + BAR_HRECV + 16 * g + 8, 6 * 2048); }
        static_for<0, 8>([&](auto I) {
          constexpr int kb = I.value;
          cons_acquire<ST_G2 + kb>(sbase, L);
          wg_fence();
          static_for<0, 4>([&](auto K) {
            constexpr int k = K.value;
            wgmma_n128<kb == 0 && k == 0, 0>(acc2, B[kb % 3][k], st_desc<ST_G2 + kb, 2048, 8192, 1024, 1>(k));
            wgmma_n64<kb == 0 && k == 0, 64>(acc2, B[kb % 3][k], st_desc<ST_G2 + kb, 1024, 4096, 512, 2>(k) + (16384 >> 4));
          });
          wg_commit();
          if constexpr (kb > 0) {
            wg_wait<1>();
            keep4(B[(kb + 2) % 3]);
            cons_release<ST_G2 + kb - 1>(sbase, lane);
          }
          if constexpr (kb + 2 < 8) {
#pragma unroll
            for (int k = 0; k < 4; k++) B[(kb + 2) % 3][k] = lds128(sm + ((kb + 2) * 4 + k) * 2048);
          }
          if constexpr (kb == 2) {
            keep4(B[0]);
            __syncwarp();
            if (lane == 0) mbar_arrive_remote(mapa(bars + BAR_HREADY + 8 * g, cbit ^ 1));
          }
          if constexpr (kb >= 4) {
            if constexpr (kb == 4) mbar_wait(bars + BAR_HREADY + 8 * g, L);
            st_async128(hdst + (2 * kb - 8) * 2048, hs[2 * kb - 8], hbar1);
            st_async128(hdst + (2 * kb - 7) * 2048, hs[2 * kb - 7], hbar1);
          }
        });
        wg_wait<0>();
        fence_acc(acc2);
        keep4(B[1]);
        cons_release<ST_G2 + 7>(sbase, lane);
#pragma unroll
        for (int s = 0; s < 4; s++) hs[8 + s] = glu8<32>(&acc2[8 * s], cl, ch);
#pragma unroll
        for (int s = 0; s < 2; s++) hs[12 + s] = glu8<16>(&acc2[64 + 8 * s], cl, ch);
      }
      {
        PHASE_VARS;
        const uint32_t hdst = mapa(areg + t128 * 16, cbit ^ 1);
        const uint32_t hbar2 = mapa(bars + BAR_HRECV + 16 * g + 8, cbit ^ 1);
        uint4* pd = g_arena + c * ARENA + AR_PART + (((slab * 2 + cbit) * 4 + ca) * 16) * 32 + lane;
        const uint4* ps = g_arena + c * ARENA + AR_PART + (((j * 2 + g) * 4) * 16 + w) * 32 + lane;
        auto fetch_partials = [&](int q) {
#pragma unroll
          for (int src = 0; src < 4; src++) cp_async16(areg + t128 * 16 + (14 + 4 * q + src) * 2048, ps + src * (16 * 32) + q * 128);
        };
        uint4 hb[7];
        float a0[32], a1[32], a2[32], a3[32];
        auto publish = [&](float (&a)[32], int q, int s0, int s1) {
#pragma unroll
          for (int s = s0; s < s1; s++) {
            uint4 o = pack8(&a[8 * s]);
            o.x = set_tag(o.x, tag);
            st_ll(pd + (4 * q + s) * 32, o);
          }
        };
        static_for<0, 16>([&](auto I) {
          constexpr int i = I.value, q = dn_q(i), par = dn_par(i), kh = dn_kh(i);
          auto mm = [&](auto K) {
            constexpr int k = decltype(K)::value;
            constexpr bool init = (k == 0 && par == 0 && kh == 0);
            constexpr uint64_t db = st_desc<ST_DN + i, 2048, 8192, 1024, 1>(k);
            if constexpr (q == 0) { if constexpr (par) wgmma_n64<init, 0>(a0, hb[k], db); else wgmma_n64<init, 0>(a0, hs[7 * kh + k], db); }
            if constexpr (q == 1) { if constexpr (par) wgmma_n64<init, 0>(a1, hb[k], db); else wgmma_n64<init, 0>(a1, hs[7 * kh + k], db); }
            if constexpr (q == 2) { if constexpr (par) wgmma_n64<init, 0>(a2, hb[k], db); else wgmma_n64<init, 0>(a2, hs[7 * kh + k], db); }
            if constexpr (q == 3) { if constexpr (par) wgmma_n64<init, 0>(a3, hb[k], db); else wgmma_n64<init, 0>(a3, hs[7 * kh + k], db); }
          };
          cons_acquire<ST_DN + i>(sbase, L);
          wg_fence();
          mm(IC<0>{}); mm(IC<1>{}); mm(IC<2>{}); mm(IC<3>{}); mm(IC<4>{}); mm(IC<5>{}); mm(IC<6>{});
          wg_commit();
          if constexpr (i > 0) { wg_wait<1>(); cons_release<ST_DN + i - 1>(sbase, lane); }
          if constexpr (i < 3) {
            st_async128(hdst + (8 + 2 * i) * 2048, hs[8 + 2 * i], hbar2);
            st_async128(hdst + (9 + 2 * i) * 2048, hs[9 + 2 * i], hbar2);
          }
          constexpr int n = i + 1;
          if constexpr (n < 16 && dn_par(n) && n != 4 && n != 7) {
            if constexpr (n == 2) { mbar_wait(bars + BAR_HRECV + 16 * g, L); }
            if constexpr (n == 6) { mbar_wait(bars + BAR_HRECV + 16 * g + 8, L); }
#pragma unroll
            for (int k = 0; k < 7; k++) { if constexpr (n != 2) keep(hb[k]); hb[k] = lds128(areg + t128 * 16 + (7 * dn_kh(n) + k) * 2048); }
          }
          if constexpr (i == 7) { fence_acc(a0); publish(a0, 0, 0, 4); }
          if constexpr (i == 8) { fence_acc(a1); publish(a1, 1, 0, 2); }
          if constexpr (i == 9) publish(a1, 1, 2, 4);
          if constexpr (i == 12) { fence_acc(a2); publish(a2, 2, 0, 2); }
          if constexpr (i == 13) publish(a2, 2, 2, 4);
          if constexpr (i == 11) fetch_partials(0);
          if constexpr (i == 12) fetch_partials(1);
        });
        wg_wait<0>();
        fence_acc(a3);
#pragma unroll
        for (int k = 0; k < 7; k++) { keep(hb[k]); keep(hs[7 + k]); }
        cons_release<NSTAGE - 1>(sbase, lane);
        {
          uint4* p3 = g_arena + c * ARENA + AR_O + (slab * 32 + (cbit * 4 + ca) * 4) * 32 + lane;
#pragma unroll
          for (int s = 0; s < 4; s++) { uint4 o = pack8(&a3[8 * s]); o.x &= ~1u; st_ll(p3 + s * 32, o); }
        }
      }
      {
        PHASE_VARS;
        const uint4* xq = g_arena + c * ARENA + AR_XRAW + (j * 32 + 16 * g + w) * 32 + lane;
        const uint4* ps = g_arena + c * ARENA + AR_PART + (((j * 2 + g) * 4) * 16 + w) * 32 + lane;
        const uint32_t sm = areg + t128 * 16;
        uint4 xr[4];
        float v[32];
#pragma unroll
        for (int i = 0; i < 4; i++) xr[i] = ld_ll(xq + i * 128);
        auto add_group = [&](uint4 (&P)[4], int i) {
          float d[8] = {0, 0, 0, 0, 0, 0, 0, 0};
#pragma unroll
          for (int src = 0; src < 4; src++) {
            const uint4 p = P[src];
            d[0] += bf_lo(p.x); d[1] += bf_hi(p.x); d[2] += bf_lo(p.y); d[3] += bf_hi(p.y);
            d[4] += bf_lo(p.z); d[5] += bf_hi(p.z); d[6] += bf_lo(p.w); d[7] += bf_hi(p.w);
          }
#pragma unroll
          for (int k = 0; k < 8; k++) v[8 * i + k] = d[k];
        };
        uint4 P2g[4];
#pragma unroll
        for (int k = 0; k < 4; k++) P2g[k] = ld_ll(ps + k * (16 * 32) + 2 * 128);
        cp_wait_all();
        {
          uint4 P[2][4];
#pragma unroll
          for (int k = 0; k < 8; k++) P[k >> 2][k & 3] = lds128(sm + (14 + k) * 2048);
          for (uint32_t n = 0; !ok_pk<8>(&P[0][0], tag) && n < SPIN_LIMIT; n++) {
#pragma unroll
            for (int k = 0; k < 8; k++) P[k >> 2][k & 3] = ld_ll(ps + (k & 3) * (16 * 32) + (k >> 2) * 128);
          }
          add_group(P[0], 0); add_group(P[1], 1);
        }
        for (uint32_t n = 0; !ok_pk<4>(P2g, tag) && n < SPIN_LIMIT; n++) {
#pragma unroll
          for (int k = 0; k < 4; k++) P2g[k] = ld_ll(ps + k * (16 * 32) + 2 * 128);
        }
        add_group(P2g, 2);
        for (uint32_t n = 0; !ok_pk<4>(xr, 0u) && n < SPIN_LIMIT; n++) {
#pragma unroll
          for (int i = 0; i < 4; i++) xr[i] = ld_ll(xq + i * 128);
        }
        spin_for(L ? D_PT1 : D_PT0);
        {
          uint4 P[4];
          const uint4* p3 = g_arena + c * ARENA + AR_O + (j * 32 + 16 * g + w) * 32 + lane;
          uint32_t n = 0;
          do {
#pragma unroll
            for (int k = 0; k < 4; k++) P[k] = ld_ll(p3 + k * 128);
          } while (!ok_pk<4>(P, 0u) && ++n < SPIN_LIMIT);
          add_group(P, 3);
        }
#pragma unroll
        for (int i = 0; i < 4; i++) {
          v[8 * i + 0] += bf_lo(xr[i].x); v[8 * i + 1] += bf_hi(xr[i].x); v[8 * i + 2] += bf_lo(xr[i].y); v[8 * i + 3] += bf_hi(xr[i].y);
          v[8 * i + 4] += bf_lo(xr[i].z); v[8 * i + 5] += bf_hi(xr[i].z); v[8 * i + 6] += bf_lo(xr[i].w); v[8 * i + 7] += bf_hi(xr[i].w);
        }
        if (L == 1) {
          const uint32_t tile = sm;
          const uint32_t tw = areg + w * 512 + ((lane & 7) + 8 * ((lane >> 3) & 1)) * 32 + (lane >> 4) * 16;
          uint4* op = reinterpret_cast<uint4*>(out + (size_t)(slab_row0(c, j >> 2, j & 3) + 2 * (lane >> 1)) * 512 + (16 * g + w) * 16 + (lane & 1) * 8);
#pragma unroll
          for (int i = 0; i < 4; i++) {
            const uint4 o = pack8(&v[8 * i]);
            asm volatile("stmatrix.sync.aligned.m8n8.x4.shared.b16 [%0], {%1,%2,%3,%4};" ::"r"(tw + i * 2048), "r"(o.x), "r"(o.y), "r"(o.z), "r"(o.w) : "memory");
          }
          __syncwarp();
#pragma unroll
          for (int i = 0; i < 4; i++) op[i * 8] = lds128(tile + i * 2048);
        }
#pragma unroll
        for (int i = 0; i < 32; i++) vres[i] = v[i];
      }
    }
  }
}

typedef CUresult (*EncodeFn)(CUtensorMap*, CUtensorMapDataType, cuuint32_t, void*, const cuuint64_t*, const cuuint64_t*,
                             const cuuint32_t*, const cuuint32_t*, CUtensorMapInterleave, CUtensorMapSwizzle,
                             CUtensorMapL2promotion, CUtensorMapFloatOOBfill);

void encode(EncodeFn fn, CUtensorMap* m, int rank, const void* base, const cuuint64_t* dims, const cuuint64_t* strides,
            const cuuint32_t* box, CUtensorMapSwizzle sw) {
  cuuint32_t es[5] = {1, 1, 1, 1, 1};
  fn(m, CU_TENSOR_MAP_DATA_TYPE_BFLOAT16, (cuuint32_t)rank, const_cast<void*>(base), dims, strides, box, es,
     CU_TENSOR_MAP_INTERLEAVE_NONE, sw, CU_TENSOR_MAP_L2_PROMOTION_L2_256B, CU_TENSOR_MAP_FLOAT_OOB_FILL_NONE);
}

}


extern "C" void kernel_launch(void* const* d_in, const int* in_sizes, int n_in, void* d_out, int out_size) {
  (void)in_sizes; (void)n_in; (void)out_size;
  const __nv_bfloat16* x = (const __nv_bfloat16*)d_in[0];
  const char* wqkv = (const char*)d_in[1];
  const char* wo = (const char*)d_in[2];
  const char* wg = (const char*)d_in[4];
  const char* wu = (const char*)d_in[5];
  const char* wd = (const char*)d_in[6];

  static EncodeFn fn = nullptr;
  if (!fn) {
    void* p = nullptr;
    cudaDriverEntryPointQueryResult st;
    cudaGetDriverEntryPoint("cuTensorMapEncodeTiled", &p, cudaEnableDefault, &st);
    fn = (EncodeFn)p;
    cudaFuncSetAttribute(fused_kernel, cudaFuncAttributeMaxDynamicSharedMemorySize, SMEM_BYTES);
  }
  CUtensorMap m_qkv, m_wo, m_gu2, m_gu1, m_guh, m_wd112, m_wd80, m_wd32;
  {
    cuuint64_t dims[3] = {512, 512, 3}, str[2] = {3072, 1024};
    cuuint32_t box[3] = {64, 64, 3};
    encode(fn, &m_qkv, 3, wqkv, dims, str, box, CU_TENSOR_MAP_SWIZZLE_128B);
  }
  {
    cuuint64_t dims[2] = {512, 512}, str[1] = {1024};
    cuuint32_t box[2] = {64, 128};
    encode(fn, &m_wo, 2, wo, dims, str, box, CU_TENSOR_MAP_SWIZZLE_128B);
  }
  {
    const char* lo = wg < wu ? wg : wu;
    cuuint64_t diff = (cuuint64_t)(wg < wu ? wu - wg : wg - wu);
    cuuint64_t dims[4] = {1792, 512, 2, 2}, str[3] = {3584, diff, 128};
    cuuint32_t box2[4] = {64, 32, 2, 2}, box1[4] = {64, 64, 2, 1}, boxh[3] = {32, 64, 2};
    encode(fn, &m_gu2, 4, lo, dims, str, box2, CU_TENSOR_MAP_SWIZZLE_128B);
    encode(fn, &m_gu1, 4, lo, dims, str, box1, CU_TENSOR_MAP_SWIZZLE_128B);
    encode(fn, &m_guh, 3, lo, dims, str, boxh, CU_TENSOR_MAP_SWIZZLE_64B);
  }
  {
    cuuint64_t dims[2] = {512, 1792}, str[1] = {1024};
    cuuint32_t b112[2] = {64, 112}, b80[2] = {64, 80}, b32[2] = {64, 32};
    encode(fn, &m_wd112, 2, wd, dims, str, b112, CU_TENSOR_MAP_SWIZZLE_128B);
    encode(fn, &m_wd80, 2, wd, dims, str, b80, CU_TENSOR_MAP_SWIZZLE_128B);
    encode(fn, &m_wd32, 2, wd, dims, str, b32, CU_TENSOR_MAP_SWIZZLE_128B);
  }
  cudaLaunchConfig_t cfg = {};
  cfg.gridDim = dim3(128);
  cfg.blockDim = dim3(NTHREADS);
  cfg.dynamicSmemBytes = SMEM_BYTES;
  cfg.stream = cudaStreamPerThread;
  cudaLaunchAttribute at[1];
  at[0].id = cudaLaunchAttributeClusterDimension;
  at[0].val.clusterDim.x = 2; at[0].val.clusterDim.y = 1; at[0].val.clusterDim.z = 1;
  cfg.attrs = at; cfg.numAttrs = 1;
  cudaLaunchKernelEx(&cfg, fused_kernel, m_qkv, m_wo, m_gu2, m_gu1, m_guh, m_wd112, m_wd80, m_wd32, x, (__nv_bfloat16*)d_out
  );
}
```
